```python
import torch

def _softmax(x, axis=-1):
    return torch.softmax(x, dim=axis)

def _gelu(x):
    return torch.nn.functional.gelu(x, approximate='tanh')

def _silu(x):
    return torch.nn.functional.silu(x)

def _sigmoid(x):
    return torch.sigmoid(x)

def _layernorm(x, axis=-1, eps=1e-05):
    m = x.mean(dim=axis, keepdim=True)
    v = x.var(dim=axis, keepdim=True, unbiased=False)
    return (x - m) / torch.sqrt(v + eps)

def _scatter_add(tgt, idx, src, axis=0):
    return tgt.clone().index_add_(axis, idx, src)

def _segment_sum(src, seg, n):
    out = torch.zeros((n,) + src.shape[1:], dtype=src.dtype)
    return out.index_add_(0, seg, src)

def _pad(x, pw):
    flat = tuple((v for pair in reversed(pw) for v in pair))
    return torch.nn.functional.pad(x, flat)
kernel_name = 'adaLN_cond__ssm_conv_h3__glu_gated_swiglu__prompt'

def setup_inputs():

    _w = lambda a: (lambda t: t.to(torch.bfloat16) if t.is_floating_point() else t)(torch.as_tensor(a))

    def _A_setup():
        B, S, D = (1, 2048, 640)
        ks = 4
        return {'q': _w((lambda *s: torch.randn(*s, dtype=torch.bfloat16) * 0.05)(B, S, D)), 'k': _w((lambda *s: torch.randn(*s, dtype=torch.bfloat16) * 0.8)(B, S, D)), 'v': _w((lambda *s: torch.randn(*s, dtype=torch.bfloat16) * 0.8)(B, S, D)), 'shift_k': _w((lambda *s: torch.randn(*s, dtype=torch.bfloat16) * 0.8)(D, ks) * 0.5), 'ssm_k': _w((lambda *s: torch.randn(*s, dtype=torch.bfloat16) * 0.8)(D, S) * (1.0 / S ** 0.5)), 'ssm_D': _w((lambda *s: torch.randn(*s, dtype=torch.bfloat16) * 0.8)(D))}
    _A_in = _A_setup()

    def _B_setup():
        B, S, D, F = (1, 2048, 640, 1536)
        return {'x': _w((lambda *s: torch.randn(*s, dtype=torch.bfloat16) * 0.05)(B, S, D)), 'w1': _w((lambda *s: torch.randn(*s, dtype=torch.bfloat16) * 0.8)(D, F) * (2.0 / D) ** 0.5), 'w3': _w((lambda *s: torch.randn(*s, dtype=torch.bfloat16) * 0.8)(D, F) * (2.0 / D) ** 0.5), 'w2': _w((lambda *s: torch.randn(*s, dtype=torch.bfloat16) * 0.8)(F, D) * (2.0 / F) ** 0.5)}
    _B_in = _B_setup()
    return {'A_q': _A_in['q'], 'A_k': _A_in['k'], 'A_v': _A_in['v'], 'A_shift_k': _A_in['shift_k'], 'A_ssm_k': _A_in['ssm_k'], 'A_ssm_D': _A_in['ssm_D'], 'B_x': _B_in['x'], 'B_w1': _B_in['w1'], 'B_w3': _B_in['w3'], 'B_w2': _B_in['w2'], 'c': _w((lambda *s: torch.randn(*s, dtype=torch.bfloat16) * 0.2)(1, 640) * 8.0), 'w_mod': _w((lambda *s: torch.randn(*s, dtype=torch.bfloat16) * 0.2)(640, 6 * 640) * 640 ** (-0.5) * 8.0)}

def reference(A_q, A_k, A_v, A_shift_k, A_ssm_k, A_ssm_D, B_x, B_w1, B_w3, B_w2, c, w_mod):

    def _A_ref(q, k, v, shift_k, ssm_k, ssm_D):
        B, S, D = q.shape
        ks = shift_k.shape[-1]
        k_pad = _pad(k, ((0, 0), (ks - 1, 0), (0, 0)))
        k_shift = torch.zeros_like(k)
        for t in range(ks):
            k_shift = k_shift + k_pad[:, t:t + S, :] * shift_k[:, ks - 1 - t][None, None, :]
        kv = k_shift * v
        L = 2 * S
        kv_pad = _pad(kv, ((0, 0), (0, S), (0, 0)))
        kf_pad = _pad(ssm_k, ((0, 0), (0, S)))
        kv_f = (lambda x, axes=(-2, -1): torch.fft.rfft2(x.float(), dim=axes))(kv_pad[:, None, :, :], axes=(1, 2))
        kf_f = (lambda x, axes=(-2, -1): torch.fft.rfft2(x.float(), dim=axes))(kf_pad[:, None, :], axes=(1, 2))
        kf_f = (lambda x, *d: x.permute(*d))(kf_f, 1, 2, 0)
        y_f = kv_f * kf_f[None, :, :, :]
        y = (lambda x, s, axes=(-2, -1): torch.fft.irfft2(x, s=s, dim=axes).to(torch.bfloat16))(y_f, (1, L), axes=(1, 2))[:, 0, :S, :]
        y = y + kv * ssm_D[None, None, :]
        return q * y

    def _B_ref(x, w1, w3, w2):
        gate = torch.einsum('bsd,df->bsf', x, w1)
        up = torch.einsum('bsd,df->bsf', x, w3)
        h = _silu(gate) * up
        out = torch.einsum('bsf,fd->bsd', h, w2)
        return out
    x = A_q
    mod = (_silu(c) @ w_mod).reshape(c.shape[0], 6, 1, -1)
    sa, ca, ga, sb, cb, gb = (mod[:, 0].clone(), mod[:, 1].clone(), mod[:, 2].clone(), mod[:, 3].clone(), mod[:, 4].clone(), mod[:, 5].clone())
    h = _layernorm(x, axis=-1) * (1 + ca) + sa
    x = x + ga * _A_ref(h, A_k, A_v, A_shift_k, A_ssm_k, A_ssm_D)
    h = _layernorm(x, axis=-1) * (1 + cb) + sb
    x = x + gb * _B_ref(h, B_w1, B_w3, B_w2)
    return x
```

```cpp
#include <cuda_runtime.h>
#include <cuda.h>
#include <cuda_bf16.h>
#include <stdint.h>
#include <stdlib.h>

typedef __nv_bfloat16 bf16;
constexpr int S_ = 2048, D_ = 640, F_ = 1536;

struct Scratch {
  uint32_t st1[2][1024];
  uint32_t st2[32][4][128];
  uint2 modc[128][32];
  uint2 modv[3][D_];
  uint32_t uv[8][3072];
  unsigned hint[9][8][32];
  unsigned xsh[5][8][32], hhf[256 * 8];
  uint4 xr[D_ * 256];
  uint4 qt[D_ * 256];
  uint4 xs[D_ * 256];
  uint4 x1[2][D_ * 256];
  uint4 hh[32 * 8 * 1536];
};
__device__ __align__(1024) Scratch g_s;

__device__ __forceinline__ uint32_t smem_u32(const void* p) { return (uint32_t)__cvta_generic_to_shared(p); }
__device__ __forceinline__ void mbar_expect_tx(uint32_t b, uint32_t n) { asm volatile("mbarrier.arrive.expect_tx.shared::cta.b64 _, [%0], %1;" ::"r"(b), "r"(n) : "memory"); }
__device__ __forceinline__ void mbar_arrive(uint32_t b) { asm volatile("mbarrier.arrive.shared::cta.b64 _, [%0];" ::"r"(b) : "memory"); }
__device__ __forceinline__ void mbar_arrive2(uint32_t b) { asm volatile("mbarrier.arrive.shared::cta.b64 _, [%0], 2;" ::"r"(b) : "memory"); }
__device__ __forceinline__ uint32_t mapa(uint32_t a, uint32_t cta) { uint32_t r; asm volatile("mapa.shared::cluster.u32 %0, %1, %2;" : "=r"(r) : "r"(a), "r"(cta)); return r; }
__device__ __forceinline__ void mbar_arrive_remote(uint32_t rb) { asm volatile("mbarrier.arrive.shared::cluster.b64 _, [%0];" ::"r"(rb) : "memory"); }
constexpr int SPIN_LIMIT = 1 << 16;
template <int N> __device__ __forceinline__ void mbar_init(uint32_t b, uint32_t count) {
#pragma unroll
  for (int i = 0; i < N; i++) asm volatile("mbarrier.init.shared::cta.b64 [%0], %1;" ::"r"(b + 8 * i), "r"(count) : "memory");
}
__device__ __forceinline__ bool elect() { uint32_t p; asm volatile("{.reg .pred q; elect.sync _|q, 0xffffffff; selp.u32 %0, 1, 0, q;}" : "=r"(p)); return p; }
__device__ __forceinline__ void arrive1(uint32_t b) { __syncwarp(); if (elect()) mbar_arrive(b); }
__device__ __forceinline__ bool mbar_test(uint32_t b) {
  uint32_t ok;
  asm volatile("{.reg .pred p; mbarrier.test_wait.parity.shared::cta.b64 p, [%1], 0; selp.u32 %0,1,0,p;}" : "=r"(ok) : "r"(b) : "memory");
  return ok;
}
#define WAIT_LOOP(sem) "{.reg .pred p; mov.u32 %0, 0; W: mbarrier.try_wait.parity" sem ".shared::cta.b64 p, [%1], %2; @p bra.uni D; add.u32 %0, %0, 1; setp.lt.u32 p, %0, %3; @p bra.uni W; D:}"
__device__ __forceinline__ void mbar_wait(uint32_t b, uint32_t ph = 0) {
  int it;
  asm volatile(WAIT_LOOP("") : "=&r"(it) : "r"(b), "r"(ph), "n"(SPIN_LIMIT) : "memory");
}
__device__ __forceinline__ void mbar_wait_cluster(uint32_t b, uint32_t ph = 0) {
  int it;
  asm volatile(WAIT_LOOP(".acquire.cluster") : "=&r"(it) : "r"(b), "r"(ph), "n"(SPIN_LIMIT) : "memory");
}
__device__ __forceinline__ void wait_clock(uint32_t t) {
  asm volatile("{.reg .pred p; .reg .s32 d; W: mov.u32 d, %%clock; sub.s32 d, d, %0; setp.lt.s32 p, d, 0; @p bra.uni W;}" ::"r"(t) : "memory");
}
__device__ __forceinline__ void tma2d(uint32_t dst, const CUtensorMap* m, int c0, int c1, uint32_t bar) {
  asm volatile("cp.async.bulk.tensor.2d.shared::cluster.global.mbarrier::complete_tx::bytes [%0], [%1, {%3,%4}], [%2];" ::"r"(dst), "l"(m), "r"(bar), "r"(c0), "r"(c1) : "memory");
}
__device__ __forceinline__ void tma3d(uint32_t dst, const CUtensorMap* m, int c0, int c1, int c2, uint32_t bar) {
  asm volatile("cp.async.bulk.tensor.3d.shared::cluster.global.mbarrier::complete_tx::bytes [%0], [%1, {%3,%4,%5}], [%2];" ::"r"(dst), "l"(m), "r"(bar), "r"(c0), "r"(c1), "r"(c2) : "memory");
}
__device__ __forceinline__ void tma5d(uint32_t dst, const CUtensorMap* m, int c0, int c4, uint32_t bar) {
  asm volatile("cp.async.bulk.tensor.5d.shared::cluster.global.mbarrier::complete_tx::bytes [%0], [%1, {%4,%3,%3,%3,%5}], [%2];" ::"r"(dst), "l"(m), "r"(bar), "r"(0), "r"(c0), "r"(c4) : "memory");
}
__device__ __forceinline__ void tma2d_store(const CUtensorMap* m, int c0, int c1, uint32_t src) {
  asm volatile("cp.async.bulk.tensor.2d.global.shared::cta.bulk_group [%0, {%2,%3}], [%1];" ::"l"(m), "r"(src), "r"(c0), "r"(c1) : "memory");
}
__device__ __forceinline__ void bulk_load(uint32_t dst, const void* src, uint32_t bytes, uint32_t bar) {
  asm volatile("cp.async.bulk.shared::cluster.global.mbarrier::complete_tx::bytes [%0], [%1], %2, [%3];" ::"r"(dst), "l"(src), "r"(bytes), "r"(bar) : "memory");
}
__device__ __forceinline__ void prefetch_map(const CUtensorMap* m) { asm volatile("prefetch.tensormap [%0];" ::"l"(m) : "memory"); }
__device__ __forceinline__ void bulk_commit() { asm volatile("cp.async.bulk.commit_group;" ::: "memory"); }
__device__ __forceinline__ void bulk_wait_read() { asm volatile("cp.async.bulk.wait_group.read 0;" ::: "memory"); }
__device__ __forceinline__ void fence_async_smem() { asm volatile("fence.proxy.async.shared::cta;" ::: "memory"); }
__device__ __forceinline__ void fence_async_all() { asm volatile("fence.proxy.async.global;" ::: "memory"); }
__device__ __forceinline__ void named_bar(int id, int n) { asm volatile("bar.sync %0, %1;" ::"r"(id), "r"(n) : "memory"); }
__device__ __forceinline__ bool bar_all(int id, bool v) {
  uint32_t r;
  asm volatile("{.reg .pred p, q; setp.ne.u32 p, %2, 0; bar.red.and.pred q, %1, 128, p; selp.u32 %0, 1, 0, q;}" : "=r"(r) : "r"(id), "r"((uint32_t)v) : "memory");
  return __all_sync(~0u, r);
}
__device__ __forceinline__ void cluster_wait() { asm volatile("barrier.cluster.wait.aligned;" ::: "memory"); }
__device__ __forceinline__ void wg_fence() { asm volatile("wgmma.fence.sync.aligned;" ::: "memory"); }
__device__ __forceinline__ void wg_commit() { asm volatile("wgmma.commit_group.sync.aligned;" ::: "memory"); }
template <int N> __device__ __forceinline__ void wg_wait() { asm volatile("wgmma.wait_group.sync.aligned %0;" ::"n"(N) : "memory"); }
template <int N> __device__ __forceinline__ void fence_regs(float (&a)[N]) {
#pragma unroll
  for (int i = 0; i < N; i++) asm volatile("" : "+f"(a[i])::"memory");
}
__device__ __forceinline__ uint64_t mkdesc(uint32_t addr, uint32_t lbo, uint32_t sbo, uint32_t swz) {
  uint32_t lo = (addr >> 4) | ((lbo >> 4) << 16), hi = (sbo >> 4) | (swz << 30);
  return ((uint64_t)hi << 32) | lo;
}
__device__ __forceinline__ void stmatrix_x4(uint32_t a, uint32_t r0, uint32_t r1, uint32_t r2, uint32_t r3) {
  asm volatile("stmatrix.sync.aligned.m8n8.x4.shared.b16 [%0], {%1,%2,%3,%4};" ::"r"(a), "r"(r0), "r"(r1), "r"(r2), "r"(r3) : "memory");
}
__device__ __forceinline__ void stmatrix_x4_t(uint32_t a, uint32_t r0, uint32_t r1, uint32_t r2, uint32_t r3) {
  asm volatile("stmatrix.sync.aligned.m8n8.x4.trans.shared.b16 [%0], {%1,%2,%3,%4};" ::"r"(a), "r"(r0), "r"(r1), "r"(r2), "r"(r3) : "memory");
}
__device__ __forceinline__ void ldmatrix_x4_t(uint32_t* r, uint32_t a) {
  asm volatile("ldmatrix.sync.aligned.m8n8.x4.trans.shared.b16 {%0,%1,%2,%3}, [%4];" : "=r"(r[0]), "=r"(r[1]), "=r"(r[2]), "=r"(r[3]) : "r"(a) : "memory");
}
__device__ __forceinline__ uint32_t lds32(uint32_t a) { uint32_t v; asm volatile("ld.shared.b32 %0, [%1];" : "=r"(v) : "r"(a) : "memory"); return v; }
__device__ __forceinline__ uint2 lds64(uint32_t a) { uint2 v; asm volatile("ld.shared.v2.b32 {%0,%1}, [%2];" : "=r"(v.x), "=r"(v.y) : "r"(a) : "memory"); return v; }
__device__ __forceinline__ uint4 lds128(uint32_t a) { uint4 v; asm volatile("ld.shared.v4.b32 {%0,%1,%2,%3}, [%4];" : "=r"(v.x), "=r"(v.y), "=r"(v.z), "=r"(v.w) : "r"(a) : "memory"); return v; }
__device__ __forceinline__ void sts32(uint32_t a, uint32_t v) { asm volatile("st.shared.b32 [%0], %1;" ::"r"(a), "r"(v) : "memory"); }
__device__ __forceinline__ void sts64(uint32_t a, uint32_t x, uint32_t y) { asm volatile("st.shared.v2.b32 [%0], {%1,%2};" ::"r"(a), "r"(x), "r"(y) : "memory"); }
__device__ __forceinline__ void sts128(uint32_t a, uint32_t x, uint32_t y, uint32_t z, uint32_t w) { asm volatile("st.shared.v4.b32 [%0], {%1,%2,%3,%4};" ::"r"(a), "r"(x), "r"(y), "r"(z), "r"(w) : "memory"); }
__device__ __forceinline__ uint4 ld_relaxed128(const void* p) { uint4 v; asm volatile("ld.relaxed.gpu.global.v4.u32 {%0,%1,%2,%3}, [%4];" : "=r"(v.x), "=r"(v.y), "=r"(v.z), "=r"(v.w) : "l"(p) : "memory"); return v; }
__device__ __forceinline__ uint2 ld_relaxed64(const void* p) { uint2 v; asm volatile("ld.relaxed.gpu.global.v2.u32 {%0,%1}, [%2];" : "=r"(v.x), "=r"(v.y) : "l"(p) : "memory"); return v; }
__device__ __forceinline__ uint32_t ld_relaxed32(const void* p) { uint32_t v; asm volatile("ld.relaxed.gpu.global.u32 %0, [%1];" : "=r"(v) : "l"(p) : "memory"); return v; }
__device__ __forceinline__ void st_relaxed128(void* p, uint32_t x, uint32_t y, uint32_t z, uint32_t w) { asm volatile("st.relaxed.gpu.global.v4.u32 [%0], {%1,%2,%3,%4};" ::"l"(p), "r"(x), "r"(y), "r"(z), "r"(w) : "memory"); }
__device__ __forceinline__ void st_relaxed32(void* p, uint32_t x) { asm volatile("st.relaxed.gpu.global.u32 [%0], %1;" ::"l"(p), "r"(x) : "memory"); }
__device__ __forceinline__ void red_hint(unsigned* p) { asm volatile("red.relaxed.gpu.global.add.u32 [%0], 1;" ::"l"(p) : "memory"); }
__device__ __forceinline__ void publish(uint32_t* p, uint32_t x) { asm volatile("{.reg .b32 t; atom.relaxed.gpu.global.exch.b32 t, [%0], %1;}" ::"l"(p), "r"(x) : "memory"); }
__device__ __forceinline__ uint32_t ldg32(const void* p) { uint32_t v; asm volatile("ld.global.nc.L1::no_allocate.b32 %0, [%1];" : "=r"(v) : "l"(p)); return v; }
__device__ __forceinline__ uint32_t pack_bf16(float lo, float hi) { uint32_t r; asm("cvt.rn.bf16x2.f32 %0, %1, %2;" : "=r"(r) : "f"(hi), "f"(lo)); return r; }
__device__ __forceinline__ float bf_lo(uint32_t v) { return __uint_as_float(v << 16); }
__device__ __forceinline__ float bf_hi(uint32_t v) { return __uint_as_float(v & 0xFFFF0000u); }
__device__ __forceinline__ uint32_t bmul2(uint32_t a, uint32_t b) { uint32_t r; asm("mul.rn.bf16x2 %0, %1, %2;" : "=r"(r) : "r"(a), "r"(b)); return r; }
__device__ __forceinline__ uint32_t badd2(uint32_t a, uint32_t b) { uint32_t r; asm("add.rn.bf16x2 %0, %1, %2;" : "=r"(r) : "r"(a), "r"(b)); return r; }
__device__ __forceinline__ uint32_t bfma2(uint32_t a, uint32_t b, uint32_t c) { uint32_t r; asm("fma.rn.bf16x2 %0, %1, %2, %3;" : "=r"(r) : "r"(a), "r"(b), "r"(c)); return r; }
__device__ __forceinline__ uint32_t set_tag(uint32_t x, uint32_t mask, uint32_t e) { uint32_t r; asm("lop3.b32 %0, %1, %2, %3, 0xB8;" : "=r"(r) : "r"(x), "r"(mask), "r"(e)); return r; }
__device__ __forceinline__ uint32_t opaque(uint32_t x) { asm volatile("" : "+r"(x)); return x; }
__device__ __forceinline__ float rbf(float x) { return __bfloat162float(__float2bfloat16(x)); }
__device__ __forceinline__ float silu_f(float x) {
  float e, r;
  asm("ex2.approx.ftz.f32 %0, %1;" : "=f"(e) : "f"(x * -1.4426950408889634f));
  asm("rcp.approx.ftz.f32 %0, %1;" : "=f"(r) : "f"(1.f + e));
  return x * r;
}
__device__ __forceinline__ float silu2(float x) {
  float t;
  asm("tanh.approx.f32 %0, %1;" : "=f"(t) : "f"(x));
  return fmaf(x, t, x);
}
__device__ __forceinline__ void pin(int off, uint32_t x) { asm volatile("{.reg .pred p; setp.lt.s32 p, %0, 0; @p st.shared.b32 [%0], %1;}" ::"r"(off), "r"(x) : "memory"); }
__device__ __forceinline__ void pin4(int off, const uint32_t* x) { asm volatile("{.reg .pred p; setp.lt.s32 p, %0, 0; @p st.shared.v4.b32 [%0], {%1,%2,%3,%4};}" ::"r"(off), "r"(x[0]), "r"(x[1]), "r"(x[2]), "r"(x[3]) : "memory"); }
__device__ __forceinline__ void split(int x, int n) { asm volatile("{.reg .pred p; setp.eq.s32 p, %0, %1; @p trap;}" ::"r"(x), "r"(~n) : "memory"); }
__device__ __forceinline__ void ln_final(float s, float q, float& m, float& sd) {
  m = s * (1.f / D_);
  asm("sqrt.approx.f32 %0, %1;" : "=f"(sd) : "f"(rbf(rbf(fmaxf(fmaf(-m, m, q * (1.f / D_)), 0.f)) + 1e-5f)));
  sd = rbf(sd);
}
__device__ __forceinline__ float rcpf(float x) { float r; asm("rcp.approx.f32 %0, %1;" : "=f"(r) : "f"(x)); return r; }

__device__ __forceinline__ void wg_rs16_0(float* d, const uint32_t* a, uint64_t db, int sc) {
  asm volatile("{.reg .pred p; setp.ne.b32 p, %13, 0; wgmma.mma_async.sync.aligned.m64n16k16.f32.bf16.bf16 {%0,%1,%2,%3,%4,%5,%6,%7}, {%8,%9,%10,%11}, %12, p, 1, 1, 0;}"
    : "+f"(d[0]),"+f"(d[1]),"+f"(d[2]),"+f"(d[3]),"+f"(d[4]),"+f"(d[5]),"+f"(d[6]),"+f"(d[7]) : "r"(a[0]),"r"(a[1]),"r"(a[2]),"r"(a[3]),"l"(db),"r"(sc));
}
__device__ __forceinline__ void wg_rs32_0(float* d, const uint32_t* a, uint64_t db, int sc) {
  asm volatile("{.reg .pred p; setp.ne.b32 p, %21, 0; wgmma.mma_async.sync.aligned.m64n32k16.f32.bf16.bf16 {%0,%1,%2,%3,%4,%5,%6,%7,%8,%9,%10,%11,%12,%13,%14,%15}, {%16,%17,%18,%19}, %20, p, 1, 1, 0;}"
    : "+f"(d[0]),"+f"(d[1]),"+f"(d[2]),"+f"(d[3]),"+f"(d[4]),"+f"(d[5]),"+f"(d[6]),"+f"(d[7]),"+f"(d[8]),"+f"(d[9]),"+f"(d[10]),"+f"(d[11]),"+f"(d[12]),"+f"(d[13]),"+f"(d[14]),"+f"(d[15]) : "r"(a[0]),"r"(a[1]),"r"(a[2]),"r"(a[3]),"l"(db),"r"(sc));
}
__device__ __forceinline__ void wg_rs48_0(float* d, const uint32_t* a, uint64_t db, int sc) {
  asm volatile("{.reg .pred p; setp.ne.b32 p, %29, 0; wgmma.mma_async.sync.aligned.m64n48k16.f32.bf16.bf16 {%0,%1,%2,%3,%4,%5,%6,%7,%8,%9,%10,%11,%12,%13,%14,%15,%16,%17,%18,%19,%20,%21,%22,%23}, {%24,%25,%26,%27}, %28, p, 1, 1, 0;}"
    : "+f"(d[0]),"+f"(d[1]),"+f"(d[2]),"+f"(d[3]),"+f"(d[4]),"+f"(d[5]),"+f"(d[6]),"+f"(d[7]),"+f"(d[8]),"+f"(d[9]),"+f"(d[10]),"+f"(d[11]),"+f"(d[12]),"+f"(d[13]),"+f"(d[14]),"+f"(d[15]),"+f"(d[16]),"+f"(d[17]),"+f"(d[18]),"+f"(d[19]),"+f"(d[20]),"+f"(d[21]),"+f"(d[22]),"+f"(d[23]) : "r"(a[0]),"r"(a[1]),"r"(a[2]),"r"(a[3]),"l"(db),"r"(sc));
}
__device__ __forceinline__ void wg_rs64_0(float* d, const uint32_t* a, uint64_t db, int sc) {
  asm volatile("{.reg .pred p; setp.ne.b32 p, %37, 0; wgmma.mma_async.sync.aligned.m64n64k16.f32.bf16.bf16 {%0,%1,%2,%3,%4,%5,%6,%7,%8,%9,%10,%11,%12,%13,%14,%15,%16,%17,%18,%19,%20,%21,%22,%23,%24,%25,%26,%27,%28,%29,%30,%31}, {%32,%33,%34,%35}, %36, p, 1, 1, 0;}"
    : "+f"(d[0]),"+f"(d[1]),"+f"(d[2]),"+f"(d[3]),"+f"(d[4]),"+f"(d[5]),"+f"(d[6]),"+f"(d[7]),"+f"(d[8]),"+f"(d[9]),"+f"(d[10]),"+f"(d[11]),"+f"(d[12]),"+f"(d[13]),"+f"(d[14]),"+f"(d[15]),"+f"(d[16]),"+f"(d[17]),"+f"(d[18]),"+f"(d[19]),"+f"(d[20]),"+f"(d[21]),"+f"(d[22]),"+f"(d[23]),"+f"(d[24]),"+f"(d[25]),"+f"(d[26]),"+f"(d[27]),"+f"(d[28]),"+f"(d[29]),"+f"(d[30]),"+f"(d[31]) : "r"(a[0]),"r"(a[1]),"r"(a[2]),"r"(a[3]),"l"(db),"r"(sc));
}
__device__ __forceinline__ void wg_rs80_0(float* d, const uint32_t* a, uint64_t db, int sc) {
  asm volatile("{.reg .pred p; setp.ne.b32 p, %45, 0; wgmma.mma_async.sync.aligned.m64n80k16.f32.bf16.bf16 {%0,%1,%2,%3,%4,%5,%6,%7,%8,%9,%10,%11,%12,%13,%14,%15,%16,%17,%18,%19,%20,%21,%22,%23,%24,%25,%26,%27,%28,%29,%30,%31,%32,%33,%34,%35,%36,%37,%38,%39}, {%40,%41,%42,%43}, %44, p, 1, 1, 0;}"
    : "+f"(d[0]),"+f"(d[1]),"+f"(d[2]),"+f"(d[3]),"+f"(d[4]),"+f"(d[5]),"+f"(d[6]),"+f"(d[7]),"+f"(d[8]),"+f"(d[9]),"+f"(d[10]),"+f"(d[11]),"+f"(d[12]),"+f"(d[13]),"+f"(d[14]),"+f"(d[15]),"+f"(d[16]),"+f"(d[17]),"+f"(d[18]),"+f"(d[19]),"+f"(d[20]),"+f"(d[21]),"+f"(d[22]),"+f"(d[23]),"+f"(d[24]),"+f"(d[25]),"+f"(d[26]),"+f"(d[27]),"+f"(d[28]),"+f"(d[29]),"+f"(d[30]),"+f"(d[31]),"+f"(d[32]),"+f"(d[33]),"+f"(d[34]),"+f"(d[35]),"+f"(d[36]),"+f"(d[37]),"+f"(d[38]),"+f"(d[39]) : "r"(a[0]),"r"(a[1]),"r"(a[2]),"r"(a[3]),"l"(db),"r"(sc));
}
__device__ __forceinline__ void wg_rs96_0(float* d, const uint32_t* a, uint64_t db, int sc) {
  asm volatile("{.reg .pred p; setp.ne.b32 p, %53, 0; wgmma.mma_async.sync.aligned.m64n96k16.f32.bf16.bf16 {%0,%1,%2,%3,%4,%5,%6,%7,%8,%9,%10,%11,%12,%13,%14,%15,%16,%17,%18,%19,%20,%21,%22,%23,%24,%25,%26,%27,%28,%29,%30,%31,%32,%33,%34,%35,%36,%37,%38,%39,%40,%41,%42,%43,%44,%45,%46,%47}, {%48,%49,%50,%51}, %52, p, 1, 1, 0;}"
    : "+f"(d[0]),"+f"(d[1]),"+f"(d[2]),"+f"(d[3]),"+f"(d[4]),"+f"(d[5]),"+f"(d[6]),"+f"(d[7]),"+f"(d[8]),"+f"(d[9]),"+f"(d[10]),"+f"(d[11]),"+f"(d[12]),"+f"(d[13]),"+f"(d[14]),"+f"(d[15]),"+f"(d[16]),"+f"(d[17]),"+f"(d[18]),"+f"(d[19]),"+f"(d[20]),"+f"(d[21]),"+f"(d[22]),"+f"(d[23]),"+f"(d[24]),"+f"(d[25]),"+f"(d[26]),"+f"(d[27]),"+f"(d[28]),"+f"(d[29]),"+f"(d[30]),"+f"(d[31]),"+f"(d[32]),"+f"(d[33]),"+f"(d[34]),"+f"(d[35]),"+f"(d[36]),"+f"(d[37]),"+f"(d[38]),"+f"(d[39]),"+f"(d[40]),"+f"(d[41]),"+f"(d[42]),"+f"(d[43]),"+f"(d[44]),"+f"(d[45]),"+f"(d[46]),"+f"(d[47]) : "r"(a[0]),"r"(a[1]),"r"(a[2]),"r"(a[3]),"l"(db),"r"(sc));
}
__device__ __forceinline__ void wg_rs112_0(float* d, const uint32_t* a, uint64_t db, int sc) {
  asm volatile("{.reg .pred p; setp.ne.b32 p, %61, 0; wgmma.mma_async.sync.aligned.m64n112k16.f32.bf16.bf16 {%0,%1,%2,%3,%4,%5,%6,%7,%8,%9,%10,%11,%12,%13,%14,%15,%16,%17,%18,%19,%20,%21,%22,%23,%24,%25,%26,%27,%28,%29,%30,%31,%32,%33,%34,%35,%36,%37,%38,%39,%40,%41,%42,%43,%44,%45,%46,%47,%48,%49,%50,%51,%52,%53,%54,%55}, {%56,%57,%58,%59}, %60, p, 1, 1, 0;}"
    : "+f"(d[0]),"+f"(d[1]),"+f"(d[2]),"+f"(d[3]),"+f"(d[4]),"+f"(d[5]),"+f"(d[6]),"+f"(d[7]),"+f"(d[8]),"+f"(d[9]),"+f"(d[10]),"+f"(d[11]),"+f"(d[12]),"+f"(d[13]),"+f"(d[14]),"+f"(d[15]),"+f"(d[16]),"+f"(d[17]),"+f"(d[18]),"+f"(d[19]),"+f"(d[20]),"+f"(d[21]),"+f"(d[22]),"+f"(d[23]),"+f"(d[24]),"+f"(d[25]),"+f"(d[26]),"+f"(d[27]),"+f"(d[28]),"+f"(d[29]),"+f"(d[30]),"+f"(d[31]),"+f"(d[32]),"+f"(d[33]),"+f"(d[34]),"+f"(d[35]),"+f"(d[36]),"+f"(d[37]),"+f"(d[38]),"+f"(d[39]),"+f"(d[40]),"+f"(d[41]),"+f"(d[42]),"+f"(d[43]),"+f"(d[44]),"+f"(d[45]),"+f"(d[46]),"+f"(d[47]),"+f"(d[48]),"+f"(d[49]),"+f"(d[50]),"+f"(d[51]),"+f"(d[52]),"+f"(d[53]),"+f"(d[54]),"+f"(d[55]) : "r"(a[0]),"r"(a[1]),"r"(a[2]),"r"(a[3]),"l"(db),"r"(sc));
}
__device__ __forceinline__ void wg_rs128_0(float* d, const uint32_t* a, uint64_t db, int sc) {
  asm volatile("{.reg .pred p; setp.ne.b32 p, %69, 0; wgmma.mma_async.sync.aligned.m64n128k16.f32.bf16.bf16 {%0,%1,%2,%3,%4,%5,%6,%7,%8,%9,%10,%11,%12,%13,%14,%15,%16,%17,%18,%19,%20,%21,%22,%23,%24,%25,%26,%27,%28,%29,%30,%31,%32,%33,%34,%35,%36,%37,%38,%39,%40,%41,%42,%43,%44,%45,%46,%47,%48,%49,%50,%51,%52,%53,%54,%55,%56,%57,%58,%59,%60,%61,%62,%63}, {%64,%65,%66,%67}, %68, p, 1, 1, 0;}"
    : "+f"(d[0]),"+f"(d[1]),"+f"(d[2]),"+f"(d[3]),"+f"(d[4]),"+f"(d[5]),"+f"(d[6]),"+f"(d[7]),"+f"(d[8]),"+f"(d[9]),"+f"(d[10]),"+f"(d[11]),"+f"(d[12]),"+f"(d[13]),"+f"(d[14]),"+f"(d[15]),"+f"(d[16]),"+f"(d[17]),"+f"(d[18]),"+f"(d[19]),"+f"(d[20]),"+f"(d[21]),"+f"(d[22]),"+f"(d[23]),"+f"(d[24]),"+f"(d[25]),"+f"(d[26]),"+f"(d[27]),"+f"(d[28]),"+f"(d[29]),"+f"(d[30]),"+f"(d[31]),"+f"(d[32]),"+f"(d[33]),"+f"(d[34]),"+f"(d[35]),"+f"(d[36]),"+f"(d[37]),"+f"(d[38]),"+f"(d[39]),"+f"(d[40]),"+f"(d[41]),"+f"(d[42]),"+f"(d[43]),"+f"(d[44]),"+f"(d[45]),"+f"(d[46]),"+f"(d[47]),"+f"(d[48]),"+f"(d[49]),"+f"(d[50]),"+f"(d[51]),"+f"(d[52]),"+f"(d[53]),"+f"(d[54]),"+f"(d[55]),"+f"(d[56]),"+f"(d[57]),"+f"(d[58]),"+f"(d[59]),"+f"(d[60]),"+f"(d[61]),"+f"(d[62]),"+f"(d[63]) : "r"(a[0]),"r"(a[1]),"r"(a[2]),"r"(a[3]),"l"(db),"r"(sc));
}
__device__ __forceinline__ void wg_rs144_0(float* d, const uint32_t* a, uint64_t db, int sc) {
  asm volatile("{.reg .pred p; setp.ne.b32 p, %77, 0; wgmma.mma_async.sync.aligned.m64n144k16.f32.bf16.bf16 {%0,%1,%2,%3,%4,%5,%6,%7,%8,%9,%10,%11,%12,%13,%14,%15,%16,%17,%18,%19,%20,%21,%22,%23,%24,%25,%26,%27,%28,%29,%30,%31,%32,%33,%34,%35,%36,%37,%38,%39,%40,%41,%42,%43,%44,%45,%46,%47,%48,%49,%50,%51,%52,%53,%54,%55,%56,%57,%58,%59,%60,%61,%62,%63,%64,%65,%66,%67,%68,%69,%70,%71}, {%72,%73,%74,%75}, %76, p, 1, 1, 0;}"
    : "+f"(d[0]),"+f"(d[1]),"+f"(d[2]),"+f"(d[3]),"+f"(d[4]),"+f"(d[5]),"+f"(d[6]),"+f"(d[7]),"+f"(d[8]),"+f"(d[9]),"+f"(d[10]),"+f"(d[11]),"+f"(d[12]),"+f"(d[13]),"+f"(d[14]),"+f"(d[15]),"+f"(d[16]),"+f"(d[17]),"+f"(d[18]),"+f"(d[19]),"+f"(d[20]),"+f"(d[21]),"+f"(d[22]),"+f"(d[23]),"+f"(d[24]),"+f"(d[25]),"+f"(d[26]),"+f"(d[27]),"+f"(d[28]),"+f"(d[29]),"+f"(d[30]),"+f"(d[31]),"+f"(d[32]),"+f"(d[33]),"+f"(d[34]),"+f"(d[35]),"+f"(d[36]),"+f"(d[37]),"+f"(d[38]),"+f"(d[39]),"+f"(d[40]),"+f"(d[41]),"+f"(d[42]),"+f"(d[43]),"+f"(d[44]),"+f"(d[45]),"+f"(d[46]),"+f"(d[47]),"+f"(d[48]),"+f"(d[49]),"+f"(d[50]),"+f"(d[51]),"+f"(d[52]),"+f"(d[53]),"+f"(d[54]),"+f"(d[55]),"+f"(d[56]),"+f"(d[57]),"+f"(d[58]),"+f"(d[59]),"+f"(d[60]),"+f"(d[61]),"+f"(d[62]),"+f"(d[63]),"+f"(d[64]),"+f"(d[65]),"+f"(d[66]),"+f"(d[67]),"+f"(d[68]),"+f"(d[69]),"+f"(d[70]),"+f"(d[71]) : "r"(a[0]),"r"(a[1]),"r"(a[2]),"r"(a[3]),"l"(db),"r"(sc));
}
__device__ __forceinline__ void wg_rs160_0(float* d, const uint32_t* a, uint64_t db, int sc) {
  asm volatile("{.reg .pred p; setp.ne.b32 p, %85, 0; wgmma.mma_async.sync.aligned.m64n160k16.f32.bf16.bf16 {%0,%1,%2,%3,%4,%5,%6,%7,%8,%9,%10,%11,%12,%13,%14,%15,%16,%17,%18,%19,%20,%21,%22,%23,%24,%25,%26,%27,%28,%29,%30,%31,%32,%33,%34,%35,%36,%37,%38,%39,%40,%41,%42,%43,%44,%45,%46,%47,%48,%49,%50,%51,%52,%53,%54,%55,%56,%57,%58,%59,%60,%61,%62,%63,%64,%65,%66,%67,%68,%69,%70,%71,%72,%73,%74,%75,%76,%77,%78,%79}, {%80,%81,%82,%83}, %84, p, 1, 1, 0;}"
    : "+f"(d[0]),"+f"(d[1]),"+f"(d[2]),"+f"(d[3]),"+f"(d[4]),"+f"(d[5]),"+f"(d[6]),"+f"(d[7]),"+f"(d[8]),"+f"(d[9]),"+f"(d[10]),"+f"(d[11]),"+f"(d[12]),"+f"(d[13]),"+f"(d[14]),"+f"(d[15]),"+f"(d[16]),"+f"(d[17]),"+f"(d[18]),"+f"(d[19]),"+f"(d[20]),"+f"(d[21]),"+f"(d[22]),"+f"(d[23]),"+f"(d[24]),"+f"(d[25]),"+f"(d[26]),"+f"(d[27]),"+f"(d[28]),"+f"(d[29]),"+f"(d[30]),"+f"(d[31]),"+f"(d[32]),"+f"(d[33]),"+f"(d[34]),"+f"(d[35]),"+f"(d[36]),"+f"(d[37]),"+f"(d[38]),"+f"(d[39]),"+f"(d[40]),"+f"(d[41]),"+f"(d[42]),"+f"(d[43]),"+f"(d[44]),"+f"(d[45]),"+f"(d[46]),"+f"(d[47]),"+f"(d[48]),"+f"(d[49]),"+f"(d[50]),"+f"(d[51]),"+f"(d[52]),"+f"(d[53]),"+f"(d[54]),"+f"(d[55]),"+f"(d[56]),"+f"(d[57]),"+f"(d[58]),"+f"(d[59]),"+f"(d[60]),"+f"(d[61]),"+f"(d[62]),"+f"(d[63]),"+f"(d[64]),"+f"(d[65]),"+f"(d[66]),"+f"(d[67]),"+f"(d[68]),"+f"(d[69]),"+f"(d[70]),"+f"(d[71]),"+f"(d[72]),"+f"(d[73]),"+f"(d[74]),"+f"(d[75]),"+f"(d[76]),"+f"(d[77]),"+f"(d[78]),"+f"(d[79]) : "r"(a[0]),"r"(a[1]),"r"(a[2]),"r"(a[3]),"l"(db),"r"(sc));
}
__device__ __forceinline__ void wg_rs176_0(float* d, const uint32_t* a, uint64_t db, int sc) {
  asm volatile("{.reg .pred p; setp.ne.b32 p, %93, 0; wgmma.mma_async.sync.aligned.m64n176k16.f32.bf16.bf16 {%0,%1,%2,%3,%4,%5,%6,%7,%8,%9,%10,%11,%12,%13,%14,%15,%16,%17,%18,%19,%20,%21,%22,%23,%24,%25,%26,%27,%28,%29,%30,%31,%32,%33,%34,%35,%36,%37,%38,%39,%40,%41,%42,%43,%44,%45,%46,%47,%48,%49,%50,%51,%52,%53,%54,%55,%56,%57,%58,%59,%60,%61,%62,%63,%64,%65,%66,%67,%68,%69,%70,%71,%72,%73,%74,%75,%76,%77,%78,%79,%80,%81,%82,%83,%84,%85,%86,%87}, {%88,%89,%90,%91}, %92, p, 1, 1, 0;}"
    : "+f"(d[0]),"+f"(d[1]),"+f"(d[2]),"+f"(d[3]),"+f"(d[4]),"+f"(d[5]),"+f"(d[6]),"+f"(d[7]),"+f"(d[8]),"+f"(d[9]),"+f"(d[10]),"+f"(d[11]),"+f"(d[12]),"+f"(d[13]),"+f"(d[14]),"+f"(d[15]),"+f"(d[16]),"+f"(d[17]),"+f"(d[18]),"+f"(d[19]),"+f"(d[20]),"+f"(d[21]),"+f"(d[22]),"+f"(d[23]),"+f"(d[24]),"+f"(d[25]),"+f"(d[26]),"+f"(d[27]),"+f"(d[28]),"+f"(d[29]),"+f"(d[30]),"+f"(d[31]),"+f"(d[32]),"+f"(d[33]),"+f"(d[34]),"+f"(d[35]),"+f"(d[36]),"+f"(d[37]),"+f"(d[38]),"+f"(d[39]),"+f"(d[40]),"+f"(d[41]),"+f"(d[42]),"+f"(d[43]),"+f"(d[44]),"+f"(d[45]),"+f"(d[46]),"+f"(d[47]),"+f"(d[48]),"+f"(d[49]),"+f"(d[50]),"+f"(d[51]),"+f"(d[52]),"+f"(d[53]),"+f"(d[54]),"+f"(d[55]),"+f"(d[56]),"+f"(d[57]),"+f"(d[58]),"+f"(d[59]),"+f"(d[60]),"+f"(d[61]),"+f"(d[62]),"+f"(d[63]),"+f"(d[64]),"+f"(d[65]),"+f"(d[66]),"+f"(d[67]),"+f"(d[68]),"+f"(d[69]),"+f"(d[70]),"+f"(d[71]),"+f"(d[72]),"+f"(d[73]),"+f"(d[74]),"+f"(d[75]),"+f"(d[76]),"+f"(d[77]),"+f"(d[78]),"+f"(d[79]),"+f"(d[80]),"+f"(d[81]),"+f"(d[82]),"+f"(d[83]),"+f"(d[84]),"+f"(d[85]),"+f"(d[86]),"+f"(d[87]) : "r"(a[0]),"r"(a[1]),"r"(a[2]),"r"(a[3]),"l"(db),"r"(sc));
}
__device__ __forceinline__ void wg_rs192_0(float* d, const uint32_t* a, uint64_t db, int sc) {
  asm volatile("{.reg .pred p; setp.ne.b32 p, %101, 0; wgmma.mma_async.sync.aligned.m64n192k16.f32.bf16.bf16 {%0,%1,%2,%3,%4,%5,%6,%7,%8,%9,%10,%11,%12,%13,%14,%15,%16,%17,%18,%19,%20,%21,%22,%23,%24,%25,%26,%27,%28,%29,%30,%31,%32,%33,%34,%35,%36,%37,%38,%39,%40,%41,%42,%43,%44,%45,%46,%47,%48,%49,%50,%51,%52,%53,%54,%55,%56,%57,%58,%59,%60,%61,%62,%63,%64,%65,%66,%67,%68,%69,%70,%71,%72,%73,%74,%75,%76,%77,%78,%79,%80,%81,%82,%83,%84,%85,%86,%87,%88,%89,%90,%91,%92,%93,%94,%95}, {%96,%97,%98,%99}, %100, p, 1, 1, 0;}"
    : "+f"(d[0]),"+f"(d[1]),"+f"(d[2]),"+f"(d[3]),"+f"(d[4]),"+f"(d[5]),"+f"(d[6]),"+f"(d[7]),"+f"(d[8]),"+f"(d[9]),"+f"(d[10]),"+f"(d[11]),"+f"(d[12]),"+f"(d[13]),"+f"(d[14]),"+f"(d[15]),"+f"(d[16]),"+f"(d[17]),"+f"(d[18]),"+f"(d[19]),"+f"(d[20]),"+f"(d[21]),"+f"(d[22]),"+f"(d[23]),"+f"(d[24]),"+f"(d[25]),"+f"(d[26]),"+f"(d[27]),"+f"(d[28]),"+f"(d[29]),"+f"(d[30]),"+f"(d[31]),"+f"(d[32]),"+f"(d[33]),"+f"(d[34]),"+f"(d[35]),"+f"(d[36]),"+f"(d[37]),"+f"(d[38]),"+f"(d[39]),"+f"(d[40]),"+f"(d[41]),"+f"(d[42]),"+f"(d[43]),"+f"(d[44]),"+f"(d[45]),"+f"(d[46]),"+f"(d[47]),"+f"(d[48]),"+f"(d[49]),"+f"(d[50]),"+f"(d[51]),"+f"(d[52]),"+f"(d[53]),"+f"(d[54]),"+f"(d[55]),"+f"(d[56]),"+f"(d[57]),"+f"(d[58]),"+f"(d[59]),"+f"(d[60]),"+f"(d[61]),"+f"(d[62]),"+f"(d[63]),"+f"(d[64]),"+f"(d[65]),"+f"(d[66]),"+f"(d[67]),"+f"(d[68]),"+f"(d[69]),"+f"(d[70]),"+f"(d[71]),"+f"(d[72]),"+f"(d[73]),"+f"(d[74]),"+f"(d[75]),"+f"(d[76]),"+f"(d[77]),"+f"(d[78]),"+f"(d[79]),"+f"(d[80]),"+f"(d[81]),"+f"(d[82]),"+f"(d[83]),"+f"(d[84]),"+f"(d[85]),"+f"(d[86]),"+f"(d[87]),"+f"(d[88]),"+f"(d[89]),"+f"(d[90]),"+f"(d[91]),"+f"(d[92]),"+f"(d[93]),"+f"(d[94]),"+f"(d[95]) : "r"(a[0]),"r"(a[1]),"r"(a[2]),"r"(a[3]),"l"(db),"r"(sc));
}
__device__ __forceinline__ void wg_ss192_11(float* d, uint64_t da, uint64_t db, int sc) {
  asm volatile("{.reg .pred p; setp.ne.b32 p, %98, 0; wgmma.mma_async.sync.aligned.m64n192k16.f32.bf16.bf16 {%0,%1,%2,%3,%4,%5,%6,%7,%8,%9,%10,%11,%12,%13,%14,%15,%16,%17,%18,%19,%20,%21,%22,%23,%24,%25,%26,%27,%28,%29,%30,%31,%32,%33,%34,%35,%36,%37,%38,%39,%40,%41,%42,%43,%44,%45,%46,%47,%48,%49,%50,%51,%52,%53,%54,%55,%56,%57,%58,%59,%60,%61,%62,%63,%64,%65,%66,%67,%68,%69,%70,%71,%72,%73,%74,%75,%76,%77,%78,%79,%80,%81,%82,%83,%84,%85,%86,%87,%88,%89,%90,%91,%92,%93,%94,%95}, %96, %97, p, 1, 1, 1, 1;}"
    : "+f"(d[0]),"+f"(d[1]),"+f"(d[2]),"+f"(d[3]),"+f"(d[4]),"+f"(d[5]),"+f"(d[6]),"+f"(d[7]),"+f"(d[8]),"+f"(d[9]),"+f"(d[10]),"+f"(d[11]),"+f"(d[12]),"+f"(d[13]),"+f"(d[14]),"+f"(d[15]),"+f"(d[16]),"+f"(d[17]),"+f"(d[18]),"+f"(d[19]),"+f"(d[20]),"+f"(d[21]),"+f"(d[22]),"+f"(d[23]),"+f"(d[24]),"+f"(d[25]),"+f"(d[26]),"+f"(d[27]),"+f"(d[28]),"+f"(d[29]),"+f"(d[30]),"+f"(d[31]),"+f"(d[32]),"+f"(d[33]),"+f"(d[34]),"+f"(d[35]),"+f"(d[36]),"+f"(d[37]),"+f"(d[38]),"+f"(d[39]),"+f"(d[40]),"+f"(d[41]),"+f"(d[42]),"+f"(d[43]),"+f"(d[44]),"+f"(d[45]),"+f"(d[46]),"+f"(d[47]),"+f"(d[48]),"+f"(d[49]),"+f"(d[50]),"+f"(d[51]),"+f"(d[52]),"+f"(d[53]),"+f"(d[54]),"+f"(d[55]),"+f"(d[56]),"+f"(d[57]),"+f"(d[58]),"+f"(d[59]),"+f"(d[60]),"+f"(d[61]),"+f"(d[62]),"+f"(d[63]),"+f"(d[64]),"+f"(d[65]),"+f"(d[66]),"+f"(d[67]),"+f"(d[68]),"+f"(d[69]),"+f"(d[70]),"+f"(d[71]),"+f"(d[72]),"+f"(d[73]),"+f"(d[74]),"+f"(d[75]),"+f"(d[76]),"+f"(d[77]),"+f"(d[78]),"+f"(d[79]),"+f"(d[80]),"+f"(d[81]),"+f"(d[82]),"+f"(d[83]),"+f"(d[84]),"+f"(d[85]),"+f"(d[86]),"+f"(d[87]),"+f"(d[88]),"+f"(d[89]),"+f"(d[90]),"+f"(d[91]),"+f"(d[92]),"+f"(d[93]),"+f"(d[94]),"+f"(d[95]) : "l"(da),"l"(db),"r"(sc));
}
__device__ __forceinline__ void wg_ss192_01(float* d, uint64_t da, uint64_t db, int sc) {
  asm volatile("{.reg .pred p; setp.ne.b32 p, %98, 0; wgmma.mma_async.sync.aligned.m64n192k16.f32.bf16.bf16 {%0,%1,%2,%3,%4,%5,%6,%7,%8,%9,%10,%11,%12,%13,%14,%15,%16,%17,%18,%19,%20,%21,%22,%23,%24,%25,%26,%27,%28,%29,%30,%31,%32,%33,%34,%35,%36,%37,%38,%39,%40,%41,%42,%43,%44,%45,%46,%47,%48,%49,%50,%51,%52,%53,%54,%55,%56,%57,%58,%59,%60,%61,%62,%63,%64,%65,%66,%67,%68,%69,%70,%71,%72,%73,%74,%75,%76,%77,%78,%79,%80,%81,%82,%83,%84,%85,%86,%87,%88,%89,%90,%91,%92,%93,%94,%95}, %96, %97, p, 1, 1, 0, 1;}"
    : "+f"(d[0]),"+f"(d[1]),"+f"(d[2]),"+f"(d[3]),"+f"(d[4]),"+f"(d[5]),"+f"(d[6]),"+f"(d[7]),"+f"(d[8]),"+f"(d[9]),"+f"(d[10]),"+f"(d[11]),"+f"(d[12]),"+f"(d[13]),"+f"(d[14]),"+f"(d[15]),"+f"(d[16]),"+f"(d[17]),"+f"(d[18]),"+f"(d[19]),"+f"(d[20]),"+f"(d[21]),"+f"(d[22]),"+f"(d[23]),"+f"(d[24]),"+f"(d[25]),"+f"(d[26]),"+f"(d[27]),"+f"(d[28]),"+f"(d[29]),"+f"(d[30]),"+f"(d[31]),"+f"(d[32]),"+f"(d[33]),"+f"(d[34]),"+f"(d[35]),"+f"(d[36]),"+f"(d[37]),"+f"(d[38]),"+f"(d[39]),"+f"(d[40]),"+f"(d[41]),"+f"(d[42]),"+f"(d[43]),"+f"(d[44]),"+f"(d[45]),"+f"(d[46]),"+f"(d[47]),"+f"(d[48]),"+f"(d[49]),"+f"(d[50]),"+f"(d[51]),"+f"(d[52]),"+f"(d[53]),"+f"(d[54]),"+f"(d[55]),"+f"(d[56]),"+f"(d[57]),"+f"(d[58]),"+f"(d[59]),"+f"(d[60]),"+f"(d[61]),"+f"(d[62]),"+f"(d[63]),"+f"(d[64]),"+f"(d[65]),"+f"(d[66]),"+f"(d[67]),"+f"(d[68]),"+f"(d[69]),"+f"(d[70]),"+f"(d[71]),"+f"(d[72]),"+f"(d[73]),"+f"(d[74]),"+f"(d[75]),"+f"(d[76]),"+f"(d[77]),"+f"(d[78]),"+f"(d[79]),"+f"(d[80]),"+f"(d[81]),"+f"(d[82]),"+f"(d[83]),"+f"(d[84]),"+f"(d[85]),"+f"(d[86]),"+f"(d[87]),"+f"(d[88]),"+f"(d[89]),"+f"(d[90]),"+f"(d[91]),"+f"(d[92]),"+f"(d[93]),"+f"(d[94]),"+f"(d[95]) : "l"(da),"l"(db),"r"(sc));
}
__device__ __forceinline__ void wg_ss160_01(float* d, uint64_t da, uint64_t db, int sc) {
  asm volatile("{.reg .pred p; setp.ne.b32 p, %82, 0; wgmma.mma_async.sync.aligned.m64n160k16.f32.bf16.bf16 {%0,%1,%2,%3,%4,%5,%6,%7,%8,%9,%10,%11,%12,%13,%14,%15,%16,%17,%18,%19,%20,%21,%22,%23,%24,%25,%26,%27,%28,%29,%30,%31,%32,%33,%34,%35,%36,%37,%38,%39,%40,%41,%42,%43,%44,%45,%46,%47,%48,%49,%50,%51,%52,%53,%54,%55,%56,%57,%58,%59,%60,%61,%62,%63,%64,%65,%66,%67,%68,%69,%70,%71,%72,%73,%74,%75,%76,%77,%78,%79}, %80, %81, p, 1, 1, 0, 1;}"
    : "+f"(d[0]),"+f"(d[1]),"+f"(d[2]),"+f"(d[3]),"+f"(d[4]),"+f"(d[5]),"+f"(d[6]),"+f"(d[7]),"+f"(d[8]),"+f"(d[9]),"+f"(d[10]),"+f"(d[11]),"+f"(d[12]),"+f"(d[13]),"+f"(d[14]),"+f"(d[15]),"+f"(d[16]),"+f"(d[17]),"+f"(d[18]),"+f"(d[19]),"+f"(d[20]),"+f"(d[21]),"+f"(d[22]),"+f"(d[23]),"+f"(d[24]),"+f"(d[25]),"+f"(d[26]),"+f"(d[27]),"+f"(d[28]),"+f"(d[29]),"+f"(d[30]),"+f"(d[31]),"+f"(d[32]),"+f"(d[33]),"+f"(d[34]),"+f"(d[35]),"+f"(d[36]),"+f"(d[37]),"+f"(d[38]),"+f"(d[39]),"+f"(d[40]),"+f"(d[41]),"+f"(d[42]),"+f"(d[43]),"+f"(d[44]),"+f"(d[45]),"+f"(d[46]),"+f"(d[47]),"+f"(d[48]),"+f"(d[49]),"+f"(d[50]),"+f"(d[51]),"+f"(d[52]),"+f"(d[53]),"+f"(d[54]),"+f"(d[55]),"+f"(d[56]),"+f"(d[57]),"+f"(d[58]),"+f"(d[59]),"+f"(d[60]),"+f"(d[61]),"+f"(d[62]),"+f"(d[63]),"+f"(d[64]),"+f"(d[65]),"+f"(d[66]),"+f"(d[67]),"+f"(d[68]),"+f"(d[69]),"+f"(d[70]),"+f"(d[71]),"+f"(d[72]),"+f"(d[73]),"+f"(d[74]),"+f"(d[75]),"+f"(d[76]),"+f"(d[77]),"+f"(d[78]),"+f"(d[79]) : "l"(da),"l"(db),"r"(sc));
}
__device__ __forceinline__ void wg_rs160_1(float* d, const uint32_t* a, uint64_t db, int sc) {
  asm volatile("{.reg .pred p; setp.ne.b32 p, %85, 0; wgmma.mma_async.sync.aligned.m64n160k16.f32.bf16.bf16 {%0,%1,%2,%3,%4,%5,%6,%7,%8,%9,%10,%11,%12,%13,%14,%15,%16,%17,%18,%19,%20,%21,%22,%23,%24,%25,%26,%27,%28,%29,%30,%31,%32,%33,%34,%35,%36,%37,%38,%39,%40,%41,%42,%43,%44,%45,%46,%47,%48,%49,%50,%51,%52,%53,%54,%55,%56,%57,%58,%59,%60,%61,%62,%63,%64,%65,%66,%67,%68,%69,%70,%71,%72,%73,%74,%75,%76,%77,%78,%79}, {%80,%81,%82,%83}, %84, p, 1, 1, 1;}"
    : "+f"(d[0]),"+f"(d[1]),"+f"(d[2]),"+f"(d[3]),"+f"(d[4]),"+f"(d[5]),"+f"(d[6]),"+f"(d[7]),"+f"(d[8]),"+f"(d[9]),"+f"(d[10]),"+f"(d[11]),"+f"(d[12]),"+f"(d[13]),"+f"(d[14]),"+f"(d[15]),"+f"(d[16]),"+f"(d[17]),"+f"(d[18]),"+f"(d[19]),"+f"(d[20]),"+f"(d[21]),"+f"(d[22]),"+f"(d[23]),"+f"(d[24]),"+f"(d[25]),"+f"(d[26]),"+f"(d[27]),"+f"(d[28]),"+f"(d[29]),"+f"(d[30]),"+f"(d[31]),"+f"(d[32]),"+f"(d[33]),"+f"(d[34]),"+f"(d[35]),"+f"(d[36]),"+f"(d[37]),"+f"(d[38]),"+f"(d[39]),"+f"(d[40]),"+f"(d[41]),"+f"(d[42]),"+f"(d[43]),"+f"(d[44]),"+f"(d[45]),"+f"(d[46]),"+f"(d[47]),"+f"(d[48]),"+f"(d[49]),"+f"(d[50]),"+f"(d[51]),"+f"(d[52]),"+f"(d[53]),"+f"(d[54]),"+f"(d[55]),"+f"(d[56]),"+f"(d[57]),"+f"(d[58]),"+f"(d[59]),"+f"(d[60]),"+f"(d[61]),"+f"(d[62]),"+f"(d[63]),"+f"(d[64]),"+f"(d[65]),"+f"(d[66]),"+f"(d[67]),"+f"(d[68]),"+f"(d[69]),"+f"(d[70]),"+f"(d[71]),"+f"(d[72]),"+f"(d[73]),"+f"(d[74]),"+f"(d[75]),"+f"(d[76]),"+f"(d[77]),"+f"(d[78]),"+f"(d[79]) : "r"(a[0]),"r"(a[1]),"r"(a[2]),"r"(a[3]),"l"(db),"r"(sc));
}
__device__ __forceinline__ void wg_ss8_10(float* d, uint64_t da, uint64_t db, int sc) {
  asm volatile("{.reg .pred p; setp.ne.b32 p, %6, 0; wgmma.mma_async.sync.aligned.m64n8k16.f32.bf16.bf16 {%0,%1,%2,%3}, %4, %5, p, 1, 1, 1, 0;}"
    : "+f"(d[0]),"+f"(d[1]),"+f"(d[2]),"+f"(d[3]) : "l"(da),"l"(db),"r"(sc));
}

constexpr uint32_t DB = 1024;
constexpr int WSLOT = 24576, NW = 6, ASLOT = 8192, ARING = 4 * ASLOT;
constexpr int OFF_A = NW * WSLOT;
constexpr int OFF_PB = OFF_A + 2 * ARING;
constexpr int OFF_CV = OFF_PB + 16384, OFF_ST = OFF_CV + 768, OFF_TS = OFF_ST + 256, OFF_MODR = OFF_TS + 512, OFF_BAR = OFF_MODR + 80, SMEM_BYTES = OFF_BAR + 1168;
constexpr int OFF_BX = OFF_PB, OFF_AX = OFF_BX + 12288, OFF_RT = OFF_AX + 2048, OFF_GB = OFF_RT + 512, OFF_CO = OFF_CV;
constexpr int OFF_UV = 5 * WSLOT, OFF_UVE = OFF_PB, OFF_SX = OFF_A + ARING + 3 * ASLOT, OFF_X1 = 2 * WSLOT + ASLOT, OFF_XCH = WSLOT;
constexpr int OFF_Q = 0, KV_V = 4096, KV_H = 8192, F_E = 16, F_O = 4176, OFF_WM = 3 * WSLOT, OFF_TAP = 168576, OFF_MR = OFF_A + 3 * ASLOT;
constexpr uint64_t pk5(int a, int b, int c, int d, int e) { return (uint64_t)(a / 128) | (uint64_t)(b / 128) << 12 | (uint64_t)(c / 128) << 24 | (uint64_t)(d / 128) << 36 | (uint64_t)(e / 128) << 48; }
constexpr uint64_t T_KV = pk5(20480, 30720, 40960, 180224, 190464), T_F = pk5(51200, 59648, 200192, 147456, 155904), T_X = pk5(208512, 164352, 68096, 208512, 164352),
                   T_P = pk5(131072, OFF_PB, 114688, 131072, OFF_PB);
__host__ __device__ __forceinline__ uint32_t tab(uint64_t t, int c) { return ((uint32_t)(t >> (12 * c)) & 0xFFF) << 7; }
enum { B_KV = 0, B_FRAW = 5, B_Q = 10, B_WM = 15, B_XR, B_MR = B_XR + 5, B_QTOK, B_ST1, B_MODR, B_FL = 32, B_PFULL = B_FL + 5, B_PEMPTY = B_PFULL + 5, B_FRDY = B_PEMPTY + 5,
       B_G3 = B_FRDY + 5, B_EXT, B_QTD, B_LAG, B_UVD, B_FULL = 60, B_RETRY = B_FULL + 33, B_XFREE = B_RETRY + 9, B_BX, B_UVB, B_UVE, B_SX, B_EMPTY = 109 };
static_assert(B_MODR + 5 <= B_FL && B_UVD < B_FULL && B_SX + 2 == B_EMPTY - 1, "barrier groups");
#define BAR(i) (base + OFF_BAR + 8 * (i))

constexpr int NE = 24;
struct Maps { CUtensorMap km, v, q, kh, tap, wm, w1s, w3s, xs, w1, w3, w1e, w3e, x1s, x1b, w2a, w2b, outa, outb; };
struct Ptrs { const bf16 *ssmk, *c, *ssmd; Scratch* g; uint64_t wms, prog[2]; uint32_t gpos; int ulo, uhi; uint32_t seq, seq2; float one; uint2 sched[NE]; uint32_t wdep[20]; uint2 w2t[12]; int hid[3][9]; };

#define REGION_IDS int tid, lane, bid; \
  asm volatile("mov.u32 %0, %%tid.x;" : "=r"(tid)); asm volatile("mov.u32 %0, %%laneid;" : "=r"(lane)); asm volatile("mov.u32 %0, %%ctaid.x;" : "=r"(bid)); \
  const int i0 = tid & 127; (void)i0; (void)lane; (void)bid

__device__ __forceinline__ void ffn_role(int& h, int& j, int& r) {
  uint32_t b;
  asm volatile("mov.u32 %0, %%ctaid.x;" : "=r"(b));
  const uint32_t c = b >> 1, q = (c - 36) * 37 >> 8, e = c - 36 - 7 * q;
  h = b & 1;
  const uint32_t k = c < 4 ? 0 : c < 36 ? (c - 4) & 7 : e + 1, p = c < 4 ? c : c < 36 ? (c - 4) >> 3 : q, up = c - 4 >= 32;
  j = 2 * (k & 1) + up;
  r = 2 * (k & 6) + p;
}
__device__ __forceinline__ int fslice(int j, int e) { return e == 2 ? j ^ 1 : (~j & 2) + e; }
__device__ __forceinline__ int mod_ch(int p) { return p < 40 ? (p >> 3) * 128 + (p & 1) * 64 : 64 * (p < 50 ? p - 40 : p - 50); }
__device__ __forceinline__ int mod_col(int p) { return mod_ch(p) + 640 * (p < 40 ? 0x4210 >> (2 * (p & 6)) & 7 : p < 50 ? 3 : 5); }
__device__ __forceinline__ uint32_t mod_sum(uint2 v) { return pack_bf16(0.f, __uint_as_float(v.x) + __uint_as_float(v.y)); }
constexpr int LAG2 = 28, MG = 4;
constexpr int NT = 3;
__device__ __forceinline__ int nib(uint32_t t, int i) { return (t >> (4 * i)) & 15; }
__device__ __forceinline__ int w_block(int up, int m) { return m == 1 ? 2 + 3 * up : 3 * (m >> 1) + up; }
__host__ __device__ constexpr int w2_at(int v) { return 8192 * (v ? 0x0613030008ull >> v % 5 * 8 & 255 : 15); }
__host__ __device__ constexpr int w2_step(int v) { return 8192 * (v ? 0x32113 >> v % 5 * 4 & 15 : 1); }
__host__ __device__ constexpr int hid_at(int m, int g) { return 8192 * ((g ? 0x0D07110F1816ull : 0x0A19101A1412ull) >> m % 6 * 8 & 255); }
__host__ __device__ constexpr uint32_t w2_desc(int v) { return (DB + w2_at(v)) >> 4 | w2_step(v) << 12; }
__device__ __forceinline__ int next_slot(int s) { return s >= 4 * WSLOT ? 0 : s + WSLOT; }

template <int U> __device__ __forceinline__ void cstep(float* acc, const uint32_t* A, uint64_t db) {
  const uint32_t* a = A + 4 * U;
  const uint64_t d = db + 16 * U;
  if (U == 4) { wg_rs64_0(acc + 96, A, db + 192, 0); wg_rs48_0(acc + 96, A + 4, db + 208, 1); wg_rs32_0(acc + 96, A + 8, db + 224, 1); wg_rs16_0(acc + 96, A + 12, db + 240, 1); }
  if (U <= 4) wg_rs192_0(acc, a, d, U);
  if (U == 5) wg_rs176_0(acc, a, d, 1);
  if (U == 6) wg_rs160_0(acc, a, d, 1);
  if (U == 7) wg_rs144_0(acc, a, d, 1);
  if (U == 8) wg_rs128_0(acc, a, d, 1);
  if (U == 9) wg_rs112_0(acc, a, d, 1);
  if (U == 10) wg_rs96_0(acc, a, d, 1);
  if (U == 11) wg_rs80_0(acc, a, d, 1);
  if (U == 12) wg_rs64_0(acc, a, d, 1);
  if (U == 13) wg_rs48_0(acc, a, d, 1);
  if (U == 14) wg_rs32_0(acc, a, d, 1);
  if (U == 15) wg_rs16_0(acc, a, d, 1);
}
template <int U0, int U1> __device__ __forceinline__ void csteps(float* acc, const uint32_t* A, uint64_t db) {
  cstep<U0>(acc, A, db);
  if constexpr (U0 > U1) csteps<U0 - 1, U1>(acc, A, db);
}
template <int U0, int U1> __device__ __forceinline__ void cload(uint32_t* A, uint32_t fa) {
  asm volatile("{ld.shared.b32 %0, [%4+%5]; ld.shared.b32 %1, [%4+%5+128]; ld.shared.b32 %2, [%4+%5+16]; ld.shared.b32 %3, [%4+%5+144];}"
               : "=r"(A[4 * U0]), "=r"(A[4 * U0 + 1]), "=r"(A[4 * U0 + 2]), "=r"(A[4 * U0 + 3]) : "r"(fa), "n"(256 * U0) : "memory");
  if constexpr (U0 > U1) cload<U0 - 1, U1>(A, fa);
}

__device__ __forceinline__ void mod_gemv(Scratch* G, uint32_t wm, int unit, int w, int lane, uint32_t par) {
  float d[4] = {};
  fence_regs(d);
  wg_fence();
#pragma unroll 1
  for (int k = 0; k < 20; k += 2) {
    wg_ss8_10(d, mkdesc(DB + wm + 2048 * k, 16, 1024, 1), mkdesc(DB + OFF_CV + 32 * k, 16, 128, 0), 1);
    wg_ss8_10(d, mkdesc(DB + wm + 2048 * k + 2048, 16, 1024, 1), mkdesc(DB + OFF_CV + 32 * k + 32, 16, 128, 0), 1);
  }
  wg_commit();
  const int p = unit >> 1, ch = mod_ch(p) + 16 * w + (lane >> 2);
  uint32_t* dst = (uint32_t*)(p < 40 ? &G->modc[ch & 127][8 + (p >> 1)] : &G->modv[p >= 50][ch]) + (unit & 1);
  wg_wait<0>();
  fence_regs(d);
  if (!(lane & 3)) {
    publish(dst, (__float_as_uint(d[0]) & ~1u) | par);
    publish(dst + (p < 40 ? 512 : 16), (__float_as_uint(d[2]) & ~1u) | par);
    if (p < 40 && (p & 6) == 6) {
      dst = (uint32_t*)&G->modv[2][ch] + (unit & 1);
      publish(dst, (__float_as_uint(d[0]) & ~1u) | par);
      publish(dst + 16, (__float_as_uint(d[2]) & ~1u) | par);
    }
  }
}
__device__ __forceinline__ void silu_vector(const bf16* c, uint32_t base) {
  REGION_IDS;
  const uint32_t c0 = ldg32(c + 320 * (bid & 1) + 2 * i0), c1 = ldg32(c + 320 * (bid & 1) + 256 + 2 * lane);
  sts32(base + OFF_CV + 4 * i0, pack_bf16(silu_f(bf_lo(c0)), silu_f(bf_hi(c0))));
  sts32(base + OFF_CV + 512 + 4 * lane, pack_bf16(silu_f(bf_lo(c1)), silu_f(bf_hi(c1))));
  fence_async_smem();
}

__global__ void __cluster_dims__(2, 1, 1) __launch_bounds__(512, 1) k_fused(const __grid_constant__ Ptrs P, const __grid_constant__ Maps maps) {
  Scratch* const G = P.g;
  extern __shared__ __align__(1024) uint8_t smem_raw[];
  const uint32_t t_start = clock();
  const uint32_t base = __shfl_sync(~0u, smem_u32(smem_raw), 0);
  if ((base & 0xFFFFFFu) != DB) __trap();
  const int wid = __shfl_sync(~0u, threadIdx.x >> 5, 0), wg = wid >> 2, w = wid & 3;
  if (blockIdx.x >= 128) {
    REGION_IDS;
    auto unit = [&](int n) { return 4 * (n + (n < P.ulo / 4 ? 0 : (P.uhi - P.ulo) / 4)) + (bid & 3); };
    auto fetch = [&](int n, int b) {
      if (unit(n) < 120 && elect()) {
        mbar_expect_tx(BAR(n), 40960);
#pragma unroll 1
        for (int k = 0; k < 5; k++) tma3d(base + 40960 * b + 8192 * k, &maps.wm, mod_col(unit(n) >> 1), 320 * (bid & 1) + 64 * k, 0, BAR(n));
      }
    };
    if (wid == 0) {
      mbar_init<5>(BAR(0), 1);
#pragma unroll 1
      for (int n = 0; n < 5; n++) fetch(n, n);
      mbar_init<25>(BAR(5), 1);
    }
    const uint32_t par = ~ld_relaxed32(G->hint[7][0]) >> 7 & 1;
    silu_vector(P.c, base);
    __syncthreads();
#pragma unroll 1
    for (int n = wg; unit(n) < 120; n += 4) {
      mbar_wait(BAR(n));
      mod_gemv(G, 40960 * (n % 5), unit(n), w, lane, par);
      named_bar(1 + wg, 128);
      if (w == 0) fetch(n + 5, n % 5);
    }
    return;
  }
  if (wid == 13) {
    mbar_init<16>(BAR(0), 1);
    asm volatile("bar.arrive 1, 512;" ::: "memory");
    if (elect()) {
      const int c0 = 64 * (blockIdx.x & 1), c1 = 2 * (blockIdx.x & 126);
      mbar_expect_tx(BAR(B_KV), 12288);
      tma3d(base + tab(T_KV, 0), &maps.km, c0, c1, 0, BAR(B_KV));
      tma3d(base + tab(T_KV, 0) + KV_V, &maps.v, c0, c1, 0, BAR(B_KV));
      tma3d(base + tab(T_KV, 0) + KV_H, &maps.kh, c0, c1 - 1, 5, BAR(B_KV));
      tma3d(base + OFF_TAP, &maps.tap, 0, blockIdx.x & 1, 0, BAR(B_KV));
    }
  } else {
    asm volatile("bar.sync 1, 512;" ::: "memory");
    if (wid < 11) mbar_init<4>(BAR(16 + 4 * wid), wid < 4 ? 1 : 4);
    asm volatile("fence.mbarrier_init.release.cluster; bar.sync 0, 480;" ::: "memory");
  }
  asm volatile("barrier.cluster.arrive.relaxed.aligned;" ::: "memory");
#define LAUNCHES const uint32_t launches = ld_relaxed32(G->hint[7][blockIdx.x >> 4])
#define EPOCH ((__shfl_sync(~0u, launches, 0) >> 7) + 1)
  if (wg == 3) {
    asm volatile("setmaxnreg.dec.sync.aligned.u32 24;");
    if (w == 1) {
      {
        REGION_IDS;
        const int c1 = 2 * (bid & 126), ws = bid >= P.ulo && bid < P.uhi ? (uint32_t)(P.wms >> (8 * (bid >> 4))) & 255 : 99;
#pragma unroll 1
        for (int e = 0; e < NE; e++) {
          const uint2 x = P.sched[e];
          const uint32_t kind = x.x >> 16 & 15, ch = x.x >> 13 & 0x380, dst = base + (x.y & 0x3FFFF), b = BAR(x.y >> 18);
          wait_clock(t_start + (x.x & 0xFFFF));
          if (kind < 3 && elect()) tma3d(dst, &maps.km + kind, ch + 64 * (bid & 1), c1, 0, b);
          if (kind == 0 && elect()) tma3d(dst + KV_H, &maps.kh, ch + 64 * (bid & 1), c1 - 1, 5, b);
          if (kind == 3 && elect()) bulk_load(dst, P.ssmk + (ch + bid) * S_, 4096, b);
          if ((uint32_t)(e - ws) < 5 && elect()) tma3d(base + OFF_WM + 8192 * (e - ws), &maps.wm, mod_col(bid >> 1), 320 * (bid & 1) + 64 * (e - ws), 0, BAR(B_WM));
          if ((uint32_t)(e - 8) < 13 && elect()) prefetch_map(&maps.w1s + (e - 8));
        }
      }
      cluster_wait();
      int h, j, r;
      ffn_role(h, j, r);
      mbar_wait(BAR(B_QTD));
      mbar_wait(BAR(B_FL));
#pragma unroll 1
      for (int u = 0; u < 20; u++) {
        const uint32_t x = P.wdep[u], s = base + (x & ~8191u);
        mbar_wait(BAR(opaque(x & 255)));
        if (elect()) {
          mbar_expect_tx(BAR(B_FULL + u), WSLOT + 4 * (x & 4096));
#pragma unroll
          for (int k = 0; k < 6; k++) tma3d(s + 4096 * w_block(k & 1, k >> 1), &maps.w1s + (k & 1), 0, 32 * u, 3 * (4 * h + j) + (k >> 1), BAR(B_FULL + u));
        }
      }
#pragma unroll 1
      for (int v = 0; v < 12; v++) {
        const int q = v * 11 >> 5, e = v - 3 * q, k32 = 24 * h + (q ? 6 * fslice(j, e) + 2 * q - 2 : 6 * j + 2 * e);
        const uint2 x = P.w2t[v];
        mbar_wait(BAR(x.y));
        if (elect()) {
          mbar_expect_tx(BAR(B_FULL + 20 + v), q ? WSLOT + 2 * ASLOT : WSLOT);
#pragma unroll
          for (int k = 0; k < 3; k++) tma5d(base - DB + 16 * ((x.x & 0xFFFF) + k * (x.x >> 16)), &maps.w2a + (q > 0), k < 2 ? 128 * j + 64 * k : 512 + 32 * (j & 2), k32, BAR(B_FULL + 20 + v));
        }
      }
    } else if (w == 0) {
      LAUNCHES;
      uint32_t epoch;
      {
        REGION_IDS;
        const unsigned* hp = G->hint[0][4 * (bid >> 6) + (bid >> 3 & 3)];
        const uint2* mp = &G->modc[bid][8 + (lane & 3)];
        uint32_t v = ld_relaxed32(hp + 256 * min(lane, 5));
        if (lane < 3) sts128(base + tab(T_X, lane) + 4096, 0, 0, 0, 0);
        if (lane && lane <= B_WM) mbar_expect_tx(BAR(lane), lane < B_FRAW ? 9728 : lane == B_WM ? 40960 : 4096);
        epoch = EPOCH;
        fence_async_smem();
        const uint32_t rdy = __ballot_sync(~0u, v == epoch << 6);
        uint32_t nx = 0, nm = 0;
#pragma unroll 1
        for (uint32_t seq = P.seq; seq; seq >>= 1) {
          int it = 0;
          if (seq & 1) {
            uint2 m;
#pragma unroll 1
            do m = ld_relaxed64(mp + 4 * nm); while (__any_sync(~0u, ((m.x ^ epoch) | (m.y ^ epoch)) & 1) && ++it < SPIN_LIMIT);
            sts32(base + OFF_MODR + 16 * nm + 4 * (lane & 3), __byte_perm(badd2(mod_sum(m), (lane & 1) * 0x3F800000u), 0, 0x3232));
            arrive1(BAR(B_MODR + nm));
            nm++;
          } else {
            if (!(rdy >> nx & 1)) {
#pragma unroll 1
              while (__any_sync(~0u, ld_relaxed32(hp + 256 * nx) != epoch << 6) && ++it < SPIN_LIMIT);
            }
            if (nx >= 3) mbar_wait(BAR(B_PFULL - 3 + nx));
            if (elect()) { mbar_expect_tx(BAR(B_XR + nx), 4096); bulk_load(base + tab(T_X, nx), G->xr + (128 * nx + bid) * 256, 4096, BAR(B_XR + nx)); }
            nx++;
          }
        }
      }
      REGION_IDS;
      int h, j, r;
      ffn_role(h, j, r);
      mbar_wait(BAR(B_G3));
      {
        const uint2* mp = &G->modv[lane & 4 ? 0 : 2][40 * (r & 14) + (lane & 24) + 2 * (lane & 3)];
        uint4 v[3];
        int it = 0;
#pragma unroll 1
        do {
          v[0] = ld_relaxed128(mp); v[1] = ld_relaxed128(mp + 32); v[2] = ld_relaxed128(mp + 64 - (lane & 16));
        } while (__any_sync(~0u, ((v[0].x ^ epoch) | (v[0].y ^ epoch) | (v[0].z ^ epoch) | (v[0].w ^ epoch) | (v[1].x ^ epoch) | (v[1].y ^ epoch) | (v[1].z ^ epoch) | (v[1].w ^ epoch) |
                                  (v[2].x ^ epoch) | (v[2].y ^ epoch) | (v[2].z ^ epoch) | (v[2].w ^ epoch)) & 1) && ++it < SPIN_LIMIT);
#pragma unroll
        for (int i = 0; i < 3; i++)
          sts32(base + OFF_CO + 128 * i + 4 * lane, badd2(pack_bf16(__uint_as_float(v[i].x) + __uint_as_float(v[i].y), __uint_as_float(v[i].z) + __uint_as_float(v[i].w)), lane & 4 ? 0 : 0x3F803F80u));
      }
      fence_async_smem();
      __syncwarp();
      ffn_role(h, j, r);
      mbar_wait(BAR(B_PEMPTY + 3));
      if (elect()) {
        mbar_expect_tx(BAR(B_UVB), WSLOT);
        tma3d(base + OFF_UV, &maps.w1 + (r & 1), 0, 40 * (r & 14), 3 * (4 * h + j), BAR(B_UVB));
        tma3d(base + OFF_UV + 12288, &maps.w1 + (r & 1), 0, 40 * (r & 14) + 32, 3 * (4 * h + j), BAR(B_UVB));
      }
      mbar_wait(BAR(B_PEMPTY + 4));
      if (elect()) {
        mbar_expect_tx(BAR(B_UVE), 6144);
        tma3d(base + OFF_UVE, &maps.w1e + (r & 1), 0, 40 * (r & 14) + 64, 3 * (4 * h + j), BAR(B_UVE));
      }
      cluster_wait();
      mbar_wait(BAR(B_UVD));
      asm volatile("fence.acq_rel.gpu;" ::: "memory");
      if (lane < 8) red_hint(G->hint[7][lane]);
      unsigned x;
      int it = 0;
#pragma unroll 1
      do { asm volatile("ld.acquire.gpu.global.u32 %0, [%1];" : "=r"(x) : "l"(G->hint[7][bid >> 4]) : "memory"); } while (__any_sync(~0u, x != 128 * epoch) && ++it < SPIN_LIMIT);
      fence_async_all();
      const int ch = D_ * (epoch & 1);
      mbar_wait(BAR(B_EXT));
      mbar_wait(BAR(B_EMPTY + 18));
      if (elect()) {
        mbar_expect_tx(BAR(B_FULL + 32), 20480);
#pragma unroll
        for (int k = 0; k < 4; k++) tma2d(base + (k < 3 ? OFF_X1 + k * WSLOT : OFF_SX), &maps.x1b, 128 * r + 64 * h, ch + 128 * j + 32 * (k ^ (j & 1)), BAR(B_FULL + 32));
        tma2d(base + OFF_SX + 4096, &maps.x1b, 128 * r + 64 * h, ch + 512 + 32 * j, BAR(B_FULL + 32));
        mbar_expect_tx(BAR(B_FULL), 8192); mbar_expect_tx(BAR(B_FULL + 1), 8192); mbar_expect_tx(BAR(B_FULL + 2), 4096);
      }
      mbar_wait(BAR(B_EMPTY + 27));
      if (elect()) mbar_arrive_remote(mapa(BAR(B_XFREE), h ^ 1));
    } else {
      LAUNCHES;
      uint32_t epoch;
      {
        REGION_IDS;
        uint32_t dv;
        asm volatile("ld.global.nc.u16 %0, [%1];" : "=r"(dv) : "l"(P.ssmd + 128 * (lane & 7) % D_ + bid));
        if (lane < 5) sts128(base + tab(T_F, lane) + (w & 1) * (F_O - 16), 0, 0, 0, 0);
        epoch = EPOCH;
        __syncwarp();
#pragma unroll 1
        for (int c = 0; c < 5; c++) {
          const float d = i0 == 64 ? bf_lo(dv) : 0.f;
          dv = __shfl_down_sync(~0u, dv, 1);
          const uint32_t a = base + tab(T_F, c) + 16 * (i0 - 64);
          mbar_wait(BAR(B_FRAW + c));
#pragma unroll
          for (int k = 0; k < 4; k++) {
            uint4 x = lds128(a + F_E + 1024 * k);
            const uint32_t pv = lds32(a + F_E - 4 + 1024 * k);
            if (k == 0) { x.x = pack_bf16(bf_lo(x.x) + d, bf_hi(x.x)); sts32(a + F_E, x.x); }
            sts128(a + F_O + 1024 * k, __byte_perm(pv, x.x, 0x5432), __byte_perm(x.x, x.y, 0x5432), __byte_perm(x.y, x.z, 0x5432), __byte_perm(x.z, x.w, 0x5432));
          }
          __syncwarp();
          if (elect()) mbar_arrive2(BAR(B_FRDY + c));
        }
      }
      REGION_IDS;
      int h, j, r;
      ffn_role(h, j, r);
      cluster_wait();
      if (w == 2) {
        const unsigned* fp = G->xsh[lane < 10 ? lane >> 1 : 0][(r & 6) + (lane & 1)];
        uint32_t rdy = 0, s = 0;
        mbar_wait(BAR(B_QTD));
        mbar_wait(BAR(B_FL + 2));
#pragma unroll 1
        for (int n = 0; n < 10; n++) {
          mbar_wait(BAR(n < 2 ? B_FL + 3 + n : n == 2 ? B_PFULL + 4 : B_EMPTY + 2 * n - 5));
#pragma unroll 1
          for (int it = 0; !(rdy >> n & 1) && it < SPIN_LIMIT; it++) rdy = __ballot_sync(~0u, ld_relaxed32(fp) == 64 * epoch);
          if (elect()) {
            tma2d(base + OFF_A + s, &maps.xs, 128 * r + 64 * h, 64 * n, BAR(B_FULL + 2 * n));
            tma2d(base + OFF_A + ARING + s, &maps.xs, 128 * r + 64 - 64 * h, 64 * n, BAR(B_FULL + 2 * n));
          }
          s = s == 2 * ASLOT ? 0 : s + ASLOT;
        }
      } else {
        float s0 = 0.f, q0 = 0.f, s1 = 0.f, q1 = 0.f;
        uint32_t nl = 0, np = 0, ph = 0;
        mbar_wait(BAR(B_FL + 2));
        mbar_wait(BAR(B_PFULL + 3));
#pragma unroll 1
        for (uint32_t seq = P.seq2; seq; seq >>= 1) {
          const uint32_t c = seq & 1 ? np : nl, buf = base + OFF_SX + 4096 * (c & 1), b = BAR(opaque(B_SX + (c & 1)));
          int it = 0;
          if (seq & 1) {
            mbar_wait(b, ph >> (c & 1) & 1);
            ph ^= 1 << (c & 1);
            const uint32_t a = buf + 32 * lane;
            if (__all_sync(~0u, min(min(lds32(a), lds32(a + 1024)), min(lds32(a + 2048), lds32(a + 3072)))) || ph > SPIN_LIMIT) {
#pragma unroll 1
              for (uint32_t o = buf + 4 * lane; o < buf + 4096; o += 1024) {
                uint32_t x[8];
#pragma unroll
                for (int i = 0; i < 8; i++) x[i] = lds32(o + 128 * i);
#pragma unroll
                for (int i = 0; i < 8; i++) { const float lo = bf_lo(x[i]), hi = bf_hi(x[i]); s0 += lo; q0 = fmaf(lo, lo, q0); s1 += hi; q1 = fmaf(hi, hi, q1); }
              }
              np++;
              continue;
            }
            ph += 4;
            seq = 2 * seq + 1;
          } else {
#pragma unroll 1
            while (__any_sync(~0u, ld_relaxed32(G->xsh[c][(r & 6) + (j >> 1)]) != 64 * epoch) && ++it < SPIN_LIMIT);
            nl++;
          }
          if (elect()) { mbar_expect_tx(b, 4096); tma2d(buf, &maps.x1s, 128 * r + 64 * h, D_ * (epoch & 1) + 128 * c + 32 * j, b); }
        }
        asm volatile("{.reg .b128 t, x; .reg .b64 a, b; mov.b64 a, {%1,%2}; mov.b64 b, {%3,%4}; mov.b128 x, {a,b}; atom.relaxed.gpu.global.exch.b128 t, [%0], x;}"
                     ::"l"(&G->st2[2 * r + h][j][4 * lane]), "r"((__float_as_uint(s0) & ~1u) | (epoch & 1)), "f"(q0), "r"((__float_as_uint(s1) & ~1u) | (epoch & 1)), "f"(q1) : "memory");
        uint4* z = G->x1[~epoch & 1] + 1280 * bid + lane;
#pragma unroll 1
        for (int k = 0; k < 40; k++) st_relaxed128(z + 32 * k, 0, 0, 0, 0);
      }
    }
  } else if (wg == 2) {
    asm volatile("setmaxnreg.dec.sync.aligned.u32 40;");
    mbar_init<12>(BAR(B_FULL + 12 * w), 1);
    mbar_init<9>(BAR(B_EMPTY - 1 + 9 * w), 8);
    asm volatile("fence.mbarrier_init.release.cluster;" ::: "memory");
    LAUNCHES;
    const uint32_t epoch = EPOCH;
    cluster_wait();
    {
      REGION_IDS;
      const uint32_t tag = opaque(~lane & 1);
      {
        const int tr = 4 * (lane & 1) + (lane >> 1 & 3);
        uint32_t a = base + OFF_Q + 128 * ((lane & 24) + tr) + ((w ^ tr) << 4);
        uint4* dst = G->qt + (64 * (bid & 1) + 8 * w + (lane >> 2)) * 256 + 4 * (bid >> 1) + (lane & 3);
#pragma unroll 1
        for (int c = 0; c < 5; c++) {
          mbar_wait(BAR(B_Q + c));
#pragma unroll
          for (int k = 0; k < 2; k++) {
            uint32_t x[4];
            ldmatrix_x4_t(x, a ^ (64 * k));
            st_relaxed128(dst + 8192 * k, set_tag(x[0], tag, epoch), x[1], x[2], x[3]);
          }
          a += 4096;
          dst += 32768;
        }
        arrive1(BAR(B_QTD));
      }
      uint4* gp = G->xs + 256 * bid + i0;
      constexpr int QO = -D_ * 256;
      const uint32_t sa = opaque(base + 16 * i0);
      uint4 q[2];
      if (w == 3) {
        mbar_wait_cluster(BAR(B_ST1));
        if (lane < 8) red_hint(G->hint[5][lane]);
        const uint2 x = lds64(base + OFF_ST + 8 * (lane & 15)), y = lds64(base + OFF_ST + 128 + 8 * (lane & 15));
        float m, sd;
        ln_final(__uint_as_float(x.x) + __uint_as_float(y.x), __uint_as_float(x.y) + __uint_as_float(y.y), m, sd);
        sd = rbf(rcpf(sd));
        const uint32_t mr = pack_bf16(sd, -rbf(m) * sd), tg = lane & 7 ? 0 : lane & 8 ? 1 : 0x8000;
        const uint32_t o = __byte_perm(__shfl_sync(~0u, mr, 2 * lane & 14), __shfl_sync(~0u, mr, (2 * lane & 14) + 1), (lane & 8) ? 0x7632 : 0x5410);
        if (lane < 16) st_relaxed32(&G->st1[lane >> 3][8 * bid + (lane & 7)], (o & ~tg) | ((epoch & 1) * tg));
      }
      if (w == 0) {
        int it = 0;
#pragma unroll 1
        while (__any_sync(~0u, ld_relaxed32(G->hint[5][4 * (bid >> 6) + (bid >> 3 & 3)]) != epoch << 7) && ++it < SPIN_LIMIT);
        if (elect()) { mbar_expect_tx(BAR(B_MR), 8192); bulk_load(base + OFF_MR, G->st1, 8192, BAR(B_MR)); mbar_arrive(BAR(B_QTOK)); }
      }
      mbar_wait(BAR(B_QTOK));
      q[0] = ld_relaxed128(gp + QO);
      q[1] = ld_relaxed128(gp + QO + 128);
#pragma unroll 1
      for (int it = 0; it < SPIN_LIMIT; it++) {
        mbar_wait(BAR(B_MR), it & 1);
        const uint32_t x = lds32(sa + 16 * i0 + OFF_MR), y = lds32(sa + 16 * i0 + OFF_MR + 4096);
        sts32(sa + 16 * i0 + OFF_MR, x & 0xFFFF7FFFu);
        if (bar_all(3, !(((x >> 15 ^ epoch) | (y ^ epoch)) & 1))) break;
        if (w == 0 && elect()) { fence_async_smem(); mbar_expect_tx(BAR(B_MR), 8192); bulk_load(base + OFF_MR, G->st1, 8192, BAR(B_MR)); }
      }
#pragma unroll 1
      for (int c = 0; c < 5; c++) {
        mbar_wait(BAR(B_MODR + c));
        uint4 co = lds128(base + OFF_MODR + 16 * c);
        co.x = bmul2(co.x, co.z); co.y = bmul2(co.y, co.z);
        mbar_wait(BAR(B_PFULL + c));
        const uint32_t pb = sa + tab(T_P, c);
#pragma unroll
        for (int hf = 0; hf < 2; hf++) {
          uint4 y = lds128(pb + 2048 * hf), z = lds128(pb + 2048 * hf + 4096);
          y.x = badd2(y.x, z.x); y.y = badd2(y.y, z.y); y.z = badd2(y.z, z.z); y.w = badd2(y.w, z.w);
          z = lds128(pb + 2048 * hf + 8192);
          uint4 m = lds128(pb + 2048 * hf + 12288);
          y.x = badd2(y.x, badd2(z.x, m.x)); y.y = badd2(y.y, badd2(z.y, m.y)); y.z = badd2(y.z, badd2(z.z, m.z)); y.w = badd2(y.w, badd2(z.w, m.w));
          z = lds128(sa + OFF_MR + 2048 * hf);
          m = lds128(sa + OFF_MR + 2048 * hf + 4096);
#pragma unroll 1
          for (int it = 0; __any_sync(~0u, (q[hf].x ^ epoch) & tag) && it < SPIN_LIMIT; it++) {
            q[hf] = ld_relaxed128(gp + QO + 128 * hf);
          }
          y.x = bfma2(bfma2(bfma2(q[hf].x, z.x, m.x), co.y, co.x), y.x, q[hf].x);
          if (hf) {
            __syncwarp();
            asm volatile("{.reg .pred p; elect.sync _|p, 0xffffffff; @p red.relaxed.gpu.global.add.u32 [%0], 1; @p mbarrier.arrive.shared::cta.b64 _, [%1];}"
                         ::"l"(G->xsh[c][2 * w + (blockIdx.x >> 6)]), "r"(BAR(B_PEMPTY + c)), "r"(y.x) : "memory");
          }
          y.y = bfma2(bfma2(bfma2(q[hf].y, z.y, m.y), co.y, co.x), y.y, q[hf].y);
          y.z = bfma2(bfma2(bfma2(q[hf].z, z.z, m.z), co.y, co.x), y.z, q[hf].z);
          y.w = bfma2(bfma2(bfma2(q[hf].w, z.w, m.w), co.y, co.x), y.w, q[hf].w);
          st_relaxed128(gp + 128 * hf, set_tag(bmul2(y.x, co.w), tag, epoch), bmul2(y.y, co.w), bmul2(y.z, co.w), bmul2(y.w, co.w));
          asm volatile("{.reg .pred p; .reg .b32 t; setp.ne.u32 p, %5, 0; max.u32 t, %1, 1; @!p st.relaxed.gpu.global.v4.u32 [%0+%6], {t,%2,%3,%4}; @p st.relaxed.gpu.global.v4.u32 [%0+%7], {t,%2,%3,%4};}"
                       ::"l"(gp + 128 * hf), "r"(y.x), "r"(y.y), "r"(y.z), "r"(y.w), "r"(epoch & 1), "n"(D_ * 4096), "n"(D_ * 8192) : "memory");
          if (c < 4) q[hf] = ld_relaxed128(gp + QO + 32768 + 128 * hf);
        }
        gp += 32768;
      }
    }
    int h, j, r;
    ffn_role(h, j, r);
    {
      REGION_IDS;
      mbar_wait(BAR(B_UVB));
      float d[12] = {};
      fence_regs(d);
      wg_fence();
#pragma unroll
      for (int k = 0; k < 15; k++) {
        if (k == 12) { wg_commit(); mbar_wait(BAR(B_UVE)); wg_fence(); }
        wg_ss8_10(d + 4 * (k % 3), mkdesc(DB + (k < 12 ? OFF_UV + 12288 * (k / 6) + 4096 * (k % 3) + 2048 * (k / 3 & 1) : OFF_UVE + 2048 * (k % 3)), 16, 1024, 1),
                  mkdesc(DB + OFF_CO + 64 * (k / 3), 32, 128, 0), 1);
      }
      wg_commit();
      const int row = (r & 14) + (lane >> 2 & 1);
      uint32_t* dst = &G->uv[4 * h + j][32 * row + 4 * ((2 * w ^ row) & 6) + (lane & 3)];
      const uint32_t tag = !(lane & 3);
      wg_wait<0>();
      fence_regs(d);
      if (elect()) { red_hint(G->hint[8][4 * h + j]); mbar_arrive(BAR(B_UVD)); }
      uint32_t x[6];
#pragma unroll
      for (int k = 0; k < 6; k++) asm volatile("movmatrix.sync.aligned.m8n8.trans.b16 %0, %1;" : "=r"(x[k]) : "r"(pack_bf16(d[2 * k], d[2 * k + 1])));
      if (lane < 8) {
#pragma unroll
        for (int k = 0; k < 6; k++) st_relaxed32(dst + 512 * w_block(r & 1, k >> 1) + ((4 * k ^ lane) & 4), set_tag(x[k], tag, epoch));
      }
    }
    {
      REGION_IDS;
      {
        uint2 g0, g1;
        int it = 0;
#pragma unroll 1
        do {
          g0 = ld_relaxed64(&G->modv[1][128 * j + i0]);
          g1 = ld_relaxed64(&G->modv[1][512 + 32 * j + lane]);
        } while (__any_sync(~0u, ((g0.x ^ epoch) | (g0.y ^ epoch) | (g1.x ^ epoch) | (g1.y ^ epoch)) & 1) && ++it < SPIN_LIMIT);
        sts32(base + OFF_GB + 4 * (i0 ^ 32 * (j & 1)), mod_sum(g0));
        sts32(base + OFF_GB + 512 + 4 * lane, mod_sum(g1));
      }
      if (w == 0) {
        int it = 0;
#pragma unroll 1
        while (__any_sync(~0u, ld_relaxed32(G->hint[8][4 * h + j]) != 64 * epoch) && ++it < SPIN_LIMIT);
      }
#pragma unroll 1
      for (int it = 0; it < SPIN_LIMIT; it++) {
        if (w == 0 && elect()) { mbar_expect_tx(BAR(B_BX), 12288); bulk_load(base + OFF_BX, G->uv[4 * h + j], 12288, BAR(B_BX)); }
        mbar_wait(BAR(B_BX), it & 1);
        uint32_t x = 0;
#pragma unroll
        for (int k = 0; k < 6; k++) x |= lds32(base + OFF_BX + 16 * i0 + 2048 * k) ^ epoch;
        if (bar_all(3, !(x & 1))) break;
      }
      const uint32_t* sp = &G->st2[2 * r + (h ^ (w >> 1))][0][2 * (i0 & 63)];
      uint2 x[4];
      int it = 0;
#pragma unroll 1
      do {
#pragma unroll
        for (int k = 0; k < 4; k++) x[k] = ld_relaxed64(sp + 128 * k);
      } while (__any_sync(~0u, ((x[0].x ^ epoch) | (x[1].x ^ epoch) | (x[2].x ^ epoch) | (x[3].x ^ epoch)) & 1) && ++it < SPIN_LIMIT);
      float m, sd;
      ln_final((__uint_as_float(x[0].x) + __uint_as_float(x[1].x)) + (__uint_as_float(x[2].x) + __uint_as_float(x[3].x)),
               (__uint_as_float(x[0].y) + __uint_as_float(x[1].y)) + (__uint_as_float(x[2].y) + __uint_as_float(x[3].y)), m, sd);
      const uint32_t e = pack_bf16(-m, sd);
      sts128(base + OFF_AX + 16 * i0, e, e, e, e);
      sts32(base + OFF_RT + 4 * i0, __float_as_uint(rcpf(sd)));
      fence_async_smem();
      arrive1(BAR(B_EXT));
      const int id = 16 * r + 4 * h + fslice(j, w);
#pragma unroll 1
      for (int q = w == 3 ? 3 : 0; q < 3; q++) {
        const int m = 3 * q + w;
        const uint4* src = G->hh + id * 1536 + 512 * q;
        it = 0;
#pragma unroll 1
        while (__any_sync(~0u, ld_relaxed32(&G->hhf[8 * id + 64 * (lane & 1) + q]) != 4 * epoch) && ++it < SPIN_LIMIT);
        mbar_wait(BAR(P.hid[2][m]));
        if (elect()) {
          bulk_load(base + OFF_A + h * ARING + P.hid[h][m], src, ASLOT, BAR(B_FULL + 23 + m));
          bulk_load(base + OFF_A + ARING - h * ARING + P.hid[h ^ 1][m], src + 8 * 1536, ASLOT, BAR(B_FULL + 23 + m));
        }
      }
    }
  } else {
    asm volatile("setmaxnreg.inc.sync.aligned.u32 224;");
    LAUNCHES;
    if (wg == 1) silu_vector(P.c, base);
    uint32_t par = EPOCH & 1;
    cluster_wait();
    {
      float acc[128];
      uint32_t A[64];
#pragma unroll
      for (int i = 0; i < 64; i++) A[i] = 0;
      int c = wg;
#pragma unroll 1
      for (uint64_t prog = P.prog[wg]; prog; prog >>= 8) {
        REGION_IDS;
        const int s = prog & 7;
        if (s < 5) {
          const uint32_t a = base + tab(T_KV, s) + 128 * (lane & 3) + ((w ^ (lane & 3)) << 4) + 4 * (lane & 16) + (lane & 12), keep = ~(lane & 1), bit = par & lane;
          uint4* dst = G->xr + (128 * s + 64 * (bid & 1) + 8 * w + 2 * (lane & 16) + (lane >> 1 & 6)) * 256 + 255 - 4 * (bid >> 1) - (lane & 3);
          mbar_wait(BAR(B_KV));
          mbar_wait(BAR(B_KV + s));
          const uint4 wv = lds128(base + OFF_TAP + 512 * s + 64 * w + 16 * (lane & 16) + 4 * (lane & 12));
          uint32_t kk[11], r[8];
#pragma unroll
          for (int k = 0; k < 11; k++) kk[k] = k < 3 ? lds32((a ^ (64 * (k & 1))) + KV_H + 512 * k) : lds32((a ^ (64 * (~k & 1))) + 512 * (k - 3));
          if (elect()) red_hint(G->hint[s][4 * (bid & 1) + w]);
#pragma unroll
          for (int k = 0; k < 8; k++) r[k] = lds32((a ^ (64 * (k & 1))) + KV_V + 512 * k);
          const uint32_t w0 = __byte_perm(wv.x, wv.z, 0x5410), w1 = __byte_perm(wv.x, wv.z, 0x7632),
                         w2 = __byte_perm(wv.y, wv.w, 0x5410), w3 = __byte_perm(wv.y, wv.w, 0x7632);
#pragma unroll
          for (int k = 0; k < 8; k++) r[k] = bmul2(bfma2(kk[k + 3], w0, bfma2(kk[k + 2], w1, bfma2(kk[k + 1], w2, bmul2(kk[k], w3)))), r[k]);
          st_relaxed128(dst, (__byte_perm(r[7], r[6], 0x5410) & keep) | bit, __byte_perm(r[5], r[4], 0x5410), __byte_perm(r[3], r[2], 0x5410), __byte_perm(r[1], r[0], 0x5410));
          st_relaxed128(dst + 256, (__byte_perm(r[7], r[6], 0x7632) & keep) | bit, __byte_perm(r[5], r[4], 0x7632), __byte_perm(r[3], r[2], 0x7632), __byte_perm(r[1], r[0], 0x7632));
        }
        if (prog & 16 && c == nib(P.gpos, bid >> 4)) {
          if (bid >= P.ulo && bid < P.uhi) {
            named_bar(2, 128);
            mbar_wait(BAR(B_WM));
            mod_gemv(G, OFF_WM, bid, w, lane, par);
          }
          arrive1(BAR(B_G3));
        }
        if (prog & 8) {
          float s0 = 0.f, s1 = 0.f, q0 = 0.f, q1 = 0.f;
          const uint32_t a = OFF_Q + 1024 * w + 128 * (lane & 7) + (((lane >> 3) ^ (lane & 7)) << 4);
          const uint32_t ra = mapa(base + OFF_ST + 128 * (bid & 1) + 64 * (lane & 1) + 16 * w + 8 * (lane >> 2), lane >> 1 & 1), rb = mapa(BAR(B_ST1), lane >> 1 & 1);
          if (w == 3 && elect()) mbar_expect_tx(BAR(B_ST1), 256);
#pragma unroll 1
          for (int k = 0; k < 5; k++) {
            mbar_wait(BAR(B_Q + k));
            const uint32_t o = opaque(base + 4096 * k);
            const uint4 x = lds128(o + a), y = lds128(o + (a ^ 64));
            const uint32_t e[8] = {x.x, x.y, x.z, x.w, y.x, y.y, y.z, y.w};
#pragma unroll
            for (int i = 0; i < 8; i++) { const float lo = bf_lo(e[i]), hi = bf_hi(e[i]); s0 += lo; s1 += hi; q0 = fmaf(lo, lo, q0); q1 = fmaf(hi, hi, q1); }
          }
          s0 += s1; q0 += q1;
          s0 += __shfl_xor_sync(~0u, s0, 8); q0 += __shfl_xor_sync(~0u, q0, 8);
          s0 += __shfl_xor_sync(~0u, s0, 16); q0 += __shfl_xor_sync(~0u, q0, 16);
          if (lane < 8) asm volatile("st.async.shared::cluster.mbarrier::complete_tx::bytes.v2.b32 [%0], {%1,%2}, [%3];" ::"r"(ra), "r"(__float_as_uint(s0)), "r"(__float_as_uint(q0)), "r"(rb) : "memory");
        }
        if (prog & 32) {
          const int L = 16 * w + (lane >> 2) + 2 * (lane & 3) - 7;
          const uint32_t fo = base + ((L & 1) ? F_O + 2 * (L + 1) : F_E + 2 * L);
          mbar_wait(BAR(B_FRDY + c));
          cload<0, 0>(A, fo + tab(T_F, c));
          cload<15, 1>(A, fo + tab(T_F, c));
          arrive1(BAR(B_FL + c));
        }
        if (!(prog & 64)) continue;
        uint32_t xo;
#pragma unroll 1
        for (int it = 0; it < SPIN_LIMIT; it++) {
          xo = tab(T_X, opaque(c));
          mbar_wait(BAR(B_XR + c), it & 1);
          const uint32_t tag = lds32(base + xo + 32 * i0);
          wg_fence();
          csteps<0, 0>(acc, A, mkdesc(DB + xo, 16, 128, 0));
          csteps<15, 6>(acc, A, mkdesc(DB + xo, 16, 128, 0));
          wg_commit();
          if (bar_all(1 + wg, !((tag ^ par) & 1))) break;
          wg_wait<0>();
          if (w == 0 && elect()) { mbar_expect_tx(BAR(B_XR + c), 4096); bulk_load(base + xo, G->xr + (128 * c + bid) * 256, 4096, BAR(B_XR + c)); }
        }
        wg_fence();
        csteps<5, 1>(acc, A, mkdesc(DB + tab(T_X, opaque(c)), 16, 128, 0));
        wg_commit();
        if (c >= 3) mbar_wait(BAR(B_PEMPTY + c - 3));
        wg_wait<0>();
        fence_regs(acc);
        const uint32_t pb = base + tab(T_P, c) + 4096 * w;
#pragma unroll
        for (int k = 0; k < 8; k++) {
          uint32_t p[4];
#pragma unroll
          for (int e = 0; e < 4; e++) { const int i = 4 * k + e; p[e] = i < 31 ? pack_bf16(acc[4 * i] + acc[4 * i + 6], acc[4 * i + 1] + acc[4 * i + 7]) : pack_bf16(acc[124], acc[125]); }
          if (k == 0 && (lane & 3) < w) p[0] = 0;
          stmatrix_x4_t(k == 0 ? pb + 16 * ((255 - lane + 2 * w) & 255) : pb + 16 * (255 - lane + 2 * w) - 512 * k, p[0], p[1], p[2], p[3]);
        }
        arrive1(BAR(B_PFULL + c));
        c += 2;
      }
    }
    uint32_t ck;
    { REGION_IDS; ck = base + OFF_A + wg * ARING + lane * 128 + (((2 * w) ^ (lane & 7)) << 4); }
    const uint32_t abd = DB + OFF_A + wg * ARING;
    auto a_tile = [&](int as, int n, bool first) {
#pragma unroll 1
      for (int it = 0; __any_sync(~0u, ((lds32(ck + as) ^ par) | (lds32(ck + as + (first ? 4096 : 256)) ^ par)) & 1) && it < SPIN_LIMIT; it++) {
        int h, j, r;
        ffn_role(h, j, r);
        if (elect()) {
          const uint32_t dst = base + OFF_A + wg * ARING + as;
          mbar_expect_tx(BAR(B_RETRY + wid), ASLOT);
          if (first) tma2d(dst, &maps.xs, 128 * r + 64 * (h ^ wg), 64 * n, BAR(B_RETRY + wid));
          else bulk_load(dst, G->hh + ((2 * r + (h ^ wg)) * 8 + 4 * h + fslice(j, n % 3)) * 1536 + (n / 3) * 512, ASLOT, BAR(B_RETRY + wid));
        }
        mbar_wait(BAR(B_RETRY + wid), par >> 1);
        par ^= 2;
      }
    };
    float acc[192];
    int ws = 0, as = 0;
#pragma unroll 1
    for (int u = 0; u < 20 - NT; u++) {
      mbar_wait(BAR(B_FULL + u));
      if (!(u & 1)) a_tile(as, u >> 1, true);
      wg_fence();
#pragma unroll
      for (int k = 0; k < 4; k++) wg_ss192_11(acc + 96 * (k & 1), mkdesc(abd + as + k / 2 * 2048, 16, 1024, 1), mkdesc(DB + ws + 12288 * (k & 1) + k / 2 * 2048, 4096, 1024, 1), u + k / 2);
      wg_commit();
      wg_wait<1>();
      if (elect()) mbar_arrive(BAR(B_EMPTY + u - 1));
      ws = next_slot(ws);
      as = as == 5 * ASLOT / 2 ? 0 : as + ASLOT / 2;
    }
    auto tail = [&](int v, int i) {
      const int u = 20 - NT + i / 2;
      if (i < 2 * NT) wg_ss192_11(acc + 96 * v, mkdesc(opaque(abd) + u % 6 * 4096 + (i & 1) * 2048, 16, 1024, 1), mkdesc(DB + u % 5 * WSLOT + (i & 1) * 2048 + 12288 * v, 4096, 1024, 1), 1);
      if (i == 2 * NT) wg_ss192_01(acc + 96 * v, mkdesc(DB + OFF_AX + 1024 * opaque(wg), 0, 128, 0), mkdesc(DB + OFF_BX + 6144 * v, 2048, 1024, 1), 1);
    };
#pragma unroll
    for (int u = 20 - NT; u <= 20; u++) {
      mbar_wait(BAR(u < 20 ? B_FULL + u : B_EXT));
      if (u == 16 || u == 18) a_tile(u % 6 * 4096, u >> 1, true);
      wg_fence();
      tail(0, 2 * (u + NT - 20));
      tail(0, 2 * (u + NT - 20) + 1);
      wg_commit();
      if (u == 20 - NT) { wg_wait<1>(); if (elect()) mbar_arrive(BAR(B_EMPTY + u - 1)); }
    }
    float o[80];
    uint32_t fr[3][16], bo;
    {
      int h, j, r;
      ffn_role(h, j, r);
      REGION_IDS;
      const float r0 = 0.5f * __uint_as_float(lds32(base + OFF_RT + 256 * wg + 64 * w + (lane & 28))), r1 = 0.5f * __uint_as_float(lds32(base + OFF_RT + 256 * wg + 64 * w + 32 + (lane & 28)));
      const int id = (2 * r + (h ^ wg)) * 8 + 4 * h + j;
      uint4* const hdst = G->hh + id * 1536 + 128 * w + (lane ^ lane >> 3);
      const uint32_t keep = ~(~lane & 1), bit = par & ~keep;
      bo = 1024 + ((j & 1) << 23);
      auto own = [&](int i) { wg_rs160_1(o, fr[i >> 2] + 4 * (i & 3), mkdesc(DB + (5 + i / 4) % 6 * WSLOT + (i & 3) * 2048, 8192, bo, 1), i); };
      auto gate = [&](float* g) { g[0] = silu2(g[0] * r0); g[1] = silu2(g[1] * r0); g[2] = silu2(g[2] * r1); g[3] = silu2(g[3] * r1); };
      auto mix = [&](uint32_t* x, const float* g, const float* up) { x[0] = pack_bf16(g[0] * up[0], g[1] * up[1]); x[1] = pack_bf16(g[2] * up[2], g[3] * up[3]); };
      auto hint = [&](int v) { asm volatile("{.reg .pred p; setp.eq.u32 p, %1, 0; @p red.relaxed.gpu.global.add.u32 [%0], 1;}" ::"l"(&G->hhf[id * 8 + v]), "r"(lane) : "memory"); };
      auto put = [&](int v, int k) {
        uint32_t* x = fr[v] + 2 * k;
        const uint32_t t0 = (x[k / 2] & keep) | bit, t1 = (x[5 + k / 2] & keep) | bit;
        if (!v) { x[k / 2] = t0; x[5 + k / 2] = t1; }
        st_relaxed128(hdst + 512 * v + 8 * k, k ? x[0] : t0, k ? t0 : x[2], x[4], x[6]);
        st_relaxed128(hdst + 512 * v + 8 * k + 64, x[1], x[3], k ? x[5] : t1, k ? t1 : x[7]);
      };
      auto move = [&](uint32_t* x) {
#pragma unroll
        for (int k = 0; k < 16; k++) asm volatile("mul.rn.f32 %0, %0, %1;" : "+r"(x[k]) : "f"(P.one));
      };
      wg_fence();
      tail(1, 0);
      tail(1, 1);
      wg_commit();
      wg_wait<1>();
#pragma unroll
      for (int k = 0; k < 96; k++) asm volatile("" : "+f"(acc[k])::"memory");
      if (elect()) mbar_arrive(BAR(B_EMPTY + 18));
#pragma unroll
      for (int k = 15; k >= 0; k--) {
        gate(acc + (k < 8 ? 64 + 4 * k : 4 * k - 32));
        if (k >= 8) mix(fr[0] + 2 * k - 16, acc + 4 * k - 32, acc + 4 * k);
        if (k == 12 || k == 8) put(0, k - 8);
        if (9 - k / 2 <= 2 * NT) pin(P.ulo, k < 8 ? __float_as_uint(acc[67 + 4 * k]) : fr[0][2 * k - 15]);
        if (k == 9) hint(0);
        if (!(k & 1)) tail(1, 9 - k / 2);
        if (k == 18 - 4 * NT) wg_commit();
        if (!(k & 1) && 9 - k / 2 <= 2 * NT) split(P.ulo, k);
      }
      move(fr[0]);
      mbar_wait(BAR(B_FULL + 20));
      mbar_wait(BAR(B_FULL + 21));
      wg_wait<0>();
#pragma unroll
      for (int k = 96; k < 192; k++) asm volatile("" : "+f"(acc[k])::"memory");
      if (elect()) mbar_arrive(BAR(B_EMPTY + 19));
#pragma unroll
      for (int k = 7; k >= 0; k--) mix(fr[1] + 2 * k, acc + 64 + 4 * k, acc + 160 + 4 * k);
#pragma unroll
      for (int k = 0; k < 4; k++) pin4(P.ulo, fr[1] + 4 * k);
      wg_fence();
      own(0);
      own(1);
      split(P.ulo, 15);
      put(1, 4);
      hint(1);
      own(2);
      put(1, 0);
      own(3);
      wg_commit();
      split(P.ulo, 16);
#pragma unroll
      for (int k = 7; k >= 0; k--) {
        gate(acc + 96 + 4 * k);
        mix(fr[2] + 2 * k, acc + 96 + 4 * k, acc + 128 + 4 * k);
        if (!(k & 3)) put(2, k);
        if (k) pin(P.ulo, fr[2][2 * k + 1]);
        if (k == 1) hint(2);
        if (k & 1) own(7 - k / 2);
        if (k == 5 || k == 1) wg_commit();
        if (k == 5) { wg_wait<1>(); if (elect()) mbar_arrive(BAR(B_EMPTY + 20)); }
        if (k & 1) split(P.ulo, 16 + k);
      }
      mbar_wait(BAR(B_FULL + 22));
      wg_fence();
#pragma unroll
      for (int i = 8; i < 12; i++) own(i);
      wg_commit();
      wg_wait<1>();
      if (elect()) mbar_arrive(BAR(B_EMPTY + 21));
      ck = base + OFF_A + wg * ARING + 2048 * w + 516 * (lane >> 3) + 144 * (lane >> 2 & 1) + 32 * (lane & 3);
    }
    uint32_t x1[40], gr[40];
    if (!wg) {
      REGION_IDS;
      const uint32_t xa = base + (lane >> 4) * 1024 + (lane & 7) * 128 + (((2 * w + ((lane >> 3) & 1)) ^ (lane & 7)) << 4);
      mbar_wait(BAR(B_FULL + 32));
#pragma unroll
      for (int k = 0; k < 10; k++) ldmatrix_x4_t(x1 + 4 * k, xa + (k < 6 ? OFF_X1 + k / 2 * WSLOT + (k & 1) * 2048 : OFF_SX + 2048 * (k - 6)));
    }
#pragma unroll 1
    for (int u = 23; u < 32; u++) {
      as = P.hid[wg][u - 23];
      const uint64_t wd = mkdesc(0, 0, bo, 1) | P.w2t[u - 20].x;
      mbar_wait(BAR(B_FULL + u));
      a_tile(as, u - 23, false);
      if (wg || u < LAG2) {
        wg_fence();
#pragma unroll
        for (int kk = 0; kk < 4; kk++) wg_ss160_01(o, mkdesc(abd + as + kk / 2 * 512 + (kk & 1) * 32, 16, 1024, 2), wd + kk * 128, 1);
        wg_commit();
        if (u == 31 && elect()) mbar_arrive(BAR(B_LAG));
        wg_wait<1>();
        if (elect()) mbar_arrive(BAR(B_EMPTY + u - 1));
      }
      if (u == LAG2 - 1 && !wg) {
        REGION_IDS;
        const float r0 = __uint_as_float(lds32(base + OFF_RT + 64 * w + (lane & 28))), r1 = __uint_as_float(lds32(base + OFF_RT + 64 * w + 32 + (lane & 28)));
#pragma unroll
        for (int k = 0; k < 20; k++) {
          const uint2 g = lds64(base + OFF_GB + 32 * k + 8 * (lane & 3));
          gr[2 * k] = pack_bf16(__uint_as_float(g.x) * r0, __uint_as_float(g.y) * r0);
          gr[2 * k + 1] = pack_bf16(__uint_as_float(g.x) * r1, __uint_as_float(g.y) * r1);
        }
        wg_wait<0>();
        if (elect()) mbar_arrive(BAR(B_EMPTY + 27));
      }
    }
    int h, j, r;
    ffn_role(h, j, r);
    REGION_IDS;
    const uint32_t xb = base + OFF_XCH + 5120 * w;
    if (wg) {
      const uint32_t rdst = mapa(xb + 16 * lane, h ^ 1), rbar = mapa(BAR(B_FULL), h ^ 1);
      mbar_wait(BAR(B_XFREE));
      wg_wait<0>();
      fence_regs(o);
#pragma unroll
      for (int k = 0; k < 10; k++)
        asm volatile("st.async.shared::cluster.mbarrier::complete_tx::bytes.v4.b32 [%0], {%1,%2,%3,%4}, [%5];" ::"r"(rdst + 512 * k), "r"(pack_bf16(o[8 * k], o[8 * k + 1])),
                     "r"(pack_bf16(o[8 * k + 2], o[8 * k + 3])), "r"(pack_bf16(o[8 * k + 4], o[8 * k + 5])), "r"(pack_bf16(o[8 * k + 6], o[8 * k + 7])), "r"(rbar + 8 * (k / 4)) : "memory");
    } else {
      mbar_wait(BAR(B_LAG));
      wg_fence();
#pragma unroll
      for (int i = 4 * LAG2; i < 128; i++) wg_ss160_01(o, mkdesc(DB + hid_at(i / 4 - 23, 0) + (i & 2) * 256 + (i & 1) * 32, 16, 1024, 2), mkdesc(DB + w2_at(i / 4 - 20) + (i & 3) * 2048, w2_step(i / 4 - 20), bo, 1), 1);
      wg_commit();
      const int row = 128 * r + 64 * h + 16 * w;
      auto merge = [&](int e0, int e1) {
#pragma unroll
        for (int e = e0; e < e1; e++) {
          if (e % 4 == 0) mbar_wait_cluster(BAR(B_FULL + e / 4), 1);
          const uint4 p = lds128(xb + 16 * lane + 512 * e);
          x1[4 * e] = bfma2(gr[4 * e], p.x, x1[4 * e]); x1[4 * e + 1] = bfma2(gr[4 * e + 1], p.y, x1[4 * e + 1]);
          x1[4 * e + 2] = bfma2(gr[4 * e + 2], p.z, x1[4 * e + 2]); x1[4 * e + 3] = bfma2(gr[4 * e + 3], p.w, x1[4 * e + 3]);
        }
        __syncwarp();
      };
      merge(0, MG);
      wg_wait<0>();
      fence_regs(o);
#pragma unroll
      for (int k = 0; k < 10; k++) {
        if (k >= MG && k % 4 == 0) merge(k, k < 8 ? k + 4 : 10);
        uint32_t y[4];
#pragma unroll
        for (int e = 0; e < 4; e++) y[e] = bfma2(gr[4 * k + e], pack_bf16(o[8 * k + 2 * e], o[8 * k + 2 * e + 1]), x1[4 * k + e]);
        stmatrix_x4(k < 8 ? xb + 2048 * (k >> 2) + (lane & 15) * 128 + (((2 * (k & 3) + (lane >> 4)) ^ (lane & 7) ^ 4 * (j & 1)) << 4)
                          : xb + 4096 + (lane & 15) * 64 + (((2 * (k & 1) + (lane >> 4)) ^ (lane >> 1 & 3)) << 4), y[0], y[1], y[2], y[3]);
        if ((k & 3) == 3 || k == 9) {
          fence_async_smem();
          __syncwarp();
          if (lane == 0) tma2d_store(k < 8 ? &maps.outa : &maps.outb, k < 8 ? 128 * j + 64 * (k >> 2) : 512 + 32 * j, row, xb + 2048 * (k >> 2));
        }
      }
      if (lane == 0) { bulk_commit(); bulk_wait_read(); }
    }
  }
}

typedef CUresult (*EncFn)(CUtensorMap*, CUtensorMapDataType, cuuint32_t, void*, const cuuint64_t*, const cuuint64_t*, const cuuint32_t*,
                          const cuuint32_t*, CUtensorMapInterleave, CUtensorMapSwizzle, CUtensorMapL2promotion, CUtensorMapFloatOOBfill);
static int enc_err = 0;
static void enc(EncFn fn, CUtensorMap* m, const void* p, int rank, const cuuint64_t* gd, const cuuint64_t* gs, const cuuint32_t* bd, CUtensorMapSwizzle sw) {
  cuuint32_t es[5] = {1, 1, 1, 1, 1};
  enc_err = 2 * enc_err + (fn(m, CU_TENSOR_MAP_DATA_TYPE_BFLOAT16, rank, (void*)p, gd, gs, bd, es, CU_TENSOR_MAP_INTERLEAVE_NONE, sw,
                              CU_TENSOR_MAP_L2_PROMOTION_L2_128B, CU_TENSOR_MAP_FLOAT_OOB_FILL_NONE) != CUDA_SUCCESS);
}

extern "C" void kernel_launch(void* const* d_in, const int* in_sizes, int n_in, void* d_out, int out_size) {
  const bf16 *q = (const bf16*)d_in[0], *k = (const bf16*)d_in[1], *v = (const bf16*)d_in[2], *shift = (const bf16*)d_in[3],
             *ssmk = (const bf16*)d_in[4], *ssmd = (const bf16*)d_in[5], *w1 = (const bf16*)d_in[7], *w3 = (const bf16*)d_in[8],
             *w2 = (const bf16*)d_in[9], *c = (const bf16*)d_in[10], *wmod = (const bf16*)d_in[11];
  EncFn fn = nullptr;
  cudaDriverEntryPointQueryResult qr;
  cudaGetDriverEntryPoint("cuTensorMapEncodeTiled", (void**)&fn, cudaEnableDefault, &qr);
  Scratch* pg;
  cudaGetSymbolAddress((void**)&pg, g_s);
  Maps maps;
  enc_err = 0;
  const CUtensorMapSwizzle S128 = CU_TENSOR_MAP_SWIZZLE_128B;
  { cuuint64_t gd[3] = {D_, S_ / 8, 8}, gs[2] = {D_ * 16, D_ * 2}; cuuint32_t b[3] = {64, 4, 8};
    enc(fn, &maps.km, k, 3, gd, gs, b, S128);
    enc(fn, &maps.v, v, 3, gd, gs, b, S128);
    enc(fn, &maps.q, q, 3, gd, gs, b, S128);
    b[2] = 3;
    enc(fn, &maps.kh, k, 3, gd, gs, b, S128); }
  { cuuint64_t gd[3] = {256, 2, 5}, gs[2] = {512, 1024}; cuuint32_t b[3] = {256, 1, 5};
    enc(fn, &maps.tap, shift, 3, gd, gs, b, CU_TENSOR_MAP_SWIZZLE_NONE); }
  { cuuint64_t gd[3] = {6 * D_, D_, 1}, gs[2] = {6 * D_ * 2, 6 * D_ * 2 * D_}; cuuint32_t b[3] = {64, 64, 1};
    enc(fn, &maps.wm, wmod, 3, gd, gs, b, S128); }
  { cuuint64_t gd[3] = {64, D_, F_ / 64}, gs[2] = {F_ * 2, 128}; cuuint32_t b[3] = {64, 32, 3};
    enc(fn, &maps.w1, w1, 3, gd, gs, b, S128);
    enc(fn, &maps.w3, w3, 3, gd, gs, b, S128);
    b[1] = 16;
    enc(fn, &maps.w1e, w1, 3, gd, gs, b, S128);
    enc(fn, &maps.w3e, w3, 3, gd, gs, b, S128);
    b[1] = 32; b[2] = 1;
    enc(fn, &maps.w1s, w1, 3, gd, gs, b, S128);
    enc(fn, &maps.w3s, w3, 3, gd, gs, b, S128); }
  { cuuint64_t gd[2] = {S_, D_}, gs[1] = {S_ * 2}; cuuint32_t b1[2] = {64, 64}, b2[2] = {64, 32};
    enc(fn, &maps.xs, pg->xs, 2, gd, gs, b1, S128);
    gd[1] = 2 * D_;
    enc(fn, &maps.x1b, pg->x1, 2, gd, gs, b2, S128);
    enc(fn, &maps.x1s, pg->x1, 2, gd, gs, b2, CU_TENSOR_MAP_SWIZZLE_NONE); }
  { cuuint64_t gd[5] = {D_, 2, 4, 4, 48}, gs[4] = {D_ * 2, D_ * 4, D_ * 16, D_ * 64}; cuuint32_t b[5] = {64, 2, 4, 4, 2};
    enc(fn, &maps.w2a, w2, 5, gd, gs, b, S128);
    gs[1] = D_ * 16; gs[2] = D_ * 4;
    enc(fn, &maps.w2b, w2, 5, gd, gs, b, S128); }
  { cuuint64_t gd[2] = {D_, S_}, gs[1] = {D_ * 2}; cuuint32_t b1[2] = {64, 16}, b2[2] = {32, 16};
    enc(fn, &maps.outa, d_out, 2, gd, gs, b1, S128);
    enc(fn, &maps.outb, d_out, 2, gd, gs, b2, CU_TENSOR_MAP_SWIZZLE_64B); }
  if (enc_err) return;
  cudaFuncSetAttribute(k_fused, cudaFuncAttributeMaxDynamicSharedMemorySize, SMEM_BYTES);
  cudaLaunchConfig_t cfg = {132, 512, SMEM_BYTES};
  cudaLaunchAttribute at = {cudaLaunchAttributeClusterDimension};
  at.val.clusterDim.x = 2; at.val.clusterDim.y = at.val.clusterDim.z = 1;
  cfg.attrs = &at; cfg.numAttrs = 1;
  int nc = 0;
  cudaOccupancyMaxActiveClusters(&nc, k_fused, &cfg);
  Ptrs P = {ssmk, c, ssmd, pg, 0x1313131313131313ull, {0x67442360, 0x1767620F01}, 0x55555555u, 64, 120, 0x3A4, 0x354, 1.f};
  if (nc < 66) { P.wms = 0x1313131313131000ull; P.prog[1] = 0x1777720F01; P.gpos = 0x55555531u; P.ulo = 0; P.uhi = 120; }
  const char* sched = "k10v14f04q04q14q24q34q44k24v24f14k34v34f24k44v44f34f44n04n02n04n06n06n06";
  int t = 1150, pace = 350;
  for (int e = 0; e < NE; e++) {
    const char x = sched[3 * e];
    const int r = sched[3 * e + 1] - '0', kind = x == 'k' ? 0 : x == 'v' ? 1 : x == 'q' ? 2 : x == 'f' ? 3 : 4;
    t += (sched[3 * e + 2] - '0') * pace / 4;
    P.sched[e] = make_uint2(t | kind << 16 | r << 20, (kind < 2 ? tab(T_KV, r) + kind * KV_V : kind == 2 ? OFF_Q + 4096 * r : tab(T_F, r) + F_E) | (r + (kind < 2 ? B_KV : kind == 2 ? B_Q : B_FRAW)) << 18);
  }
  const int dep[5] = {B_FL + 1, B_FL + 2, B_PFULL + 2, B_G3, B_PEMPTY + 2};
  for (int u = 0; u < 20; u++) P.wdep[u] = u % 5 * WSLOT | (~u & 1) << 12 | (u < 5 ? dep[u] : B_EMPTY + u - 5);
  for (int v = 0; v < 12; v++) P.w2t[v] = make_uint2(w2_desc(v), v ? B_EMPTY + (v > 5 ? 15 + v : v > 3 ? 14 + v : v > 1 ? 16 : 15) : B_UVD);
  for (int m = 0; m < 9; m++) { P.hid[0][m] = hid_at(m, 0) - OFF_A; P.hid[1][m] = hid_at(m, 1) - OFF_A - ARING; P.hid[2][m] = B_EMPTY + 19 + (m > 2 ? m : m / 2); }
  k_fused<<<nc < 66 ? 128 : 132, 512, SMEM_BYTES, cudaStreamPerThread>>>(P, maps);
}
```

```cpp
#include <cuda_runtime.h>
#include <cuda.h>
#include <cuda_bf16.h>
#include <stdint.h>
#include <stdlib.h>

typedef __nv_bfloat16 bf16;
constexpr int S_ = 2048, D_ = 640, F_ = 1536;

struct Scratch {
  uint32_t st1[2][1024];
  uint32_t st2[32][4][128];
  uint2 modc[128][32];
  uint2 modv[3][D_];
  uint32_t uv[8][3072];
  unsigned hint[9][8][32];
  unsigned xsh[5][8][32], hhf[256 * 8];
  uint4 xr[D_ * 256];
  uint4 qt[D_ * 256];
  uint4 xs[D_ * 256];
  uint4 x1[2][D_ * 256];
  uint4 hh[32 * 8 * 1536];
};
__device__ __align__(1024) Scratch g_s;

__device__ __forceinline__ uint32_t smem_u32(const void* p) { return (uint32_t)__cvta_generic_to_shared(p); }
__device__ __forceinline__ void mbar_expect_tx(uint32_t b, uint32_t n) { asm volatile("mbarrier.arrive.expect_tx.shared::cta.b64 _, [%0], %1;" ::"r"(b), "r"(n) : "memory"); }
__device__ __forceinline__ void mbar_arrive(uint32_t b) { asm volatile("mbarrier.arrive.shared::cta.b64 _, [%0];" ::"r"(b) : "memory"); }
__device__ __forceinline__ void mbar_arrive2(uint32_t b) { asm volatile("mbarrier.arrive.shared::cta.b64 _, [%0], 2;" ::"r"(b) : "memory"); }
__device__ __forceinline__ uint32_t mapa(uint32_t a, uint32_t cta) { uint32_t r; asm volatile("mapa.shared::cluster.u32 %0, %1, %2;" : "=r"(r) : "r"(a), "r"(cta)); return r; }
__device__ __forceinline__ void mbar_arrive_remote(uint32_t rb) { asm volatile("mbarrier.arrive.shared::cluster.b64 _, [%0];" ::"r"(rb) : "memory"); }
constexpr int SPIN_LIMIT = 1 << 16;
template <int N> __device__ __forceinline__ void mbar_init(uint32_t b, uint32_t count) {
#pragma unroll
  for (int i = 0; i < N; i++) asm volatile("mbarrier.init.shared::cta.b64 [%0], %1;" ::"r"(b + 8 * i), "r"(count) : "memory");
}
__device__ __forceinline__ bool elect() { uint32_t p; asm volatile("{.reg .pred q; elect.sync _|q, 0xffffffff; selp.u32 %0, 1, 0, q;}" : "=r"(p)); return p; }
__device__ __forceinline__ void arrive1(uint32_t b) { __syncwarp(); if (elect()) mbar_arrive(b); }
__device__ __forceinline__ bool mbar_test(uint32_t b) {
  uint32_t ok;
  asm volatile("{.reg .pred p; mbarrier.test_wait.parity.shared::cta.b64 p, [%1], 0; selp.u32 %0,1,0,p;}" : "=r"(ok) : "r"(b) : "memory");
  return ok;
}
#define WAIT_LOOP(sem) "{.reg .pred p; mov.u32 %0, 0; W: mbarrier.try_wait.parity" sem ".shared::cta.b64 p, [%1], %2; @p bra.uni D; add.u32 %0, %0, 1; setp.lt.u32 p, %0, %3; @p bra.uni W; D:}"
__device__ __forceinline__ void mbar_wait(uint32_t b, uint32_t ph = 0) {
  int it;
  asm volatile(WAIT_LOOP("") : "=&r"(it) : "r"(b), "r"(ph), "n"(SPIN_LIMIT) : "memory");
}
__device__ __forceinline__ void mbar_wait_cluster(uint32_t b, uint32_t ph = 0) {
  int it;
  asm volatile(WAIT_LOOP(".acquire.cluster") : "=&r"(it) : "r"(b), "r"(ph), "n"(SPIN_LIMIT) : "memory");
}
__device__ __forceinline__ void wait_clock(uint32_t t) {
  asm volatile("{.reg .pred p; .reg .s32 d; W: mov.u32 d, %%clock; sub.s32 d, d, %0; setp.lt.s32 p, d, 0; @p bra.uni W;}" ::"r"(t) : "memory");
}
__device__ __forceinline__ void tma2d(uint32_t dst, const CUtensorMap* m, int c0, int c1, uint32_t bar) {
  asm volatile("cp.async.bulk.tensor.2d.shared::cluster.global.mbarrier::complete_tx::bytes [%0], [%1, {%3,%4}], [%2];" ::"r"(dst), "l"(m), "r"(bar), "r"(c0), "r"(c1) : "memory");
}
__device__ __forceinline__ void tma3d(uint32_t dst, const CUtensorMap* m, int c0, int c1, int c2, uint32_t bar) {
  asm volatile("cp.async.bulk.tensor.3d.shared::cluster.global.mbarrier::complete_tx::bytes [%0], [%1, {%3,%4,%5}], [%2];" ::"r"(dst), "l"(m), "r"(bar), "r"(c0), "r"(c1), "r"(c2) : "memory");
}
__device__ __forceinline__ void tma5d(uint32_t dst, const CUtensorMap* m, int c0, int c4, uint32_t bar) {
  asm volatile("cp.async.bulk.tensor.5d.shared::cluster.global.mbarrier::complete_tx::bytes [%0], [%1, {%4,%3,%3,%3,%5}], [%2];" ::"r"(dst), "l"(m), "r"(bar), "r"(0), "r"(c0), "r"(c4) : "memory");
}
__device__ __forceinline__ void tma2d_store(const CUtensorMap* m, int c0, int c1, uint32_t src) {
  asm volatile("cp.async.bulk.tensor.2d.global.shared::cta.bulk_group [%0, {%2,%3}], [%1];" ::"l"(m), "r"(src), "r"(c0), "r"(c1) : "memory");
}
__device__ __forceinline__ void bulk_load(uint32_t dst, const void* src, uint32_t bytes, uint32_t bar) {
  asm volatile("cp.async.bulk.shared::cluster.global.mbarrier::complete_tx::bytes [%0], [%1], %2, [%3];" ::"r"(dst), "l"(src), "r"(bytes), "r"(bar) : "memory");
}
__device__ __forceinline__ void prefetch_map(const CUtensorMap* m) { asm volatile("prefetch.tensormap [%0];" ::"l"(m) : "memory"); }
__device__ __forceinline__ void bulk_commit() { asm volatile("cp.async.bulk.commit_group;" ::: "memory"); }
__device__ __forceinline__ void bulk_wait_read() { asm volatile("cp.async.bulk.wait_group.read 0;" ::: "memory"); }
__device__ __forceinline__ void fence_async_smem() { asm volatile("fence.proxy.async.shared::cta;" ::: "memory"); }
__device__ __forceinline__ void fence_async_all() { asm volatile("fence.proxy.async.global;" ::: "memory"); }
__device__ __forceinline__ void named_bar(int id, int n) { asm volatile("bar.sync %0, %1;" ::"r"(id), "r"(n) : "memory"); }
__device__ __forceinline__ bool bar_all(int id, bool v) {
  uint32_t r;
  asm volatile("{.reg .pred p, q; setp.ne.u32 p, %2, 0; bar.red.and.pred q, %1, 128, p; selp.u32 %0, 1, 0, q;}" : "=r"(r) : "r"(id), "r"((uint32_t)v) : "memory");
  return __all_sync(~0u, r);
}
__device__ __forceinline__ void cluster_wait() { asm volatile("barrier.cluster.wait.aligned;" ::: "memory"); }
__device__ __forceinline__ void wg_fence() { asm volatile("wgmma.fence.sync.aligned;" ::: "memory"); }
__device__ __forceinline__ void wg_commit() { asm volatile("wgmma.commit_group.sync.aligned;" ::: "memory"); }
template <int N> __device__ __forceinline__ void wg_wait() { asm volatile("wgmma.wait_group.sync.aligned %0;" ::"n"(N) : "memory"); }
template <int N> __device__ __forceinline__ void fence_regs(float (&a)[N]) {
#pragma unroll
  for (int i = 0; i < N; i++) asm volatile("" : "+f"(a[i])::"memory");
}
template <int N> __device__ __forceinline__ void fence_n(float* a) {
#pragma unroll
  for (int i = 0; i < N; i++) asm volatile("" : "+f"(a[i])::"memory");
}
__device__ __forceinline__ uint64_t mkdesc(uint32_t addr, uint32_t lbo, uint32_t sbo, uint32_t swz) {
  uint32_t lo = (addr >> 4) | ((lbo >> 4) << 16), hi = (sbo >> 4) | (swz << 30);
  return ((uint64_t)hi << 32) | lo;
}
__device__ __forceinline__ void stmatrix_x4(uint32_t a, uint32_t r0, uint32_t r1, uint32_t r2, uint32_t r3) {
  asm volatile("stmatrix.sync.aligned.m8n8.x4.shared.b16 [%0], {%1,%2,%3,%4};" ::"r"(a), "r"(r0), "r"(r1), "r"(r2), "r"(r3) : "memory");
}
__device__ __forceinline__ void stmatrix_x4_t(uint32_t a, uint32_t r0, uint32_t r1, uint32_t r2, uint32_t r3) {
  asm volatile("stmatrix.sync.aligned.m8n8.x4.trans.shared.b16 [%0], {%1,%2,%3,%4};" ::"r"(a), "r"(r0), "r"(r1), "r"(r2), "r"(r3) : "memory");
}
__device__ __forceinline__ void ldmatrix_x4_t(uint32_t* r, uint32_t a) {
  asm volatile("ldmatrix.sync.aligned.m8n8.x4.trans.shared.b16 {%0,%1,%2,%3}, [%4];" : "=r"(r[0]), "=r"(r[1]), "=r"(r[2]), "=r"(r[3]) : "r"(a) : "memory");
}
__device__ __forceinline__ uint32_t lds32(uint32_t a) { uint32_t v; asm volatile("ld.shared.b32 %0, [%1];" : "=r"(v) : "r"(a) : "memory"); return v; }
__device__ __forceinline__ uint2 lds64(uint32_t a) { uint2 v; asm volatile("ld.shared.v2.b32 {%0,%1}, [%2];" : "=r"(v.x), "=r"(v.y) : "r"(a) : "memory"); return v; }
__device__ __forceinline__ uint4 lds128(uint32_t a) { uint4 v; asm volatile("ld.shared.v4.b32 {%0,%1,%2,%3}, [%4];" : "=r"(v.x), "=r"(v.y), "=r"(v.z), "=r"(v.w) : "r"(a) : "memory"); return v; }
__device__ __forceinline__ void sts32(uint32_t a, uint32_t v) { asm volatile("st.shared.b32 [%0], %1;" ::"r"(a), "r"(v) : "memory"); }
__device__ __forceinline__ void sts64(uint32_t a, uint32_t x, uint32_t y) { asm volatile("st.shared.v2.b32 [%0], {%1,%2};" ::"r"(a), "r"(x), "r"(y) : "memory"); }
__device__ __forceinline__ void sts128(uint32_t a, uint32_t x, uint32_t y, uint32_t z, uint32_t w) { asm volatile("st.shared.v4.b32 [%0], {%1,%2,%3,%4};" ::"r"(a), "r"(x), "r"(y), "r"(z), "r"(w) : "memory"); }
__device__ __forceinline__ uint4 ld_relaxed128(const void* p) { uint4 v; asm volatile("ld.relaxed.gpu.global.v4.u32 {%0,%1,%2,%3}, [%4];" : "=r"(v.x), "=r"(v.y), "=r"(v.z), "=r"(v.w) : "l"(p) : "memory"); return v; }
__device__ __forceinline__ uint2 ld_relaxed64(const void* p) { uint2 v; asm volatile("ld.relaxed.gpu.global.v2.u32 {%0,%1}, [%2];" : "=r"(v.x), "=r"(v.y) : "l"(p) : "memory"); return v; }
__device__ __forceinline__ uint32_t ld_relaxed32(const void* p) { uint32_t v; asm volatile("ld.relaxed.gpu.global.u32 %0, [%1];" : "=r"(v) : "l"(p) : "memory"); return v; }
__device__ __forceinline__ void st_relaxed128(void* p, uint32_t x, uint32_t y, uint32_t z, uint32_t w) { asm volatile("st.relaxed.gpu.global.v4.u32 [%0], {%1,%2,%3,%4};" ::"l"(p), "r"(x), "r"(y), "r"(z), "r"(w) : "memory"); }
__device__ __forceinline__ void st_relaxed32(void* p, uint32_t x) { asm volatile("st.relaxed.gpu.global.u32 [%0], %1;" ::"l"(p), "r"(x) : "memory"); }
__device__ __forceinline__ void red_hint(unsigned* p) { asm volatile("red.relaxed.gpu.global.add.u32 [%0], 1;" ::"l"(p) : "memory"); }
__device__ __forceinline__ void publish(uint32_t* p, uint32_t x) { asm volatile("{.reg .b32 t; atom.relaxed.gpu.global.exch.b32 t, [%0], %1;}" ::"l"(p), "r"(x) : "memory"); }
__device__ __forceinline__ uint32_t ldg32(const void* p) { uint32_t v; asm volatile("ld.global.nc.L1::no_allocate.b32 %0, [%1];" : "=r"(v) : "l"(p)); return v; }
__device__ __forceinline__ uint32_t pack_bf16(float lo, float hi) { uint32_t r; asm("cvt.rn.bf16x2.f32 %0, %1, %2;" : "=r"(r) : "f"(hi), "f"(lo)); return r; }
__device__ __forceinline__ float bf_lo(uint32_t v) { return __uint_as_float(v << 16); }
__device__ __forceinline__ float bf_hi(uint32_t v) { return __uint_as_float(v & 0xFFFF0000u); }
__device__ __forceinline__ uint32_t bmul2(uint32_t a, uint32_t b) { uint32_t r; asm("mul.rn.bf16x2 %0, %1, %2;" : "=r"(r) : "r"(a), "r"(b)); return r; }
__device__ __forceinline__ uint32_t badd2(uint32_t a, uint32_t b) { uint32_t r; asm("add.rn.bf16x2 %0, %1, %2;" : "=r"(r) : "r"(a), "r"(b)); return r; }
__device__ __forceinline__ uint32_t bfma2(uint32_t a, uint32_t b, uint32_t c) { uint32_t r; asm("fma.rn.bf16x2 %0, %1, %2, %3;" : "=r"(r) : "r"(a), "r"(b), "r"(c)); return r; }
__device__ __forceinline__ uint32_t set_tag(uint32_t x, uint32_t mask, uint32_t e) { uint32_t r; asm("lop3.b32 %0, %1, %2, %3, 0xB8;" : "=r"(r) : "r"(x), "r"(mask), "r"(e)); return r; }
__device__ __forceinline__ uint32_t opaque(uint32_t x) { asm volatile("" : "+r"(x)); return x; }
__device__ __forceinline__ float rbf(float x) { return __bfloat162float(__float2bfloat16(x)); }
__device__ __forceinline__ float silu_f(float x) {
  float e, r;
  asm("ex2.approx.ftz.f32 %0, %1;" : "=f"(e) : "f"(x * -1.4426950408889634f));
  asm("rcp.approx.ftz.f32 %0, %1;" : "=f"(r) : "f"(1.f + e));
  return x * r;
}
__device__ __forceinline__ float silu2(float x) {
  float t;
  asm("tanh.approx.f32 %0, %1;" : "=f"(t) : "f"(x));
  return fmaf(x, t, x);
}
__device__ __forceinline__ void pin(int off, uint32_t x) { asm volatile("{.reg .pred p; setp.lt.s32 p, %0, 0; @p st.shared.b32 [%0], %1;}" ::"r"(off), "r"(x) : "memory"); }
__device__ __forceinline__ void pin4(int off, const uint32_t* x) { asm volatile("{.reg .pred p; setp.lt.s32 p, %0, 0; @p st.shared.v4.b32 [%0], {%1,%2,%3,%4};}" ::"r"(off), "r"(x[0]), "r"(x[1]), "r"(x[2]), "r"(x[3]) : "memory"); }
__device__ __forceinline__ void split(int x, int n) { asm volatile("{.reg .pred p; setp.eq.s32 p, %0, %1; @p trap;}" ::"r"(x), "r"(~n) : "memory"); }
__device__ __forceinline__ void ln_final(float s, float q, float& m, float& sd) {
  m = s * (1.f / D_);
  asm("sqrt.approx.f32 %0, %1;" : "=f"(sd) : "f"(rbf(rbf(fmaxf(fmaf(-m, m, q * (1.f / D_)), 0.f)) + 1e-5f)));
  sd = rbf(sd);
}
__device__ __forceinline__ float rcpf(float x) { float r; asm("rcp.approx.f32 %0, %1;" : "=f"(r) : "f"(x)); return r; }

__device__ __forceinline__ void wg_rs16_0(float* d, const uint32_t* a, uint64_t db, int sc) {
  asm volatile("{.reg .pred p; setp.ne.b32 p, %13, 0; wgmma.mma_async.sync.aligned.m64n16k16.f32.bf16.bf16 {%0,%1,%2,%3,%4,%5,%6,%7}, {%8,%9,%10,%11}, %12, p, 1, 1, 0;}"
    : "+f"(d[0]),"+f"(d[1]),"+f"(d[2]),"+f"(d[3]),"+f"(d[4]),"+f"(d[5]),"+f"(d[6]),"+f"(d[7]) : "r"(a[0]),"r"(a[1]),"r"(a[2]),"r"(a[3]),"l"(db),"r"(sc));
}
__device__ __forceinline__ void wg_rs32_0(float* d, const uint32_t* a, uint64_t db, int sc) {
  asm volatile("{.reg .pred p; setp.ne.b32 p, %21, 0; wgmma.mma_async.sync.aligned.m64n32k16.f32.bf16.bf16 {%0,%1,%2,%3,%4,%5,%6,%7,%8,%9,%10,%11,%12,%13,%14,%15}, {%16,%17,%18,%19}, %20, p, 1, 1, 0;}"
    : "+f"(d[0]),"+f"(d[1]),"+f"(d[2]),"+f"(d[3]),"+f"(d[4]),"+f"(d[5]),"+f"(d[6]),"+f"(d[7]),"+f"(d[8]),"+f"(d[9]),"+f"(d[10]),"+f"(d[11]),"+f"(d[12]),"+f"(d[13]),"+f"(d[14]),"+f"(d[15]) : "r"(a[0]),"r"(a[1]),"r"(a[2]),"r"(a[3]),"l"(db),"r"(sc));
}
__device__ __forceinline__ void wg_rs48_0(float* d, const uint32_t* a, uint64_t db, int sc) {
  asm volatile("{.reg .pred p; setp.ne.b32 p, %29, 0; wgmma.mma_async.sync.aligned.m64n48k16.f32.bf16.bf16 {%0,%1,%2,%3,%4,%5,%6,%7,%8,%9,%10,%11,%12,%13,%14,%15,%16,%17,%18,%19,%20,%21,%22,%23}, {%24,%25,%26,%27}, %28, p, 1, 1, 0;}"
    : "+f"(d[0]),"+f"(d[1]),"+f"(d[2]),"+f"(d[3]),"+f"(d[4]),"+f"(d[5]),"+f"(d[6]),"+f"(d[7]),"+f"(d[8]),"+f"(d[9]),"+f"(d[10]),"+f"(d[11]),"+f"(d[12]),"+f"(d[13]),"+f"(d[14]),"+f"(d[15]),"+f"(d[16]),"+f"(d[17]),"+f"(d[18]),"+f"(d[19]),"+f"(d[20]),"+f"(d[21]),"+f"(d[22]),"+f"(d[23]) : "r"(a[0]),"r"(a[1]),"r"(a[2]),"r"(a[3]),"l"(db),"r"(sc));
}
__device__ __forceinline__ void wg_rs64_0(float* d, const uint32_t* a, uint64_t db, int sc) {
  asm volatile("{.reg .pred p; setp.ne.b32 p, %37, 0; wgmma.mma_async.sync.aligned.m64n64k16.f32.bf16.bf16 {%0,%1,%2,%3,%4,%5,%6,%7,%8,%9,%10,%11,%12,%13,%14,%15,%16,%17,%18,%19,%20,%21,%22,%23,%24,%25,%26,%27,%28,%29,%30,%31}, {%32,%33,%34,%35}, %36, p, 1, 1, 0;}"
    : "+f"(d[0]),"+f"(d[1]),"+f"(d[2]),"+f"(d[3]),"+f"(d[4]),"+f"(d[5]),"+f"(d[6]),"+f"(d[7]),"+f"(d[8]),"+f"(d[9]),"+f"(d[10]),"+f"(d[11]),"+f"(d[12]),"+f"(d[13]),"+f"(d[14]),"+f"(d[15]),"+f"(d[16]),"+f"(d[17]),"+f"(d[18]),"+f"(d[19]),"+f"(d[20]),"+f"(d[21]),"+f"(d[22]),"+f"(d[23]),"+f"(d[24]),"+f"(d[25]),"+f"(d[26]),"+f"(d[27]),"+f"(d[28]),"+f"(d[29]),"+f"(d[30]),"+f"(d[31]) : "r"(a[0]),"r"(a[1]),"r"(a[2]),"r"(a[3]),"l"(db),"r"(sc));
}
__device__ __forceinline__ void wg_rs80_0(float* d, const uint32_t* a, uint64_t db, int sc) {
  asm volatile("{.reg .pred p; setp.ne.b32 p, %45, 0; wgmma.mma_async.sync.aligned.m64n80k16.f32.bf16.bf16 {%0,%1,%2,%3,%4,%5,%6,%7,%8,%9,%10,%11,%12,%13,%14,%15,%16,%17,%18,%19,%20,%21,%22,%23,%24,%25,%26,%27,%28,%29,%30,%31,%32,%33,%34,%35,%36,%37,%38,%39}, {%40,%41,%42,%43}, %44, p, 1, 1, 0;}"
    : "+f"(d[0]),"+f"(d[1]),"+f"(d[2]),"+f"(d[3]),"+f"(d[4]),"+f"(d[5]),"+f"(d[6]),"+f"(d[7]),"+f"(d[8]),"+f"(d[9]),"+f"(d[10]),"+f"(d[11]),"+f"(d[12]),"+f"(d[13]),"+f"(d[14]),"+f"(d[15]),"+f"(d[16]),"+f"(d[17]),"+f"(d[18]),"+f"(d[19]),"+f"(d[20]),"+f"(d[21]),"+f"(d[22]),"+f"(d[23]),"+f"(d[24]),"+f"(d[25]),"+f"(d[26]),"+f"(d[27]),"+f"(d[28]),"+f"(d[29]),"+f"(d[30]),"+f"(d[31]),"+f"(d[32]),"+f"(d[33]),"+f"(d[34]),"+f"(d[35]),"+f"(d[36]),"+f"(d[37]),"+f"(d[38]),"+f"(d[39]) : "r"(a[0]),"r"(a[1]),"r"(a[2]),"r"(a[3]),"l"(db),"r"(sc));
}
__device__ __forceinline__ void wg_rs96_0(float* d, const uint32_t* a, uint64_t db, int sc) {
  asm volatile("{.reg .pred p; setp.ne.b32 p, %53, 0; wgmma.mma_async.sync.aligned.m64n96k16.f32.bf16.bf16 {%0,%1,%2,%3,%4,%5,%6,%7,%8,%9,%10,%11,%12,%13,%14,%15,%16,%17,%18,%19,%20,%21,%22,%23,%24,%25,%26,%27,%28,%29,%30,%31,%32,%33,%34,%35,%36,%37,%38,%39,%40,%41,%42,%43,%44,%45,%46,%47}, {%48,%49,%50,%51}, %52, p, 1, 1, 0;}"
    : "+f"(d[0]),"+f"(d[1]),"+f"(d[2]),"+f"(d[3]),"+f"(d[4]),"+f"(d[5]),"+f"(d[6]),"+f"(d[7]),"+f"(d[8]),"+f"(d[9]),"+f"(d[10]),"+f"(d[11]),"+f"(d[12]),"+f"(d[13]),"+f"(d[14]),"+f"(d[15]),"+f"(d[16]),"+f"(d[17]),"+f"(d[18]),"+f"(d[19]),"+f"(d[20]),"+f"(d[21]),"+f"(d[22]),"+f"(d[23]),"+f"(d[24]),"+f"(d[25]),"+f"(d[26]),"+f"(d[27]),"+f"(d[28]),"+f"(d[29]),"+f"(d[30]),"+f"(d[31]),"+f"(d[32]),"+f"(d[33]),"+f"(d[34]),"+f"(d[35]),"+f"(d[36]),"+f"(d[37]),"+f"(d[38]),"+f"(d[39]),"+f"(d[40]),"+f"(d[41]),"+f"(d[42]),"+f"(d[43]),"+f"(d[44]),"+f"(d[45]),"+f"(d[46]),"+f"(d[47]) : "r"(a[0]),"r"(a[1]),"r"(a[2]),"r"(a[3]),"l"(db),"r"(sc));
}
__device__ __forceinline__ void wg_rs112_0(float* d, const uint32_t* a, uint64_t db, int sc) {
  asm volatile("{.reg .pred p; setp.ne.b32 p, %61, 0; wgmma.mma_async.sync.aligned.m64n112k16.f32.bf16.bf16 {%0,%1,%2,%3,%4,%5,%6,%7,%8,%9,%10,%11,%12,%13,%14,%15,%16,%17,%18,%19,%20,%21,%22,%23,%24,%25,%26,%27,%28,%29,%30,%31,%32,%33,%34,%35,%36,%37,%38,%39,%40,%41,%42,%43,%44,%45,%46,%47,%48,%49,%50,%51,%52,%53,%54,%55}, {%56,%57,%58,%59}, %60, p, 1, 1, 0;}"
    : "+f"(d[0]),"+f"(d[1]),"+f"(d[2]),"+f"(d[3]),"+f"(d[4]),"+f"(d[5]),"+f"(d[6]),"+f"(d[7]),"+f"(d[8]),"+f"(d[9]),"+f"(d[10]),"+f"(d[11]),"+f"(d[12]),"+f"(d[13]),"+f"(d[14]),"+f"(d[15]),"+f"(d[16]),"+f"(d[17]),"+f"(d[18]),"+f"(d[19]),"+f"(d[20]),"+f"(d[21]),"+f"(d[22]),"+f"(d[23]),"+f"(d[24]),"+f"(d[25]),"+f"(d[26]),"+f"(d[27]),"+f"(d[28]),"+f"(d[29]),"+f"(d[30]),"+f"(d[31]),"+f"(d[32]),"+f"(d[33]),"+f"(d[34]),"+f"(d[35]),"+f"(d[36]),"+f"(d[37]),"+f"(d[38]),"+f"(d[39]),"+f"(d[40]),"+f"(d[41]),"+f"(d[42]),"+f"(d[43]),"+f"(d[44]),"+f"(d[45]),"+f"(d[46]),"+f"(d[47]),"+f"(d[48]),"+f"(d[49]),"+f"(d[50]),"+f"(d[51]),"+f"(d[52]),"+f"(d[53]),"+f"(d[54]),"+f"(d[55]) : "r"(a[0]),"r"(a[1]),"r"(a[2]),"r"(a[3]),"l"(db),"r"(sc));
}
__device__ __forceinline__ void wg_rs128_0(float* d, const uint32_t* a, uint64_t db, int sc) {
  asm volatile("{.reg .pred p; setp.ne.b32 p, %69, 0; wgmma.mma_async.sync.aligned.m64n128k16.f32.bf16.bf16 {%0,%1,%2,%3,%4,%5,%6,%7,%8,%9,%10,%11,%12,%13,%14,%15,%16,%17,%18,%19,%20,%21,%22,%23,%24,%25,%26,%27,%28,%29,%30,%31,%32,%33,%34,%35,%36,%37,%38,%39,%40,%41,%42,%43,%44,%45,%46,%47,%48,%49,%50,%51,%52,%53,%54,%55,%56,%57,%58,%59,%60,%61,%62,%63}, {%64,%65,%66,%67}, %68, p, 1, 1, 0;}"
    : "+f"(d[0]),"+f"(d[1]),"+f"(d[2]),"+f"(d[3]),"+f"(d[4]),"+f"(d[5]),"+f"(d[6]),"+f"(d[7]),"+f"(d[8]),"+f"(d[9]),"+f"(d[10]),"+f"(d[11]),"+f"(d[12]),"+f"(d[13]),"+f"(d[14]),"+f"(d[15]),"+f"(d[16]),"+f"(d[17]),"+f"(d[18]),"+f"(d[19]),"+f"(d[20]),"+f"(d[21]),"+f"(d[22]),"+f"(d[23]),"+f"(d[24]),"+f"(d[25]),"+f"(d[26]),"+f"(d[27]),"+f"(d[28]),"+f"(d[29]),"+f"(d[30]),"+f"(d[31]),"+f"(d[32]),"+f"(d[33]),"+f"(d[34]),"+f"(d[35]),"+f"(d[36]),"+f"(d[37]),"+f"(d[38]),"+f"(d[39]),"+f"(d[40]),"+f"(d[41]),"+f"(d[42]),"+f"(d[43]),"+f"(d[44]),"+f"(d[45]),"+f"(d[46]),"+f"(d[47]),"+f"(d[48]),"+f"(d[49]),"+f"(d[50]),"+f"(d[51]),"+f"(d[52]),"+f"(d[53]),"+f"(d[54]),"+f"(d[55]),"+f"(d[56]),"+f"(d[57]),"+f"(d[58]),"+f"(d[59]),"+f"(d[60]),"+f"(d[61]),"+f"(d[62]),"+f"(d[63]) : "r"(a[0]),"r"(a[1]),"r"(a[2]),"r"(a[3]),"l"(db),"r"(sc));
}
__device__ __forceinline__ void wg_rs144_0(float* d, const uint32_t* a, uint64_t db, int sc) {
  asm volatile("{.reg .pred p; setp.ne.b32 p, %77, 0; wgmma.mma_async.sync.aligned.m64n144k16.f32.bf16.bf16 {%0,%1,%2,%3,%4,%5,%6,%7,%8,%9,%10,%11,%12,%13,%14,%15,%16,%17,%18,%19,%20,%21,%22,%23,%24,%25,%26,%27,%28,%29,%30,%31,%32,%33,%34,%35,%36,%37,%38,%39,%40,%41,%42,%43,%44,%45,%46,%47,%48,%49,%50,%51,%52,%53,%54,%55,%56,%57,%58,%59,%60,%61,%62,%63,%64,%65,%66,%67,%68,%69,%70,%71}, {%72,%73,%74,%75}, %76, p, 1, 1, 0;}"
    : "+f"(d[0]),"+f"(d[1]),"+f"(d[2]),"+f"(d[3]),"+f"(d[4]),"+f"(d[5]),"+f"(d[6]),"+f"(d[7]),"+f"(d[8]),"+f"(d[9]),"+f"(d[10]),"+f"(d[11]),"+f"(d[12]),"+f"(d[13]),"+f"(d[14]),"+f"(d[15]),"+f"(d[16]),"+f"(d[17]),"+f"(d[18]),"+f"(d[19]),"+f"(d[20]),"+f"(d[21]),"+f"(d[22]),"+f"(d[23]),"+f"(d[24]),"+f"(d[25]),"+f"(d[26]),"+f"(d[27]),"+f"(d[28]),"+f"(d[29]),"+f"(d[30]),"+f"(d[31]),"+f"(d[32]),"+f"(d[33]),"+f"(d[34]),"+f"(d[35]),"+f"(d[36]),"+f"(d[37]),"+f"(d[38]),"+f"(d[39]),"+f"(d[40]),"+f"(d[41]),"+f"(d[42]),"+f"(d[43]),"+f"(d[44]),"+f"(d[45]),"+f"(d[46]),"+f"(d[47]),"+f"(d[48]),"+f"(d[49]),"+f"(d[50]),"+f"(d[51]),"+f"(d[52]),"+f"(d[53]),"+f"(d[54]),"+f"(d[55]),"+f"(d[56]),"+f"(d[57]),"+f"(d[58]),"+f"(d[59]),"+f"(d[60]),"+f"(d[61]),"+f"(d[62]),"+f"(d[63]),"+f"(d[64]),"+f"(d[65]),"+f"(d[66]),"+f"(d[67]),"+f"(d[68]),"+f"(d[69]),"+f"(d[70]),"+f"(d[71]) : "r"(a[0]),"r"(a[1]),"r"(a[2]),"r"(a[3]),"l"(db),"r"(sc));
}
__device__ __forceinline__ void wg_rs160_0(float* d, const uint32_t* a, uint64_t db, int sc) {
  asm volatile("{.reg .pred p; setp.ne.b32 p, %85, 0; wgmma.mma_async.sync.aligned.m64n160k16.f32.bf16.bf16 {%0,%1,%2,%3,%4,%5,%6,%7,%8,%9,%10,%11,%12,%13,%14,%15,%16,%17,%18,%19,%20,%21,%22,%23,%24,%25,%26,%27,%28,%29,%30,%31,%32,%33,%34,%35,%36,%37,%38,%39,%40,%41,%42,%43,%44,%45,%46,%47,%48,%49,%50,%51,%52,%53,%54,%55,%56,%57,%58,%59,%60,%61,%62,%63,%64,%65,%66,%67,%68,%69,%70,%71,%72,%73,%74,%75,%76,%77,%78,%79}, {%80,%81,%82,%83}, %84, p, 1, 1, 0;}"
    : "+f"(d[0]),"+f"(d[1]),"+f"(d[2]),"+f"(d[3]),"+f"(d[4]),"+f"(d[5]),"+f"(d[6]),"+f"(d[7]),"+f"(d[8]),"+f"(d[9]),"+f"(d[10]),"+f"(d[11]),"+f"(d[12]),"+f"(d[13]),"+f"(d[14]),"+f"(d[15]),"+f"(d[16]),"+f"(d[17]),"+f"(d[18]),"+f"(d[19]),"+f"(d[20]),"+f"(d[21]),"+f"(d[22]),"+f"(d[23]),"+f"(d[24]),"+f"(d[25]),"+f"(d[26]),"+f"(d[27]),"+f"(d[28]),"+f"(d[29]),"+f"(d[30]),"+f"(d[31]),"+f"(d[32]),"+f"(d[33]),"+f"(d[34]),"+f"(d[35]),"+f"(d[36]),"+f"(d[37]),"+f"(d[38]),"+f"(d[39]),"+f"(d[40]),"+f"(d[41]),"+f"(d[42]),"+f"(d[43]),"+f"(d[44]),"+f"(d[45]),"+f"(d[46]),"+f"(d[47]),"+f"(d[48]),"+f"(d[49]),"+f"(d[50]),"+f"(d[51]),"+f"(d[52]),"+f"(d[53]),"+f"(d[54]),"+f"(d[55]),"+f"(d[56]),"+f"(d[57]),"+f"(d[58]),"+f"(d[59]),"+f"(d[60]),"+f"(d[61]),"+f"(d[62]),"+f"(d[63]),"+f"(d[64]),"+f"(d[65]),"+f"(d[66]),"+f"(d[67]),"+f"(d[68]),"+f"(d[69]),"+f"(d[70]),"+f"(d[71]),"+f"(d[72]),"+f"(d[73]),"+f"(d[74]),"+f"(d[75]),"+f"(d[76]),"+f"(d[77]),"+f"(d[78]),"+f"(d[79]) : "r"(a[0]),"r"(a[1]),"r"(a[2]),"r"(a[3]),"l"(db),"r"(sc));
}
__device__ __forceinline__ void wg_rs176_0(float* d, const uint32_t* a, uint64_t db, int sc) {
  asm volatile("{.reg .pred p; setp.ne.b32 p, %93, 0; wgmma.mma_async.sync.aligned.m64n176k16.f32.bf16.bf16 {%0,%1,%2,%3,%4,%5,%6,%7,%8,%9,%10,%11,%12,%13,%14,%15,%16,%17,%18,%19,%20,%21,%22,%23,%24,%25,%26,%27,%28,%29,%30,%31,%32,%33,%34,%35,%36,%37,%38,%39,%40,%41,%42,%43,%44,%45,%46,%47,%48,%49,%50,%51,%52,%53,%54,%55,%56,%57,%58,%59,%60,%61,%62,%63,%64,%65,%66,%67,%68,%69,%70,%71,%72,%73,%74,%75,%76,%77,%78,%79,%80,%81,%82,%83,%84,%85,%86,%87}, {%88,%89,%90,%91}, %92, p, 1, 1, 0;}"
    : "+f"(d[0]),"+f"(d[1]),"+f"(d[2]),"+f"(d[3]),"+f"(d[4]),"+f"(d[5]),"+f"(d[6]),"+f"(d[7]),"+f"(d[8]),"+f"(d[9]),"+f"(d[10]),"+f"(d[11]),"+f"(d[12]),"+f"(d[13]),"+f"(d[14]),"+f"(d[15]),"+f"(d[16]),"+f"(d[17]),"+f"(d[18]),"+f"(d[19]),"+f"(d[20]),"+f"(d[21]),"+f"(d[22]),"+f"(d[23]),"+f"(d[24]),"+f"(d[25]),"+f"(d[26]),"+f"(d[27]),"+f"(d[28]),"+f"(d[29]),"+f"(d[30]),"+f"(d[31]),"+f"(d[32]),"+f"(d[33]),"+f"(d[34]),"+f"(d[35]),"+f"(d[36]),"+f"(d[37]),"+f"(d[38]),"+f"(d[39]),"+f"(d[40]),"+f"(d[41]),"+f"(d[42]),"+f"(d[43]),"+f"(d[44]),"+f"(d[45]),"+f"(d[46]),"+f"(d[47]),"+f"(d[48]),"+f"(d[49]),"+f"(d[50]),"+f"(d[51]),"+f"(d[52]),"+f"(d[53]),"+f"(d[54]),"+f"(d[55]),"+f"(d[56]),"+f"(d[57]),"+f"(d[58]),"+f"(d[59]),"+f"(d[60]),"+f"(d[61]),"+f"(d[62]),"+f"(d[63]),"+f"(d[64]),"+f"(d[65]),"+f"(d[66]),"+f"(d[67]),"+f"(d[68]),"+f"(d[69]),"+f"(d[70]),"+f"(d[71]),"+f"(d[72]),"+f"(d[73]),"+f"(d[74]),"+f"(d[75]),"+f"(d[76]),"+f"(d[77]),"+f"(d[78]),"+f"(d[79]),"+f"(d[80]),"+f"(d[81]),"+f"(d[82]),"+f"(d[83]),"+f"(d[84]),"+f"(d[85]),"+f"(d[86]),"+f"(d[87]) : "r"(a[0]),"r"(a[1]),"r"(a[2]),"r"(a[3]),"l"(db),"r"(sc));
}
__device__ __forceinline__ void wg_rs192_0(float* d, const uint32_t* a, uint64_t db, int sc) {
  asm volatile("{.reg .pred p; setp.ne.b32 p, %101, 0; wgmma.mma_async.sync.aligned.m64n192k16.f32.bf16.bf16 {%0,%1,%2,%3,%4,%5,%6,%7,%8,%9,%10,%11,%12,%13,%14,%15,%16,%17,%18,%19,%20,%21,%22,%23,%24,%25,%26,%27,%28,%29,%30,%31,%32,%33,%34,%35,%36,%37,%38,%39,%40,%41,%42,%43,%44,%45,%46,%47,%48,%49,%50,%51,%52,%53,%54,%55,%56,%57,%58,%59,%60,%61,%62,%63,%64,%65,%66,%67,%68,%69,%70,%71,%72,%73,%74,%75,%76,%77,%78,%79,%80,%81,%82,%83,%84,%85,%86,%87,%88,%89,%90,%91,%92,%93,%94,%95}, {%96,%97,%98,%99}, %100, p, 1, 1, 0;}"
    : "+f"(d[0]),"+f"(d[1]),"+f"(d[2]),"+f"(d[3]),"+f"(d[4]),"+f"(d[5]),"+f"(d[6]),"+f"(d[7]),"+f"(d[8]),"+f"(d[9]),"+f"(d[10]),"+f"(d[11]),"+f"(d[12]),"+f"(d[13]),"+f"(d[14]),"+f"(d[15]),"+f"(d[16]),"+f"(d[17]),"+f"(d[18]),"+f"(d[19]),"+f"(d[20]),"+f"(d[21]),"+f"(d[22]),"+f"(d[23]),"+f"(d[24]),"+f"(d[25]),"+f"(d[26]),"+f"(d[27]),"+f"(d[28]),"+f"(d[29]),"+f"(d[30]),"+f"(d[31]),"+f"(d[32]),"+f"(d[33]),"+f"(d[34]),"+f"(d[35]),"+f"(d[36]),"+f"(d[37]),"+f"(d[38]),"+f"(d[39]),"+f"(d[40]),"+f"(d[41]),"+f"(d[42]),"+f"(d[43]),"+f"(d[44]),"+f"(d[45]),"+f"(d[46]),"+f"(d[47]),"+f"(d[48]),"+f"(d[49]),"+f"(d[50]),"+f"(d[51]),"+f"(d[52]),"+f"(d[53]),"+f"(d[54]),"+f"(d[55]),"+f"(d[56]),"+f"(d[57]),"+f"(d[58]),"+f"(d[59]),"+f"(d[60]),"+f"(d[61]),"+f"(d[62]),"+f"(d[63]),"+f"(d[64]),"+f"(d[65]),"+f"(d[66]),"+f"(d[67]),"+f"(d[68]),"+f"(d[69]),"+f"(d[70]),"+f"(d[71]),"+f"(d[72]),"+f"(d[73]),"+f"(d[74]),"+f"(d[75]),"+f"(d[76]),"+f"(d[77]),"+f"(d[78]),"+f"(d[79]),"+f"(d[80]),"+f"(d[81]),"+f"(d[82]),"+f"(d[83]),"+f"(d[84]),"+f"(d[85]),"+f"(d[86]),"+f"(d[87]),"+f"(d[88]),"+f"(d[89]),"+f"(d[90]),"+f"(d[91]),"+f"(d[92]),"+f"(d[93]),"+f"(d[94]),"+f"(d[95]) : "r"(a[0]),"r"(a[1]),"r"(a[2]),"r"(a[3]),"l"(db),"r"(sc));
}
__device__ __forceinline__ void wg_ss192_11(float* d, uint64_t da, uint64_t db, int sc) {
  asm volatile("{.reg .pred p; setp.ne.b32 p, %98, 0; wgmma.mma_async.sync.aligned.m64n192k16.f32.bf16.bf16 {%0,%1,%2,%3,%4,%5,%6,%7,%8,%9,%10,%11,%12,%13,%14,%15,%16,%17,%18,%19,%20,%21,%22,%23,%24,%25,%26,%27,%28,%29,%30,%31,%32,%33,%34,%35,%36,%37,%38,%39,%40,%41,%42,%43,%44,%45,%46,%47,%48,%49,%50,%51,%52,%53,%54,%55,%56,%57,%58,%59,%60,%61,%62,%63,%64,%65,%66,%67,%68,%69,%70,%71,%72,%73,%74,%75,%76,%77,%78,%79,%80,%81,%82,%83,%84,%85,%86,%87,%88,%89,%90,%91,%92,%93,%94,%95}, %96, %97, p, 1, 1, 1, 1;}"
    : "+f"(d[0]),"+f"(d[1]),"+f"(d[2]),"+f"(d[3]),"+f"(d[4]),"+f"(d[5]),"+f"(d[6]),"+f"(d[7]),"+f"(d[8]),"+f"(d[9]),"+f"(d[10]),"+f"(d[11]),"+f"(d[12]),"+f"(d[13]),"+f"(d[14]),"+f"(d[15]),"+f"(d[16]),"+f"(d[17]),"+f"(d[18]),"+f"(d[19]),"+f"(d[20]),"+f"(d[21]),"+f"(d[22]),"+f"(d[23]),"+f"(d[24]),"+f"(d[25]),"+f"(d[26]),"+f"(d[27]),"+f"(d[28]),"+f"(d[29]),"+f"(d[30]),"+f"(d[31]),"+f"(d[32]),"+f"(d[33]),"+f"(d[34]),"+f"(d[35]),"+f"(d[36]),"+f"(d[37]),"+f"(d[38]),"+f"(d[39]),"+f"(d[40]),"+f"(d[41]),"+f"(d[42]),"+f"(d[43]),"+f"(d[44]),"+f"(d[45]),"+f"(d[46]),"+f"(d[47]),"+f"(d[48]),"+f"(d[49]),"+f"(d[50]),"+f"(d[51]),"+f"(d[52]),"+f"(d[53]),"+f"(d[54]),"+f"(d[55]),"+f"(d[56]),"+f"(d[57]),"+f"(d[58]),"+f"(d[59]),"+f"(d[60]),"+f"(d[61]),"+f"(d[62]),"+f"(d[63]),"+f"(d[64]),"+f"(d[65]),"+f"(d[66]),"+f"(d[67]),"+f"(d[68]),"+f"(d[69]),"+f"(d[70]),"+f"(d[71]),"+f"(d[72]),"+f"(d[73]),"+f"(d[74]),"+f"(d[75]),"+f"(d[76]),"+f"(d[77]),"+f"(d[78]),"+f"(d[79]),"+f"(d[80]),"+f"(d[81]),"+f"(d[82]),"+f"(d[83]),"+f"(d[84]),"+f"(d[85]),"+f"(d[86]),"+f"(d[87]),"+f"(d[88]),"+f"(d[89]),"+f"(d[90]),"+f"(d[91]),"+f"(d[92]),"+f"(d[93]),"+f"(d[94]),"+f"(d[95]) : "l"(da),"l"(db),"r"(sc));
}
__device__ __forceinline__ void wg_ss192_01(float* d, uint64_t da, uint64_t db, int sc) {
  asm volatile("{.reg .pred p; setp.ne.b32 p, %98, 0; wgmma.mma_async.sync.aligned.m64n192k16.f32.bf16.bf16 {%0,%1,%2,%3,%4,%5,%6,%7,%8,%9,%10,%11,%12,%13,%14,%15,%16,%17,%18,%19,%20,%21,%22,%23,%24,%25,%26,%27,%28,%29,%30,%31,%32,%33,%34,%35,%36,%37,%38,%39,%40,%41,%42,%43,%44,%45,%46,%47,%48,%49,%50,%51,%52,%53,%54,%55,%56,%57,%58,%59,%60,%61,%62,%63,%64,%65,%66,%67,%68,%69,%70,%71,%72,%73,%74,%75,%76,%77,%78,%79,%80,%81,%82,%83,%84,%85,%86,%87,%88,%89,%90,%91,%92,%93,%94,%95}, %96, %97, p, 1, 1, 0, 1;}"
    : "+f"(d[0]),"+f"(d[1]),"+f"(d[2]),"+f"(d[3]),"+f"(d[4]),"+f"(d[5]),"+f"(d[6]),"+f"(d[7]),"+f"(d[8]),"+f"(d[9]),"+f"(d[10]),"+f"(d[11]),"+f"(d[12]),"+f"(d[13]),"+f"(d[14]),"+f"(d[15]),"+f"(d[16]),"+f"(d[17]),"+f"(d[18]),"+f"(d[19]),"+f"(d[20]),"+f"(d[21]),"+f"(d[22]),"+f"(d[23]),"+f"(d[24]),"+f"(d[25]),"+f"(d[26]),"+f"(d[27]),"+f"(d[28]),"+f"(d[29]),"+f"(d[30]),"+f"(d[31]),"+f"(d[32]),"+f"(d[33]),"+f"(d[34]),"+f"(d[35]),"+f"(d[36]),"+f"(d[37]),"+f"(d[38]),"+f"(d[39]),"+f"(d[40]),"+f"(d[41]),"+f"(d[42]),"+f"(d[43]),"+f"(d[44]),"+f"(d[45]),"+f"(d[46]),"+f"(d[47]),"+f"(d[48]),"+f"(d[49]),"+f"(d[50]),"+f"(d[51]),"+f"(d[52]),"+f"(d[53]),"+f"(d[54]),"+f"(d[55]),"+f"(d[56]),"+f"(d[57]),"+f"(d[58]),"+f"(d[59]),"+f"(d[60]),"+f"(d[61]),"+f"(d[62]),"+f"(d[63]),"+f"(d[64]),"+f"(d[65]),"+f"(d[66]),"+f"(d[67]),"+f"(d[68]),"+f"(d[69]),"+f"(d[70]),"+f"(d[71]),"+f"(d[72]),"+f"(d[73]),"+f"(d[74]),"+f"(d[75]),"+f"(d[76]),"+f"(d[77]),"+f"(d[78]),"+f"(d[79]),"+f"(d[80]),"+f"(d[81]),"+f"(d[82]),"+f"(d[83]),"+f"(d[84]),"+f"(d[85]),"+f"(d[86]),"+f"(d[87]),"+f"(d[88]),"+f"(d[89]),"+f"(d[90]),"+f"(d[91]),"+f"(d[92]),"+f"(d[93]),"+f"(d[94]),"+f"(d[95]) : "l"(da),"l"(db),"r"(sc));
}
__device__ __forceinline__ void wg_ss160_01(float* d, uint64_t da, uint64_t db, int sc) {
  asm volatile("{.reg .pred p; setp.ne.b32 p, %82, 0; wgmma.mma_async.sync.aligned.m64n160k16.f32.bf16.bf16 {%0,%1,%2,%3,%4,%5,%6,%7,%8,%9,%10,%11,%12,%13,%14,%15,%16,%17,%18,%19,%20,%21,%22,%23,%24,%25,%26,%27,%28,%29,%30,%31,%32,%33,%34,%35,%36,%37,%38,%39,%40,%41,%42,%43,%44,%45,%46,%47,%48,%49,%50,%51,%52,%53,%54,%55,%56,%57,%58,%59,%60,%61,%62,%63,%64,%65,%66,%67,%68,%69,%70,%71,%72,%73,%74,%75,%76,%77,%78,%79}, %80, %81, p, 1, 1, 0, 1;}"
    : "+f"(d[0]),"+f"(d[1]),"+f"(d[2]),"+f"(d[3]),"+f"(d[4]),"+f"(d[5]),"+f"(d[6]),"+f"(d[7]),"+f"(d[8]),"+f"(d[9]),"+f"(d[10]),"+f"(d[11]),"+f"(d[12]),"+f"(d[13]),"+f"(d[14]),"+f"(d[15]),"+f"(d[16]),"+f"(d[17]),"+f"(d[18]),"+f"(d[19]),"+f"(d[20]),"+f"(d[21]),"+f"(d[22]),"+f"(d[23]),"+f"(d[24]),"+f"(d[25]),"+f"(d[26]),"+f"(d[27]),"+f"(d[28]),"+f"(d[29]),"+f"(d[30]),"+f"(d[31]),"+f"(d[32]),"+f"(d[33]),"+f"(d[34]),"+f"(d[35]),"+f"(d[36]),"+f"(d[37]),"+f"(d[38]),"+f"(d[39]),"+f"(d[40]),"+f"(d[41]),"+f"(d[42]),"+f"(d[43]),"+f"(d[44]),"+f"(d[45]),"+f"(d[46]),"+f"(d[47]),"+f"(d[48]),"+f"(d[49]),"+f"(d[50]),"+f"(d[51]),"+f"(d[52]),"+f"(d[53]),"+f"(d[54]),"+f"(d[55]),"+f"(d[56]),"+f"(d[57]),"+f"(d[58]),"+f"(d[59]),"+f"(d[60]),"+f"(d[61]),"+f"(d[62]),"+f"(d[63]),"+f"(d[64]),"+f"(d[65]),"+f"(d[66]),"+f"(d[67]),"+f"(d[68]),"+f"(d[69]),"+f"(d[70]),"+f"(d[71]),"+f"(d[72]),"+f"(d[73]),"+f"(d[74]),"+f"(d[75]),"+f"(d[76]),"+f"(d[77]),"+f"(d[78]),"+f"(d[79]) : "l"(da),"l"(db),"r"(sc));
}
__device__ __forceinline__ void wg_ss96_01(float* d, uint64_t da, uint64_t db, int sc) {
  asm volatile("{.reg .pred p; setp.ne.b32 p, %50, 0; wgmma.mma_async.sync.aligned.m64n96k16.f32.bf16.bf16 {%0,%1,%2,%3,%4,%5,%6,%7,%8,%9,%10,%11,%12,%13,%14,%15,%16,%17,%18,%19,%20,%21,%22,%23,%24,%25,%26,%27,%28,%29,%30,%31,%32,%33,%34,%35,%36,%37,%38,%39,%40,%41,%42,%43,%44,%45,%46,%47}, %48, %49, p, 1, 1, 0, 1;}"
    : "+f"(d[0]),"+f"(d[1]),"+f"(d[2]),"+f"(d[3]),"+f"(d[4]),"+f"(d[5]),"+f"(d[6]),"+f"(d[7]),"+f"(d[8]),"+f"(d[9]),"+f"(d[10]),"+f"(d[11]),"+f"(d[12]),"+f"(d[13]),"+f"(d[14]),"+f"(d[15]),"+f"(d[16]),"+f"(d[17]),"+f"(d[18]),"+f"(d[19]),"+f"(d[20]),"+f"(d[21]),"+f"(d[22]),"+f"(d[23]),"+f"(d[24]),"+f"(d[25]),"+f"(d[26]),"+f"(d[27]),"+f"(d[28]),"+f"(d[29]),"+f"(d[30]),"+f"(d[31]),"+f"(d[32]),"+f"(d[33]),"+f"(d[34]),"+f"(d[35]),"+f"(d[36]),"+f"(d[37]),"+f"(d[38]),"+f"(d[39]),"+f"(d[40]),"+f"(d[41]),"+f"(d[42]),"+f"(d[43]),"+f"(d[44]),"+f"(d[45]),"+f"(d[46]),"+f"(d[47]) : "l"(da),"l"(db),"r"(sc));
}
__device__ __forceinline__ void wg_ss64_01(float* d, uint64_t da, uint64_t db, int sc) {
  asm volatile("{.reg .pred p; setp.ne.b32 p, %34, 0; wgmma.mma_async.sync.aligned.m64n64k16.f32.bf16.bf16 {%0,%1,%2,%3,%4,%5,%6,%7,%8,%9,%10,%11,%12,%13,%14,%15,%16,%17,%18,%19,%20,%21,%22,%23,%24,%25,%26,%27,%28,%29,%30,%31}, %32, %33, p, 1, 1, 0, 1;}"
    : "+f"(d[0]),"+f"(d[1]),"+f"(d[2]),"+f"(d[3]),"+f"(d[4]),"+f"(d[5]),"+f"(d[6]),"+f"(d[7]),"+f"(d[8]),"+f"(d[9]),"+f"(d[10]),"+f"(d[11]),"+f"(d[12]),"+f"(d[13]),"+f"(d[14]),"+f"(d[15]),"+f"(d[16]),"+f"(d[17]),"+f"(d[18]),"+f"(d[19]),"+f"(d[20]),"+f"(d[21]),"+f"(d[22]),"+f"(d[23]),"+f"(d[24]),"+f"(d[25]),"+f"(d[26]),"+f"(d[27]),"+f"(d[28]),"+f"(d[29]),"+f"(d[30]),"+f"(d[31]) : "l"(da),"l"(db),"r"(sc));
}
__device__ __forceinline__ void wg_rs160_1(float* d, const uint32_t* a, uint64_t db, int sc) {
  asm volatile("{.reg .pred p; setp.ne.b32 p, %85, 0; wgmma.mma_async.sync.aligned.m64n160k16.f32.bf16.bf16 {%0,%1,%2,%3,%4,%5,%6,%7,%8,%9,%10,%11,%12,%13,%14,%15,%16,%17,%18,%19,%20,%21,%22,%23,%24,%25,%26,%27,%28,%29,%30,%31,%32,%33,%34,%35,%36,%37,%38,%39,%40,%41,%42,%43,%44,%45,%46,%47,%48,%49,%50,%51,%52,%53,%54,%55,%56,%57,%58,%59,%60,%61,%62,%63,%64,%65,%66,%67,%68,%69,%70,%71,%72,%73,%74,%75,%76,%77,%78,%79}, {%80,%81,%82,%83}, %84, p, 1, 1, 1;}"
    : "+f"(d[0]),"+f"(d[1]),"+f"(d[2]),"+f"(d[3]),"+f"(d[4]),"+f"(d[5]),"+f"(d[6]),"+f"(d[7]),"+f"(d[8]),"+f"(d[9]),"+f"(d[10]),"+f"(d[11]),"+f"(d[12]),"+f"(d[13]),"+f"(d[14]),"+f"(d[15]),"+f"(d[16]),"+f"(d[17]),"+f"(d[18]),"+f"(d[19]),"+f"(d[20]),"+f"(d[21]),"+f"(d[22]),"+f"(d[23]),"+f"(d[24]),"+f"(d[25]),"+f"(d[26]),"+f"(d[27]),"+f"(d[28]),"+f"(d[29]),"+f"(d[30]),"+f"(d[31]),"+f"(d[32]),"+f"(d[33]),"+f"(d[34]),"+f"(d[35]),"+f"(d[36]),"+f"(d[37]),"+f"(d[38]),"+f"(d[39]),"+f"(d[40]),"+f"(d[41]),"+f"(d[42]),"+f"(d[43]),"+f"(d[44]),"+f"(d[45]),"+f"(d[46]),"+f"(d[47]),"+f"(d[48]),"+f"(d[49]),"+f"(d[50]),"+f"(d[51]),"+f"(d[52]),"+f"(d[53]),"+f"(d[54]),"+f"(d[55]),"+f"(d[56]),"+f"(d[57]),"+f"(d[58]),"+f"(d[59]),"+f"(d[60]),"+f"(d[61]),"+f"(d[62]),"+f"(d[63]),"+f"(d[64]),"+f"(d[65]),"+f"(d[66]),"+f"(d[67]),"+f"(d[68]),"+f"(d[69]),"+f"(d[70]),"+f"(d[71]),"+f"(d[72]),"+f"(d[73]),"+f"(d[74]),"+f"(d[75]),"+f"(d[76]),"+f"(d[77]),"+f"(d[78]),"+f"(d[79]) : "r"(a[0]),"r"(a[1]),"r"(a[2]),"r"(a[3]),"l"(db),"r"(sc));
}
__device__ __forceinline__ void wg_ss8_10(float* d, uint64_t da, uint64_t db, int sc) {
  asm volatile("{.reg .pred p; setp.ne.b32 p, %6, 0; wgmma.mma_async.sync.aligned.m64n8k16.f32.bf16.bf16 {%0,%1,%2,%3}, %4, %5, p, 1, 1, 1, 0;}"
    : "+f"(d[0]),"+f"(d[1]),"+f"(d[2]),"+f"(d[3]) : "l"(da),"l"(db),"r"(sc));
}

constexpr uint32_t DB = 1024;
constexpr int WSLOT = 24576, NW = 6, ASLOT = 8192, ARING = 4 * ASLOT;
constexpr int OFF_A = NW * WSLOT;
constexpr int OFF_PB = OFF_A + 2 * ARING;
constexpr int OFF_CV = OFF_PB + 16384, OFF_ST = OFF_CV + 768, OFF_TS = OFF_ST + 256, OFF_MODR = OFF_TS + 512, OFF_BAR = OFF_MODR + 80, SMEM_BYTES = OFF_BAR + 1168;
constexpr int OFF_BX = OFF_PB, OFF_AX = OFF_BX + 12288, OFF_RT = OFF_AX + 2048, OFF_GB = OFF_RT + 512, OFF_CO = OFF_CV;
constexpr int OFF_UV = 5 * WSLOT, OFF_UVE = OFF_PB, OFF_SX = OFF_A + ARING + 3 * ASLOT, OFF_X1 = 2 * WSLOT + ASLOT, OFF_XCH = WSLOT;
constexpr int OFF_Q = 0, KV_V = 4096, KV_H = 8192, F_E = 16, F_O = 4176, OFF_WM = 3 * WSLOT, OFF_TAP = 168576, OFF_MR = OFF_A + 3 * ASLOT;
constexpr uint64_t pk5(int a, int b, int c, int d, int e) { return (uint64_t)(a / 128) | (uint64_t)(b / 128) << 12 | (uint64_t)(c / 128) << 24 | (uint64_t)(d / 128) << 36 | (uint64_t)(e / 128) << 48; }
constexpr uint64_t T_KV = pk5(20480, 30720, 40960, 180224, 190464), T_F = pk5(51200, 59648, 200192, 147456, 155904), T_X = pk5(208512, 164352, 68096, 208512, 164352),
                   T_P = pk5(131072, OFF_PB, 114688, 131072, OFF_PB);
__host__ __device__ __forceinline__ uint32_t tab(uint64_t t, int c) { return ((uint32_t)(t >> (12 * c)) & 0xFFF) << 7; }
enum { B_KV = 0, B_FRAW = 5, B_Q = 10, B_WM = 15, B_XR, B_MR = B_XR + 5, B_QTOK, B_ST1, B_MODR, B_S3 = B_MODR + 5, B_FL = 32, B_PFULL = B_FL + 5, B_PEMPTY = B_PFULL + 5, B_FRDY = B_PEMPTY + 5,
       B_G3 = B_FRDY + 5, B_EXT, B_QTD, B_LAG, B_GB, B_UVD, B_TURN, B_FULL = 60, B_RETRY = B_FULL + 33, B_XFREE = B_RETRY + 9, B_BX, B_UVB, B_UVE, B_SX, B_EMPTY = 109 };
static_assert(B_MODR + 5 <= B_FL && B_UVD < B_FULL && B_SX + 2 == B_EMPTY - 1, "barrier groups");
#define BAR(i) (base + OFF_BAR + 8 * (i))

constexpr int NE = 24;
struct Maps { CUtensorMap km, v, q, kh, tap, wm, w1s, w3s, xs, w1, w3, w1e, w3e, x1s, x1b, w2a, w2b, outa, outb; };
struct Ptrs { const bf16 *ssmk, *c, *ssmd; Scratch* g; uint64_t prog, cprog[2]; int boff, th, wms, ulo, uhi; uint32_t fin, turn, mr2, m3, seq; float one; uint2 sched[NE]; uint32_t wdep[20], wt[5]; uint2 w2t[12]; int hid[3][9]; };

#define REGION_IDS int tid, lane, bid; \
  asm volatile("mov.u32 %0, %%tid.x;" : "=r"(tid)); asm volatile("mov.u32 %0, %%laneid;" : "=r"(lane)); asm volatile("mov.u32 %0, %%ctaid.x;" : "=r"(bid)); \
  const int i0 = tid & 127; (void)i0; (void)lane; (void)bid

__device__ __forceinline__ void ffn_role(int& h, int& j, int& r) {
  uint32_t b;
  asm volatile("mov.u32 %0, %%ctaid.x;" : "=r"(b));
  const uint32_t c = b >> 1, q = (c - 36) * 37 >> 8, e = c - 36 - 7 * q;
  h = b & 1;
  const uint32_t k = c < 4 ? 0 : c < 36 ? (c - 4) & 7 : e + 1, p = c < 4 ? c : c < 36 ? (c - 4) >> 3 : q, up = c - 4 >= 32;
  j = 2 * (k & 1) + up;
  r = 2 * (k & 6) + p;
}
__device__ __forceinline__ int fslice(int j, int e) { return e == 2 ? j ^ 1 : (~j & 2) + e; }
__device__ __forceinline__ int mod_ch(int p) { return p < 40 ? (p >> 3) * 128 + (p & 1) * 64 : 64 * (p < 50 ? p - 40 : p - 50); }
__device__ __forceinline__ int mod_col(int p) { return mod_ch(p) + 640 * (p < 40 ? 0x4210 >> (2 * (p & 6)) & 7 : p < 50 ? 3 : 5); }
__device__ __forceinline__ uint32_t mod_sum(uint2 v) { return pack_bf16(0.f, __uint_as_float(v.x) + __uint_as_float(v.y)); }

constexpr int NT = 3, LAG2 = 29, MG = 4;
__device__ __forceinline__ int w_block(int up, int m) { return m == 1 ? 2 + 3 * up : 3 * (m >> 1) + up; }
__host__ __device__ constexpr int w2_at(int v) { return 8192 * (v ? 0x0613030008ull >> v % 5 * 8 & 255 : 15); }
__host__ __device__ constexpr int w2_step(int v) { return 8192 * (v ? 0x32113 >> v % 5 * 4 & 15 : 1); }
__host__ __device__ constexpr int hid_at(int m, int g) { return 8192 * ((g ? 0x0D07110F1816ull : 0x0A19101A1412ull) >> m % 6 * 8 & 255); }
__host__ __device__ constexpr uint32_t w2_desc(int v) { return (DB + w2_at(v)) >> 4 | w2_step(v) << 12; }
__device__ __forceinline__ int next_slot(int s) { return s >= 4 * WSLOT ? 0 : s + WSLOT; }

template <int U> __device__ __forceinline__ void cstep(float* acc, const uint32_t* A, uint64_t db) {
  const uint32_t* a = A + 4 * U;
  const uint64_t d = db + 16 * U;
  if (U == 4) { wg_rs64_0(acc + 96, A, db + 192, 0); wg_rs48_0(acc + 96, A + 4, db + 208, 1); wg_rs32_0(acc + 96, A + 8, db + 224, 1); wg_rs16_0(acc + 96, A + 12, db + 240, 1); }
  if (U <= 4) wg_rs192_0(acc, a, d, U);
  if (U == 5) wg_rs176_0(acc, a, d, 1);
  if (U == 6) wg_rs160_0(acc, a, d, 1);
  if (U == 7) wg_rs144_0(acc, a, d, 1);
  if (U == 8) wg_rs128_0(acc, a, d, 1);
  if (U == 9) wg_rs112_0(acc, a, d, 1);
  if (U == 10) wg_rs96_0(acc, a, d, 1);
  if (U == 11) wg_rs80_0(acc, a, d, 1);
  if (U == 12) wg_rs64_0(acc, a, d, 1);
  if (U == 13) wg_rs48_0(acc, a, d, 1);
  if (U == 14) wg_rs32_0(acc, a, d, 1);
  if (U == 15) wg_rs16_0(acc, a, d, 1);
}
template <int U0, int U1> __device__ __forceinline__ void csteps(float* acc, const uint32_t* A, uint64_t db) {
  cstep<U0>(acc, A, db);
  if constexpr (U0 > U1) csteps<U0 - 1, U1>(acc, A, db);
}
template <int U0, int U1> __device__ __forceinline__ void cload(uint32_t* A, uint32_t fa) {
  asm volatile("{ld.shared.b32 %0, [%4+%5]; ld.shared.b32 %1, [%4+%5+128]; ld.shared.b32 %2, [%4+%5+16]; ld.shared.b32 %3, [%4+%5+144];}"
               : "=r"(A[4 * U0]), "=r"(A[4 * U0 + 1]), "=r"(A[4 * U0 + 2]), "=r"(A[4 * U0 + 3]) : "r"(fa), "n"(256 * U0) : "memory");
  if constexpr (U0 > U1) cload<U0 - 1, U1>(A, fa);
}

__device__ __forceinline__ void mod_gemv(Scratch* G, uint32_t wm, int unit, int w, int lane, uint32_t par) {
  float d[4] = {};
  fence_regs(d);
  wg_fence();
#pragma unroll 1
  for (int k = 0; k < 20; k += 2) {
    wg_ss8_10(d, mkdesc(DB + wm + 2048 * k, 16, 1024, 1), mkdesc(DB + OFF_CV + 32 * k, 16, 128, 0), 1);
    wg_ss8_10(d, mkdesc(DB + wm + 2048 * k + 2048, 16, 1024, 1), mkdesc(DB + OFF_CV + 32 * k + 32, 16, 128, 0), 1);
  }
  wg_commit();
  const int p = unit >> 1, ch = mod_ch(p) + 16 * w + (lane >> 2);
  uint32_t* dst = (uint32_t*)(p < 40 ? &G->modc[ch & 127][8 + (p >> 1)] : &G->modv[p >= 50][ch]) + (unit & 1);
  wg_wait<0>();
  fence_regs(d);
  if (!(lane & 3)) {
    publish(dst, (__float_as_uint(d[0]) & ~1u) | par);
    publish(dst + (p < 40 ? 512 : 16), (__float_as_uint(d[2]) & ~1u) | par);
    if (p < 40 && (p & 6) == 6) {
      dst = (uint32_t*)&G->modv[2][ch] + (unit & 1);
      publish(dst, (__float_as_uint(d[0]) & ~1u) | par);
      publish(dst + 16, (__float_as_uint(d[2]) & ~1u) | par);
    }
  }
}
__device__ __forceinline__ void silu_vector(const bf16* c, uint32_t base) {
  REGION_IDS;
  const uint32_t c0 = ldg32(c + 320 * (bid & 1) + 2 * i0), c1 = ldg32(c + 320 * (bid & 1) + 256 + 2 * lane);
  sts32(base + OFF_CV + 4 * i0, pack_bf16(silu_f(bf_lo(c0)), silu_f(bf_hi(c0))));
  sts32(base + OFF_CV + 512 + 4 * lane, pack_bf16(silu_f(bf_lo(c1)), silu_f(bf_hi(c1))));
  fence_async_smem();
}

__device__ __forceinline__ void mod_poll(Scratch* G, uint32_t base, int c, int n, uint32_t epoch) {
  REGION_IDS;
  const int e = 4 * c + (lane & (4 * n - 1));
  uint2 m;
  int it = 0;
#pragma unroll 1
  do m = ld_relaxed64(&G->modc[bid][8 + e]); while (__any_sync(~0u, ((m.x ^ epoch) | (m.y ^ epoch)) & 1) && ++it < SPIN_LIMIT);
  sts32(base + OFF_MODR + 4 * e, __byte_perm(badd2(mod_sum(m), (lane & 1) * 0x3F800000u), 0, 0x3232));
  __syncwarp();
  if (elect()) { mbar_arrive(BAR(B_MODR + c)); if (n > 1) mbar_arrive(BAR(B_MODR + c + 1)); }
}
__device__ __forceinline__ void row_stats(Scratch* G, uint32_t base, uint32_t epoch) {
  REGION_IDS;
  mbar_wait_cluster(BAR(B_ST1));
  if (lane < 8) red_hint(G->hint[5][lane]);
  const uint2 x = lds64(base + OFF_ST + 8 * (lane & 15)), y = lds64(base + OFF_ST + 128 + 8 * (lane & 15));
  float m, sd;
  ln_final(__uint_as_float(x.x) + __uint_as_float(y.x), __uint_as_float(x.y) + __uint_as_float(y.y), m, sd);
  sd = rbf(rcpf(sd));
  const uint32_t mr = pack_bf16(sd, -rbf(m) * sd), tg = lane & 7 ? 0 : lane & 8 ? 1 : 0x8000;
  const uint32_t o = __byte_perm(__shfl_sync(~0u, mr, 2 * lane & 14), __shfl_sync(~0u, mr, (2 * lane & 14) + 1), (lane & 8) ? 0x7632 : 0x5410);
  if (lane < 16) st_relaxed32(&G->st1[lane >> 3][8 * bid + (lane & 7)], (o & ~tg) | ((epoch & 1) * tg));
}
template <int B, int NEXT> __device__ __forceinline__ void strip(Scratch* G, const CUtensorMap* map, uint32_t base, int c, uint32_t epoch, uint32_t& ph, uint32_t& pre, float4& s) {
  REGION_IDS;
  int h, j, r, it = 0;
  ffn_role(h, j, r);
  const uint32_t buf = base + OFF_SX + 4096 * B, a = buf + 32 * lane;
#pragma unroll 1
  while (__any_sync(~0u, pre != 64 * epoch) && ++it < SPIN_LIMIT) pre = ld_relaxed32(G->xsh[c][(r & 6) + (j >> 1)]);
#pragma unroll 1
  for (it = 0; it < SPIN_LIMIT; it++) {
    if (elect()) { mbar_expect_tx(BAR(B_SX + B), 4096); tma2d(buf, map, 128 * r + 64 * h, D_ * (epoch & 1) + 128 * c + 32 * j, BAR(B_SX + B)); }
    mbar_wait(BAR(B_SX + B), ph);
    ph ^= 1;
    if (__all_sync(~0u, min(min(lds32(a), lds32(a + 1024)), min(lds32(a + 2048), lds32(a + 3072))))) break;
  }
  pre = 0;
  if (c == NEXT - 1 || c == NEXT - 2) pre = ld_relaxed32(G->xsh[c + 1][(r & 6) + (j >> 1)]);
#pragma unroll 1
  for (uint32_t o = buf + 4 * lane; o < buf + 4096; o += 1024) {
    uint32_t x[8];
#pragma unroll
    for (int i = 0; i < 8; i++) x[i] = lds32(o + 128 * i);
#pragma unroll
    for (int i = 0; i < 8; i++) { const float lo = bf_lo(x[i]), hi = bf_hi(x[i]); s.x += lo; s.y = fmaf(lo, lo, s.y); s.z += hi; s.w = fmaf(hi, hi, s.w); }
  }
}
__device__ __forceinline__ void mr_poll(Scratch* G, uint32_t base, uint32_t epoch) {
  int it = 0;
#pragma unroll 1
  while (__any_sync(~0u, ld_relaxed32(G->hint[5][4 * (blockIdx.x >> 6) + (blockIdx.x >> 3 & 3)]) != epoch << 7) && ++it < SPIN_LIMIT);
  if (elect()) { mbar_expect_tx(BAR(B_MR), 8192); bulk_load(base + OFF_MR, G->st1, 8192, BAR(B_MR)); mbar_arrive(BAR(B_QTOK)); }
}

__global__ void __cluster_dims__(2, 1, 1) __launch_bounds__(512, 1) k_fused(const __grid_constant__ Ptrs P, const __grid_constant__ Maps maps) {
  Scratch* const G = P.g;
  extern __shared__ __align__(1024) uint8_t smem_raw[];
  const uint32_t t_start = clock();
  const uint32_t base = __shfl_sync(~0u, smem_u32(smem_raw), 0);
  if ((base & 0xFFFFFFu) != DB) __trap();
  const int wid = __shfl_sync(~0u, threadIdx.x >> 5, 0), wg = wid >> 2, w = wid & 3;
  if (blockIdx.x + P.boff >= 128) {
    REGION_IDS;
    auto unit = [&](int n) { return 4 * (n + (n < P.ulo / 4 ? 0 : (P.uhi - P.ulo) / 4)) + (bid & 3); };
    auto fetch = [&](int n, int b) {
      if (unit(n) < 120 && elect()) {
        mbar_expect_tx(BAR(n), 40960);
#pragma unroll 1
        for (int k = 0; k < 5; k++) tma3d(base + 40960 * b + 8192 * k, &maps.wm, mod_col(unit(n) >> 1), 320 * (bid & 1) + 64 * k, 0, BAR(n));
      }
    };
    if (wid == 0) {
      mbar_init<5>(BAR(0), 1);
#pragma unroll 1
      for (int n = 0; n < 4; n++) fetch(n, n);
      mbar_init<25>(BAR(5), 1);
    }
    const uint32_t par = ~ld_relaxed32(G->hint[7][0]) >> 7 & 1;
    silu_vector(P.c, base);
    __syncthreads();
#pragma unroll 1
    for (int n = wg; unit(n) < 120; n += 4) {
      mbar_wait(BAR(n));
      mod_gemv(G, 40960 * (n % 5), unit(n), w, lane, par);
      named_bar(1 + wg, 128);
      if (w == 0) {
        if (n < 4) wait_clock(t_start + P.th);
        if (n == 0) fetch(4, 4);
        fetch(n + 5, n % 5);
      }
    }
    return;
  }
  if (wid == 13) {
    mbar_init<16>(BAR(0), 1);
    asm volatile("bar.arrive 1, 512;" ::: "memory");
    if (elect()) {
      const int c0 = 64 * (blockIdx.x & 1), c1 = 2 * (blockIdx.x & 126);
      mbar_expect_tx(BAR(B_KV), 12288);
      tma3d(base + tab(T_KV, 0), &maps.km, c0, c1, 0, BAR(B_KV));
      tma3d(base + tab(T_KV, 0) + KV_V, &maps.v, c0, c1, 0, BAR(B_KV));
      tma3d(base + tab(T_KV, 0) + KV_H, &maps.kh, c0, c1 - 1, 5, BAR(B_KV));
      tma3d(base + OFF_TAP, &maps.tap, 0, blockIdx.x & 1, 0, BAR(B_KV));
    }
  } else {
    asm volatile("bar.sync 1, 512;" ::: "memory");
    if (wid < 11) mbar_init<4>(BAR(16 + 4 * wid), wid < 4 ? 1 : 4);
    asm volatile("fence.mbarrier_init.release.cluster; bar.sync 0, 480;" ::: "memory");
  }
  asm volatile("barrier.cluster.arrive.relaxed.aligned;" ::: "memory");
#define LAUNCHES const uint32_t launches = ld_relaxed32(G->hint[7][blockIdx.x >> 4])
#define EPOCH ((__shfl_sync(~0u, launches, 0) >> 7) + 1)
  if (wg == 3) {
    asm volatile("setmaxnreg.dec.sync.aligned.u32 24;");
    if (w == 1) {
      {
        REGION_IDS;
        const int c1 = 2 * (bid & 126), ws = bid >= P.ulo && bid < P.uhi ? P.wms : 99;
#pragma unroll 1
        for (int e = 0; e < NE; e++) {
          const uint2 x = P.sched[e];
          const uint32_t kind = x.x >> 16 & 15, ch = x.x >> 13 & 0x380, dst = base + (x.y & 0x3FFFF), b = BAR(x.y >> 18);
          wait_clock(t_start + (x.x & 0xFFFF));
          if (kind < 3 && elect()) tma3d(dst, &maps.km + kind, ch + 64 * (bid & 1), c1, 0, b);
          if (kind == 0 && elect()) tma3d(dst + KV_H, &maps.kh, ch + 64 * (bid & 1), c1 - 1, 5, b);
          if (kind == 3 && elect()) bulk_load(dst, P.ssmk + (ch + bid) * S_, 4096, b);
          if ((uint32_t)(e - ws) < 5 && elect()) tma3d(base + OFF_WM + 8192 * (e - ws), &maps.wm, mod_col(bid >> 1), 320 * (bid & 1) + 64 * (e - ws), 0, BAR(B_WM));
          if ((uint32_t)(e - 8) < 13 && elect()) prefetch_map(&maps.w1s + (e - 8));
        }
      }
      cluster_wait();
      int h, j, r;
      ffn_role(h, j, r);
      mbar_wait(BAR(B_QTD));
      mbar_wait(BAR(B_FL));
#pragma unroll 1
      for (int u = 0; u < 20; u++) {
        const uint32_t x = P.wdep[u], s = base + (x & ~8191u);
        if (u < 5) wait_clock(t_start + P.wt[u]);
        mbar_wait(BAR(opaque(x & 255)));
        if (elect()) {
          mbar_expect_tx(BAR(B_FULL + u), WSLOT + 4 * (x & 4096));
#pragma unroll
          for (int k = 0; k < 6; k++) tma3d(s + 4096 * w_block(k & 1, k >> 1), &maps.w1s + (k & 1), 0, 32 * u, 3 * (4 * h + j) + (k >> 1), BAR(B_FULL + u));
        }
      }
#pragma unroll 1
      for (int v = 0; v < 12; v++) {
        const int q = v * 11 >> 5, e = v - 3 * q, k32 = 24 * h + (q ? 6 * fslice(j, e) + 2 * q - 2 : 6 * j + 2 * e);
        const uint2 x = P.w2t[v];
        mbar_wait(BAR(x.y));
        if (elect()) {
          mbar_expect_tx(BAR(B_FULL + 20 + v), q ? WSLOT + 2 * ASLOT : WSLOT);
#pragma unroll
          for (int k = 0; k < 3; k++) tma5d(base - DB + 16 * ((x.x & 0xFFFF) + k * (x.x >> 16)), &maps.w2a + (q > 0), k < 2 ? 128 * j + 64 * k : 512 + 32 * (j & 2), k32, BAR(B_FULL + 20 + v));
        }
      }
    } else if (w == 0) {
      LAUNCHES;
      uint32_t epoch;
      {
        REGION_IDS;
        const unsigned* hp = G->hint[0][4 * (bid >> 6) + (bid >> 3 & 3)];
        uint32_t v = ld_relaxed32(hp + 256 * min(lane, 5));
        if (lane < 3) sts128(base + tab(T_X, lane) + 4096, 0, 0, 0, 0);
        if (lane && lane <= B_WM) mbar_expect_tx(BAR(lane), lane < B_FRAW ? 9728 : lane == B_WM ? 40960 : 4096);
        epoch = EPOCH;
        fence_async_smem();
        const uint32_t rdy = __ballot_sync(~0u, v == epoch << 6);
        uint32_t nx = 0, nm = 0;
#pragma unroll 1
        for (uint32_t seq = P.seq; seq; seq >>= 2) {
          int it = 0;
          if (seq & 1) {
            if (!(seq & 2)) mod_poll(G, base, nm, 1 + (seq == 13), epoch);
            nm++;
          } else if (seq & 2) {
            mr_poll(G, base, epoch);
          } else {
            if (!(rdy >> nx & 1)) {
#pragma unroll 1
              while (__any_sync(~0u, ld_relaxed32(hp + 256 * nx) != epoch << 6) && ++it < SPIN_LIMIT);
            }
            if (nx >= 3) mbar_wait(BAR(B_PFULL - 3 + nx));
            if (elect()) { mbar_expect_tx(BAR(B_XR + nx), 4096); bulk_load(base + tab(T_X, nx), G->xr + (128 * nx + bid) * 256, 4096, BAR(B_XR + nx)); }
            nx++;
          }
        }
      }
      REGION_IDS;
      int h, j, r;
      ffn_role(h, j, r);
      mbar_wait(BAR(B_G3));
      {
        const uint2* mp = &G->modv[lane & 4 ? 0 : 2][40 * (r & 14) + (lane & 24) + 2 * (lane & 3)];
        uint4 v[3];
        int it = 0;
#pragma unroll 1
        do {
          v[0] = ld_relaxed128(mp); v[1] = ld_relaxed128(mp + 32); v[2] = ld_relaxed128(mp + 64 - (lane & 16));
        } while (__any_sync(~0u, ((v[0].x ^ epoch) | (v[0].y ^ epoch) | (v[0].z ^ epoch) | (v[0].w ^ epoch) | (v[1].x ^ epoch) | (v[1].y ^ epoch) | (v[1].z ^ epoch) | (v[1].w ^ epoch) |
                                  (v[2].x ^ epoch) | (v[2].y ^ epoch) | (v[2].z ^ epoch) | (v[2].w ^ epoch)) & 1) && ++it < SPIN_LIMIT);
#pragma unroll
        for (int i = 0; i < 3; i++)
          sts32(base + OFF_CO + 128 * i + 4 * lane, badd2(pack_bf16(__uint_as_float(v[i].x) + __uint_as_float(v[i].y), __uint_as_float(v[i].z) + __uint_as_float(v[i].w)), lane & 4 ? 0 : 0x3F803F80u));
      }
      fence_async_smem();
      __syncwarp();
      ffn_role(h, j, r);
      mbar_wait(BAR(B_PEMPTY + 3));
      if (elect()) {
        mbar_expect_tx(BAR(B_UVB), WSLOT);
        tma3d(base + OFF_UV, &maps.w1 + (r & 1), 0, 40 * (r & 14), 3 * (4 * h + j), BAR(B_UVB));
        tma3d(base + OFF_UV + 12288, &maps.w1 + (r & 1), 0, 40 * (r & 14) + 32, 3 * (4 * h + j), BAR(B_UVB));
      }
      {
        float4 s = {};
        uint32_t ph = 0, pre = 0;
#pragma unroll 1
        for (int c = 2; c < 4; c++) strip<1, 3>(G, &maps.x1s, base, c, epoch, ph, pre, s);
        __syncwarp();
        sts128(base + OFF_SX + 4096 + 16 * lane, __float_as_uint(s.x), __float_as_uint(s.y), __float_as_uint(s.z), __float_as_uint(s.w));
        arrive1(BAR(B_S3));
      }
      ffn_role(h, j, r);
      cluster_wait();
      mbar_wait(BAR(B_UVD));
      asm volatile("fence.acq_rel.gpu;" ::: "memory");
      if (lane < 8) red_hint(G->hint[7][lane]);
      unsigned x;
      int it = 0;
#pragma unroll 1
      do { asm volatile("ld.acquire.gpu.global.u32 %0, [%1];" : "=r"(x) : "l"(G->hint[7][bid >> 4]) : "memory"); } while (__any_sync(~0u, x != 128 * epoch) && ++it < SPIN_LIMIT);
      fence_async_all();
      const int ch = D_ * (epoch & 1);
      mbar_wait(BAR(B_EXT));
      mbar_wait(BAR(B_EMPTY + 18));
      if (elect()) {
        mbar_expect_tx(BAR(B_FULL + 32), 20480);
#pragma unroll
        for (int k = 0; k < 4; k++) tma2d(base + (k < 3 ? OFF_X1 + k * WSLOT : OFF_SX), &maps.x1b, 128 * r + 64 * h, ch + 128 * j + 32 * (k ^ (j & 1)), BAR(B_FULL + 32));
        tma2d(base + OFF_SX + 4096, &maps.x1b, 128 * r + 64 * h, ch + 512 + 32 * j, BAR(B_FULL + 32));
        mbar_expect_tx(BAR(B_FULL), 8192); mbar_expect_tx(BAR(B_FULL + 1), 8192); mbar_expect_tx(BAR(B_FULL + 2), 4096);
      }
      mbar_wait(BAR(B_EMPTY + 27));
      if (elect()) mbar_arrive_remote(mapa(BAR(B_XFREE), h ^ 1));
    } else {
      LAUNCHES;
      uint32_t epoch;
      {
        REGION_IDS;
        uint32_t dv;
        asm volatile("ld.global.nc.u16 %0, [%1];" : "=r"(dv) : "l"(P.ssmd + 128 * (lane & 7) % D_ + bid));
        if (lane < 5) sts128(base + tab(T_F, lane) + (w & 1) * (F_O - 16), 0, 0, 0, 0);
        epoch = EPOCH;
        __syncwarp();
#pragma unroll 1
        for (int c = 0; c < 5; c++) {
          const float d = i0 == 64 ? bf_lo(dv) : 0.f;
          dv = __shfl_down_sync(~0u, dv, 1);
          const uint32_t a = base + tab(T_F, c) + 16 * (i0 - 64);
          mbar_wait(BAR(B_FRAW + c));
#pragma unroll
          for (int k = 0; k < 4; k++) {
            uint4 x = lds128(a + F_E + 1024 * k);
            const uint32_t pv = lds32(a + F_E - 4 + 1024 * k);
            if (k == 0) { x.x = pack_bf16(bf_lo(x.x) + d, bf_hi(x.x)); sts32(a + F_E, x.x); }
            sts128(a + F_O + 1024 * k, __byte_perm(pv, x.x, 0x5432), __byte_perm(x.x, x.y, 0x5432), __byte_perm(x.y, x.z, 0x5432), __byte_perm(x.z, x.w, 0x5432));
          }
          __syncwarp();
          if (elect()) mbar_arrive2(BAR(B_FRDY + c));
          if (c == 0 && w == P.fin) row_stats(G, base, epoch);
        }
      }
      REGION_IDS;
      int h, j, r;
      ffn_role(h, j, r);
      cluster_wait();
      if (w == 2) {
        const unsigned* fp = G->xsh[lane < 10 ? lane >> 1 : 0][(r & 6) + (lane & 1)];
        uint32_t rdy = 0, s = 0;
        mbar_wait(BAR(B_QTD));
        mbar_wait(BAR(B_FL + 2));
#pragma unroll 1
        for (int n = 0; n < 10; n++) {
          mbar_wait(BAR(n < 2 ? B_FL + 3 + n : n == 2 ? B_PFULL + 4 : B_EMPTY + 2 * n - 5));
#pragma unroll 1
          for (int it = 0; !(rdy >> n & 1) && it < SPIN_LIMIT; it++) rdy = __ballot_sync(~0u, ld_relaxed32(fp) == 64 * epoch);
          if (elect()) {
            tma2d(base + OFF_A + s, &maps.xs, 128 * r + 64 * h, 64 * n, BAR(B_FULL + 2 * n));
            tma2d(base + OFF_A + ARING + s, &maps.xs, 128 * r + 64 - 64 * h, 64 * n, BAR(B_FULL + 2 * n));
          }
          s = s == 2 * ASLOT ? 0 : s + ASLOT;
        }
      } else {
        if (P.m3 < 5) mod_poll(G, base, P.m3, 1, epoch);
        float4 s = {};
        uint32_t ph = 0, pre = 0;
        mbar_wait(BAR(B_FL + 2));
        mbar_wait(BAR(B_PFULL + 3));
#pragma unroll 1
        for (int c = 0; c < 5; c = c == 1 ? 4 : c + 1) {
          if (c == 4) {
            ffn_role(h, j, r);
            mbar_wait(BAR(B_PEMPTY + 4));
            if (elect()) {
              mbar_expect_tx(BAR(B_UVE), 6144);
              tma3d(base + OFF_UVE, &maps.w1e + (r & 1), 0, 40 * (r & 14) + 64, 3 * (4 * h + j), BAR(B_UVE));
            }
          }
          strip<0, 1>(G, &maps.x1s, base, c, epoch, ph, pre, s);
        }
        mbar_wait(BAR(B_S3));
        const uint4 y = lds128(base + OFF_SX + 4096 + 16 * lane);
        const float s0 = s.x + __uint_as_float(y.x), q0 = s.y + __uint_as_float(y.y), s1 = s.z + __uint_as_float(y.z), q1 = s.w + __uint_as_float(y.w);
        ffn_role(h, j, r);
        asm volatile("{.reg .b128 t, x; .reg .b64 a, b; mov.b64 a, {%1,%2}; mov.b64 b, {%3,%4}; mov.b128 x, {a,b}; atom.relaxed.gpu.global.exch.b128 t, [%0], x;}"
                     ::"l"(&G->st2[2 * r + h][j][4 * lane]), "r"((__float_as_uint(s0) & ~1u) | (epoch & 1)), "f"(q0), "r"((__float_as_uint(s1) & ~1u) | (epoch & 1)), "f"(q1) : "memory");
        uint4* z = G->x1[~epoch & 1] + 1280 * bid + lane;
#pragma unroll 1
        for (int k = 0; k < 40; k++) st_relaxed128(z + 32 * k, 0, 0, 0, 0);
      }
    }
  } else if (wg == 2) {
    asm volatile("setmaxnreg.dec.sync.aligned.u32 40;");
    mbar_init<12>(BAR(B_FULL + 12 * w), 1);
    mbar_init<9>(BAR(B_EMPTY - 1 + 9 * w), 8);
    asm volatile("fence.mbarrier_init.release.cluster;" ::: "memory");
    LAUNCHES;
    const uint32_t epoch = EPOCH;
    cluster_wait();
#pragma unroll 1
    for (uint64_t prog = P.prog; prog; prog >>= 4) {
      REGION_IDS;
      const int s = (prog & 7) - 1;
      if (!(prog & 8)) {
        const uint32_t a = base + tab(T_KV, s) + 128 * (lane & 3) + ((w ^ (lane & 3)) << 4) + 4 * (lane & 16) + (lane & 12), keep = ~(lane & 1), bit = epoch & lane & 1;
        uint4* dst = G->xr + (128 * s + 64 * (bid & 1) + 8 * w + 2 * (lane & 16) + (lane >> 1 & 6)) * 256 + 255 - 4 * (bid >> 1) - (lane & 3);
        mbar_wait(BAR(B_KV));
        mbar_wait(BAR(B_KV + s));
        const uint4 wv = lds128(base + OFF_TAP + 512 * s + 64 * w + 16 * (lane & 16) + 4 * (lane & 12));
        uint32_t kk[11], r[8];
#pragma unroll
        for (int k = 0; k < 11; k++) kk[k] = k < 3 ? lds32((a ^ (64 * (k & 1))) + KV_H + 512 * k) : lds32((a ^ (64 * (~k & 1))) + 512 * (k - 3));
        if (elect()) red_hint(G->hint[s][4 * (bid & 1) + w]);
#pragma unroll
        for (int k = 0; k < 8; k++) r[k] = lds32((a ^ (64 * (k & 1))) + KV_V + 512 * k);
        const uint32_t w0 = __byte_perm(wv.x, wv.z, 0x5410), w1 = __byte_perm(wv.x, wv.z, 0x7632),
                       w2 = __byte_perm(wv.y, wv.w, 0x5410), w3 = __byte_perm(wv.y, wv.w, 0x7632);
#pragma unroll
        for (int k = 0; k < 8; k++) r[k] = bmul2(bfma2(kk[k + 3], w0, bfma2(kk[k + 2], w1, bfma2(kk[k + 1], w2, bmul2(kk[k], w3)))), r[k]);
        st_relaxed128(dst, (__byte_perm(r[7], r[6], 0x5410) & keep) | bit, __byte_perm(r[5], r[4], 0x5410), __byte_perm(r[3], r[2], 0x5410), __byte_perm(r[1], r[0], 0x5410));
        st_relaxed128(dst + 256, (__byte_perm(r[7], r[6], 0x7632) & keep) | bit, __byte_perm(r[5], r[4], 0x7632), __byte_perm(r[3], r[2], 0x7632), __byte_perm(r[1], r[0], 0x7632));
      } else if (s >= 0) {
        const int tr = 4 * (lane & 1) + (lane >> 1 & 3);
        const uint32_t a = base + OFF_Q + 4096 * s + 128 * ((lane & 24) + tr) + ((w ^ tr) << 4);
        uint4* dst = G->qt + (128 * s + 64 * (bid & 1) + 8 * w + (lane >> 2)) * 256 + 4 * (bid >> 1) + (lane & 3);
        mbar_wait(BAR(B_Q + s));
#pragma unroll
        for (int k = 0; k < 2; k++) {
          uint32_t x[4];
          ldmatrix_x4_t(x, a ^ (64 * k));
          st_relaxed128(dst + 8192 * k, set_tag(x[0], ~lane & 1, epoch), x[1], x[2], x[3]);
        }
      } else if (w == 3) {
        row_stats(G, base, epoch);
      }
    }
    arrive1(BAR(B_QTD));
    {
      REGION_IDS;
      const uint32_t tag = opaque(~lane & 1);
      const uint32_t io = 16 * i0;
      uint4* gp = (uint4*)((char*)(G->xs + 256 * blockIdx.x) + io);
      constexpr int QO = -D_ * 256;
      const uint32_t sa = base + io;
      uint4 q[2];
      if (w == 0 && P.mr2) mr_poll(G, base, epoch);
      mbar_wait(BAR(B_QTOK));
      q[0] = ld_relaxed128(gp + QO);
      q[1] = ld_relaxed128(gp + QO + 128);
#pragma unroll 1
      for (int it = 0; it < SPIN_LIMIT; it++) {
        mbar_wait(BAR(B_MR), it & 1);
        const uint32_t x = lds32(sa + 16 * i0 + OFF_MR), y = lds32(sa + 16 * i0 + OFF_MR + 4096);
        sts32(sa + 16 * i0 + OFF_MR, x & 0xFFFF7FFFu);
        if (bar_all(3, !(((x >> 15 ^ epoch) | (y ^ epoch)) & 1))) break;
        if (w == 0 && elect()) { fence_async_smem(); mbar_expect_tx(BAR(B_MR), 8192); bulk_load(base + OFF_MR, G->st1, 8192, BAR(B_MR)); }
      }
#pragma unroll 1
      for (int c = 0; c < 5; c++) {
        mbar_wait(BAR(B_MODR + c));
        uint4 co = lds128(base + OFF_MODR + 16 * c);
        co.x = bmul2(co.x, co.z); co.y = bmul2(co.y, co.z);
        mbar_wait(BAR(B_PFULL + c));
        const uint32_t pb = io + (base + tab(T_P, c));
        gp = (uint4*)((char*)(G->xs + 256 * blockIdx.x + 32768 * c) + io);
#pragma unroll
        for (int hf = 0; hf < 2; hf++) {
#pragma unroll 1
          for (int it = 0; __any_sync(~0u, set_tag(q[hf].x, tag, epoch) != q[hf].x) && it < SPIN_LIMIT; it++) {
            q[hf] = ld_relaxed128(gp + QO + 128 * hf);
          }
          uint4 y = lds128(pb + 2048 * hf), z = lds128(pb + 2048 * hf + 4096);
          y.x = badd2(y.x, z.x); y.y = badd2(y.y, z.y); y.z = badd2(y.z, z.z); y.w = badd2(y.w, z.w);
          z = lds128(pb + 2048 * hf + 8192);
          uint4 m = lds128(pb + 2048 * hf + 12288);
          y.x = badd2(y.x, badd2(z.x, m.x)); y.y = badd2(y.y, badd2(z.y, m.y)); y.z = badd2(y.z, badd2(z.z, m.z)); y.w = badd2(y.w, badd2(z.w, m.w));
          z = lds128(sa + OFF_MR + 2048 * hf);
          m = lds128(sa + OFF_MR + 2048 * hf + 4096);
          y.x = bfma2(bfma2(bfma2(q[hf].x, z.x, m.x), co.y, co.x), y.x, q[hf].x);
          if (hf) {
            __syncwarp();
            asm volatile("{.reg .pred p; elect.sync _|p, 0xffffffff; @p red.relaxed.gpu.global.add.u32 [%0], 1; @p mbarrier.arrive.shared::cta.b64 _, [%1];}"
                         ::"l"(G->xsh[c][2 * w + (blockIdx.x >> 6)]), "r"(BAR(B_PEMPTY + c)), "r"(y.x) : "memory");
          }
          y.y = bfma2(bfma2(bfma2(q[hf].y, z.y, m.y), co.y, co.x), y.y, q[hf].y);
          y.z = bfma2(bfma2(bfma2(q[hf].z, z.z, m.z), co.y, co.x), y.z, q[hf].z);
          y.w = bfma2(bfma2(bfma2(q[hf].w, z.w, m.w), co.y, co.x), y.w, q[hf].w);
          st_relaxed128(gp + 128 * hf, set_tag(bmul2(y.x, co.w), tag, epoch), bmul2(y.y, co.w), bmul2(y.z, co.w), bmul2(y.w, co.w));
          asm volatile("{.reg .pred p; .reg .b32 t; setp.ne.u32 p, %5, 0; max.u32 t, %1, 1; @!p st.relaxed.gpu.global.v4.u32 [%0+%6], {t,%2,%3,%4}; @p st.relaxed.gpu.global.v4.u32 [%0+%7], {t,%2,%3,%4};}"
                       ::"l"(gp + 128 * hf), "r"(y.x), "r"(y.y), "r"(y.z), "r"(y.w), "r"(epoch & 1), "n"(D_ * 4096), "n"(D_ * 8192) : "memory");
          if (c < 4) q[hf] = ld_relaxed128(gp + QO + 32768 + 128 * hf);
        }
      }
    }
    int h, j, r;
    ffn_role(h, j, r);
    {
      REGION_IDS;
      mbar_wait(BAR(B_UVB));
      float d[12] = {};
      fence_regs(d);
      wg_fence();
#pragma unroll
      for (int k = 0; k < 15; k++) {
        if (k == 12) { wg_commit(); mbar_wait(BAR(B_UVE)); wg_fence(); }
        wg_ss8_10(d + 4 * (k % 3), mkdesc(DB + (k < 12 ? OFF_UV + 12288 * (k / 6) + 4096 * (k % 3) + 2048 * (k / 3 & 1) : OFF_UVE + 2048 * (k % 3)), 16, 1024, 1),
                  mkdesc(DB + OFF_CO + 64 * (k / 3), 32, 128, 0), 1);
      }
      wg_commit();
      const int row = (r & 14) + (lane >> 2 & 1);
      uint32_t* dst = &G->uv[4 * h + j][32 * row + 4 * ((2 * w ^ row) & 6) + (lane & 3)];
      const uint32_t tag = !(lane & 3);
      wg_wait<0>();
      fence_regs(d);
      if (elect()) { red_hint(G->hint[8][4 * h + j]); mbar_arrive(BAR(B_UVD)); }
      uint32_t x[6];
#pragma unroll
      for (int k = 0; k < 6; k++) asm volatile("movmatrix.sync.aligned.m8n8.trans.b16 %0, %1;" : "=r"(x[k]) : "r"(pack_bf16(d[2 * k], d[2 * k + 1])));
      if (lane < 8) {
#pragma unroll
        for (int k = 0; k < 6; k++) st_relaxed32(dst + 512 * w_block(r & 1, k >> 1) + ((4 * k ^ lane) & 4), set_tag(x[k], tag, epoch));
      }
    }
    {
      REGION_IDS;
      if (w == 0) {
        int it = 0;
#pragma unroll 1
        while (__any_sync(~0u, ld_relaxed32(G->hint[8][4 * h + j]) != 64 * epoch) && ++it < SPIN_LIMIT);
        if (elect()) { mbar_expect_tx(BAR(B_BX), 12288); bulk_load(base + OFF_BX, G->uv[4 * h + j], 12288, BAR(B_BX)); }
      }
      const uint32_t* sp = &G->st2[2 * r + (h ^ (w >> 1))][0][2 * (i0 & 63)];
      uint2 x[4];
      int it = 0;
#pragma unroll 1
      do {
#pragma unroll
        for (int k = 0; k < 4; k++) x[k] = ld_relaxed64(sp + 128 * k);
      } while (__any_sync(~0u, ((x[0].x ^ epoch) | (x[1].x ^ epoch) | (x[2].x ^ epoch) | (x[3].x ^ epoch)) & 1) && ++it < SPIN_LIMIT);
      float m, sd;
      ln_final((__uint_as_float(x[0].x) + __uint_as_float(x[1].x)) + (__uint_as_float(x[2].x) + __uint_as_float(x[3].x)),
               (__uint_as_float(x[0].y) + __uint_as_float(x[1].y)) + (__uint_as_float(x[2].y) + __uint_as_float(x[3].y)), m, sd);
      const uint32_t e = pack_bf16(-m, sd);
      sts128(base + OFF_AX + 16 * i0, e, e, e, e);
      sts32(base + OFF_RT + 4 * i0, __float_as_uint(rcpf(sd)));
      fence_async_smem();
#pragma unroll 1
      for (it = 0; it < SPIN_LIMIT; it++) {
        mbar_wait(BAR(B_BX), it & 1);
        uint32_t y = 0;
#pragma unroll
        for (int k = 0; k < 6; k++) y |= lds32(base + OFF_BX + 16 * i0 + 2048 * k) ^ epoch;
        if (bar_all(3, !(y & 1))) break;
        if (w == 0 && elect()) { mbar_expect_tx(BAR(B_BX), 12288); bulk_load(base + OFF_BX, G->uv[4 * h + j], 12288, BAR(B_BX)); }
      }
      arrive1(BAR(B_EXT));
      {
        uint2 g0, g1;
        int it = 0;
#pragma unroll 1
        do {
          g0 = ld_relaxed64(&G->modv[1][128 * j + i0]);
          g1 = ld_relaxed64(&G->modv[1][512 + 32 * j + lane]);
        } while (__any_sync(~0u, ((g0.x ^ epoch) | (g0.y ^ epoch) | (g1.x ^ epoch) | (g1.y ^ epoch)) & 1) && ++it < SPIN_LIMIT);
        const uint32_t ga = base + OFF_GB + 80 * (lane >> 1 & 3) + 2 * (lane & 1) + (lane >> 3) * 4;
        asm volatile("st.shared.u16 [%0], %1;" ::"r"(ga + 16 * (w ^ (j & 1))), "h"((uint16_t)(mod_sum(g0) >> 16)) : "memory");
        asm volatile("st.shared.u16 [%0], %1;" ::"r"(ga + 64), "h"((uint16_t)(mod_sum(g1) >> 16)) : "memory");
        arrive1(BAR(B_GB));
      }
      const int id = 16 * r + 4 * h + fslice(j, w);
#pragma unroll 1
      for (int q = w == 3 ? 3 : 0; q < 3; q++) {
        const int m = 3 * q + w;
        const uint4* src = G->hh + id * 1536 + 512 * q;
        it = 0;
#pragma unroll 1
        while (__any_sync(~0u, ld_relaxed32(&G->hhf[8 * id + 64 * (lane & 1) + q]) != 4 * epoch) && ++it < SPIN_LIMIT);
        mbar_wait(BAR(P.hid[2][m]));
        if (elect()) {
          bulk_load(base + OFF_A + h * ARING + P.hid[h][m], src, ASLOT, BAR(B_FULL + 23 + m));
          bulk_load(base + OFF_A + ARING - h * ARING + P.hid[h ^ 1][m], src + 8 * 1536, ASLOT, BAR(B_FULL + 23 + m));
        }
      }
    }
  } else {
    asm volatile("setmaxnreg.inc.sync.aligned.u32 224;");
    LAUNCHES;
    if (wg == 1) silu_vector(P.c, base);
    uint32_t par = EPOCH & 1;
    cluster_wait();
    {
      float acc[128];
      uint32_t A[64];
#pragma unroll
      for (int i = 0; i < 64; i++) A[i] = 0;
      int c = wg;
#pragma unroll 1
      for (uint64_t prog = P.cprog[wg]; prog; prog >>= 8) {
        REGION_IDS;
        const int s = prog & 7;
        if (s < 5) {
          const uint32_t a = base + tab(T_KV, s) + 128 * (lane & 3) + ((w ^ (lane & 3)) << 4) + 4 * (lane & 16) + (lane & 12), keep = ~(lane & 1), bit = par & lane;
          uint4* dst = G->xr + (128 * s + 64 * (bid & 1) + 8 * w + 2 * (lane & 16) + (lane >> 1 & 6)) * 256 + 255 - 4 * (bid >> 1) - (lane & 3);
          mbar_wait(BAR(B_KV));
          mbar_wait(BAR(B_KV + s));
          const uint4 wv = lds128(base + OFF_TAP + 512 * s + 64 * w + 16 * (lane & 16) + 4 * (lane & 12));
          uint32_t kk[11], r[8];
#pragma unroll
          for (int k = 0; k < 11; k++) kk[k] = k < 3 ? lds32((a ^ (64 * (k & 1))) + KV_H + 512 * k) : lds32((a ^ (64 * (~k & 1))) + 512 * (k - 3));
          if (elect()) red_hint(G->hint[s][4 * (bid & 1) + w]);
#pragma unroll
          for (int k = 0; k < 8; k++) r[k] = lds32((a ^ (64 * (k & 1))) + KV_V + 512 * k);
          const uint32_t w0 = __byte_perm(wv.x, wv.z, 0x5410), w1 = __byte_perm(wv.x, wv.z, 0x7632),
                         w2 = __byte_perm(wv.y, wv.w, 0x5410), w3 = __byte_perm(wv.y, wv.w, 0x7632);
#pragma unroll
          for (int k = 0; k < 8; k++) r[k] = bmul2(bfma2(kk[k + 3], w0, bfma2(kk[k + 2], w1, bfma2(kk[k + 1], w2, bmul2(kk[k], w3)))), r[k]);
          st_relaxed128(dst, (__byte_perm(r[7], r[6], 0x5410) & keep) | bit, __byte_perm(r[5], r[4], 0x5410), __byte_perm(r[3], r[2], 0x5410), __byte_perm(r[1], r[0], 0x5410));
          st_relaxed128(dst + 256, (__byte_perm(r[7], r[6], 0x7632) & keep) | bit, __byte_perm(r[5], r[4], 0x7632), __byte_perm(r[3], r[2], 0x7632), __byte_perm(r[1], r[0], 0x7632));
        }
        if (prog & 8) {
          float s0 = 0.f, s1 = 0.f, q0 = 0.f, q1 = 0.f;
          const uint32_t a = OFF_Q + 1024 * w + 128 * (lane & 7) + (((lane >> 3) ^ (lane & 7)) << 4);
          const uint32_t ra = mapa(base + OFF_ST + 128 * (bid & 1) + 64 * (lane & 1) + 16 * w + 8 * (lane >> 2), lane >> 1 & 1), rb = mapa(BAR(B_ST1), lane >> 1 & 1);
          if (w == 3 && elect()) mbar_expect_tx(BAR(B_ST1), 256);
#pragma unroll 1
          for (int k = 0; k < 5; k++) {
            mbar_wait(BAR(B_Q + k));
            const uint32_t o = opaque(base + 4096 * k);
            const uint4 x = lds128(o + a), y = lds128(o + (a ^ 64));
            const uint32_t e[8] = {x.x, x.y, x.z, x.w, y.x, y.y, y.z, y.w};
#pragma unroll
            for (int i = 0; i < 8; i++) { const float lo = bf_lo(e[i]), hi = bf_hi(e[i]); s0 += lo; s1 += hi; q0 = fmaf(lo, lo, q0); q1 = fmaf(hi, hi, q1); }
          }
          s0 += s1; q0 += q1;
          s0 += __shfl_xor_sync(~0u, s0, 8); q0 += __shfl_xor_sync(~0u, q0, 8);
          s0 += __shfl_xor_sync(~0u, s0, 16); q0 += __shfl_xor_sync(~0u, q0, 16);
          if (lane < 8) asm volatile("st.async.shared::cluster.mbarrier::complete_tx::bytes.v2.b32 [%0], {%1,%2}, [%3];" ::"r"(ra), "r"(__float_as_uint(s0)), "r"(__float_as_uint(q0)), "r"(rb) : "memory");
        }
        if (prog & 32) {
          const int L = 16 * w + (lane >> 2) + 2 * (lane & 3) - 7;
          const uint32_t fo = base + ((L & 1) ? F_O + 2 * (L + 1) : F_E + 2 * L);
          mbar_wait(BAR(B_FRDY + c));
          cload<0, 0>(A, fo + tab(T_F, c));
          cload<15, 1>(A, fo + tab(T_F, c));
          arrive1(BAR(B_FL + c));
        }
        if (!(prog & 64)) continue;
        uint32_t xo;
        if (P.turn >> c & 1) mbar_wait(BAR(B_TURN - 3 + c));
#pragma unroll 1
        for (int it = 0; it < SPIN_LIMIT; it++) {
          xo = tab(T_X, opaque(c));
          mbar_wait(BAR(B_XR + c), it & 1);
          const uint32_t tag = lds32(base + xo + 32 * i0);
          wg_fence();
          csteps<0, 0>(acc, A, mkdesc(DB + xo, 16, 128, 0));
          csteps<15, 6>(acc, A, mkdesc(DB + xo, 16, 128, 0));
          wg_commit();
          if (bar_all(1 + wg, !((tag ^ par) & 1))) break;
          wg_wait<0>();
          if (w == 0 && elect()) { mbar_expect_tx(BAR(B_XR + c), 4096); bulk_load(base + xo, G->xr + (128 * c + bid) * 256, 4096, BAR(B_XR + c)); }
        }
        wg_fence();
        csteps<5, 1>(acc, A, mkdesc(DB + tab(T_X, opaque(c)), 16, 128, 0));
        wg_commit();
        if (c >= 2 && c < 4 && elect()) mbar_arrive(BAR(B_TURN - 2 + c));
        if (c >= 3) mbar_wait(BAR(B_PEMPTY + c - 3));
        wg_wait<0>();
        fence_regs(acc);
        const uint32_t pb = base + tab(T_P, c) + 4096 * w;
#pragma unroll
        for (int k = 0; k < 8; k++) {
          uint32_t p[4];
#pragma unroll
          for (int e = 0; e < 4; e++) { const int i = 4 * k + e; p[e] = i < 31 ? pack_bf16(acc[4 * i] + acc[4 * i + 6], acc[4 * i + 1] + acc[4 * i + 7]) : pack_bf16(acc[124], acc[125]); }
          if (k == 0 && (lane & 3) < w) p[0] = 0;
          stmatrix_x4_t(k == 0 ? pb + 16 * ((255 - lane + 2 * w) & 255) : pb + 16 * (255 - lane + 2 * w) - 512 * k, p[0], p[1], p[2], p[3]);
        }
        arrive1(BAR(B_PFULL + c));
        c += 2;
      }
    }
    if (wg) {
      REGION_IDS;
      if (bid >= P.ulo && bid < P.uhi) {
        named_bar(2, 128);
        mbar_wait(BAR(B_WM));
        mod_gemv(G, OFF_WM, bid, w, lane, par);
      }
      arrive1(BAR(B_G3));
    }
    uint32_t ck;
    { REGION_IDS; ck = base + OFF_A + wg * ARING + lane * 128 + (((2 * w) ^ (lane & 7)) << 4); }
    const uint32_t abd = DB + OFF_A + wg * ARING;
    auto a_tile = [&](int as, int n, bool first) {
#pragma unroll 1
      for (int it = 0; __any_sync(~0u, ((lds32(ck + as) ^ par) | (lds32(ck + as + (first ? 4096 : 256)) ^ par)) & 1) && it < SPIN_LIMIT; it++) {
        int h, j, r;
        ffn_role(h, j, r);
        if (elect()) {
          const uint32_t dst = base + OFF_A + wg * ARING + as;
          mbar_expect_tx(BAR(B_RETRY + wid), ASLOT);
          if (first) tma2d(dst, &maps.xs, 128 * r + 64 * (h ^ wg), 64 * n, BAR(B_RETRY + wid));
          else bulk_load(dst, G->hh + ((2 * r + (h ^ wg)) * 8 + 4 * h + fslice(j, n % 3)) * 1536 + (n / 3) * 512, ASLOT, BAR(B_RETRY + wid));
        }
        mbar_wait(BAR(B_RETRY + wid), par >> 1);
        par ^= 2;
      }
    };
    float acc[192];
    int ws = 0, as = 0;
#pragma unroll 1
    for (int u = 0; u < 20 - NT; u++) {
      mbar_wait(BAR(B_FULL + u));
      if (!(u & 1)) a_tile(as, u >> 1, true);
      wg_fence();
#pragma unroll
      for (int k = 0; k < 4; k++) wg_ss192_11(acc + 96 * (k & 1), mkdesc(abd + as + k / 2 * 2048, 16, 1024, 1), mkdesc(DB + ws + 12288 * (k & 1) + k / 2 * 2048, 4096, 1024, 1), u + k / 2);
      wg_commit();
      wg_wait<1>();
      if (elect()) mbar_arrive(BAR(B_EMPTY + u - 1));
      ws = next_slot(ws);
      as = as == 5 * ASLOT / 2 ? 0 : as + ASLOT / 2;
    }
    auto tail = [&](int v, int i) {
      const int u = 20 - NT + i / 2;
      if (i < 2 * NT) wg_ss192_11(acc + 96 * v, mkdesc(opaque(abd) + u % 6 * 4096 + (i & 1) * 2048, 16, 1024, 1), mkdesc(DB + u % 5 * WSLOT + (i & 1) * 2048 + 12288 * v, 4096, 1024, 1), 1);
      if (i == 2 * NT) wg_ss192_01(acc + 96 * v, mkdesc(DB + OFF_AX + 1024 * opaque(wg), 0, 128, 0), mkdesc(DB + OFF_BX + 6144 * v, 2048, 1024, 1), 1);
    };
#pragma unroll
    for (int u = 20 - NT; u <= 20; u++) {
      mbar_wait(BAR(u < 20 ? B_FULL + u : B_EXT));
      if (u == 16 || u == 18) a_tile(u % 6 * 4096, u >> 1, true);
      wg_fence();
      tail(0, 2 * (u + NT - 20));
      tail(0, 2 * (u + NT - 20) + 1);
      wg_commit();
      if (u == 20 - NT) { wg_wait<1>(); if (elect()) mbar_arrive(BAR(B_EMPTY + u - 1)); }
    }
    float o[80];
    uint32_t fr[3][16], bo;
    {
      int h, j, r;
      ffn_role(h, j, r);
      REGION_IDS;
      const float r0 = 0.5f * __uint_as_float(lds32(base + OFF_RT + 256 * wg + 64 * w + (lane & 28))), r1 = 0.5f * __uint_as_float(lds32(base + OFF_RT + 256 * wg + 64 * w + 32 + (lane & 28)));
      const int id = (2 * r + (h ^ wg)) * 8 + 4 * h + j;
      uint4* const hdst = G->hh + id * 1536 + 128 * w + (lane ^ lane >> 3);
      const uint32_t keep = ~(~lane & 1), bit = par & ~keep;
      bo = 1024 + ((j & 1) << 23);
      auto own = [&](int i) { wg_rs160_1(o, fr[i >> 2] + 4 * (i & 3), mkdesc(DB + (5 + i / 4) % 6 * WSLOT + (i & 3) * 2048, 8192, bo, 1), i); };
      auto gate = [&](float* g) { g[0] = silu2(g[0] * r0); g[1] = silu2(g[1] * r0); g[2] = silu2(g[2] * r1); g[3] = silu2(g[3] * r1); };
      auto mix = [&](uint32_t* x, const float* g, const float* up) { x[0] = pack_bf16(g[0] * up[0], g[1] * up[1]); x[1] = pack_bf16(g[2] * up[2], g[3] * up[3]); };
      auto hint = [&](int v) { asm volatile("{.reg .pred p; setp.eq.u32 p, %1, 0; @p red.relaxed.gpu.global.add.u32 [%0], 1;}" ::"l"(&G->hhf[id * 8 + v]), "r"(lane) : "memory"); };
      auto put = [&](int v, int k) {
        uint32_t* x = fr[v] + 2 * k;
        const uint32_t t0 = (x[k / 2] & keep) | bit, t1 = (x[5 + k / 2] & keep) | bit;
        if (!v) { x[k / 2] = t0; x[5 + k / 2] = t1; }
        st_relaxed128(hdst + 512 * v + 8 * k, k ? x[0] : t0, k ? t0 : x[2], x[4], x[6]);
        st_relaxed128(hdst + 512 * v + 8 * k + 64, x[1], x[3], k ? x[5] : t1, k ? t1 : x[7]);
      };
      auto move = [&](uint32_t* x) {
#pragma unroll
        for (int k = 0; k < 16; k++) asm volatile("mul.rn.f32 %0, %0, %1;" : "+r"(x[k]) : "f"(P.one));
      };
      wg_fence();
      tail(1, 0);
      tail(1, 1);
      wg_commit();
      wg_wait<1>();
#pragma unroll
      for (int k = 0; k < 96; k++) asm volatile("" : "+f"(acc[k])::"memory");
      if (elect()) mbar_arrive(BAR(B_EMPTY + 18));
#pragma unroll
      for (int k = 15; k >= 0; k--) {
        gate(acc + (k < 8 ? 64 + 4 * k : 4 * k - 32));
        if (k >= 8) mix(fr[0] + 2 * k - 16, acc + 4 * k - 32, acc + 4 * k);
        if (k == 12 || k == 8) put(0, k - 8);
        if (9 - k / 2 <= 2 * NT) pin(P.ulo, k < 8 ? __float_as_uint(acc[67 + 4 * k]) : fr[0][2 * k - 15]);
        if (k == 9) hint(0);
        if (!(k & 1)) tail(1, 9 - k / 2);
        if (k == 18 - 4 * NT) wg_commit();
        if (!(k & 1) && 9 - k / 2 <= 2 * NT) split(P.ulo, k);
      }
      move(fr[0]);
      mbar_wait(BAR(B_FULL + 20));
      mbar_wait(BAR(B_FULL + 21));
      wg_wait<0>();
#pragma unroll
      for (int k = 96; k < 192; k++) asm volatile("" : "+f"(acc[k])::"memory");
      if (elect()) mbar_arrive(BAR(B_EMPTY + 19));
#pragma unroll
      for (int k = 7; k >= 0; k--) mix(fr[1] + 2 * k, acc + 64 + 4 * k, acc + 160 + 4 * k);
#pragma unroll
      for (int k = 0; k < 4; k++) pin4(P.ulo, fr[1] + 4 * k);
      wg_fence();
      own(0);
      own(1);
      split(P.ulo, 15);
      put(1, 4);
      hint(1);
      own(2);
      put(1, 0);
      own(3);
      wg_commit();
      split(P.ulo, 16);
#pragma unroll
      for (int k = 7; k >= 0; k--) {
        gate(acc + 96 + 4 * k);
        mix(fr[2] + 2 * k, acc + 96 + 4 * k, acc + 128 + 4 * k);
        if (!(k & 3)) put(2, k);
        if (k) pin(P.ulo, fr[2][2 * k + 1]);
        if (k == 1) hint(2);
        if (k & 1) own(7 - k / 2);
        if (k == 5 || k == 1) wg_commit();
        if (k == 5) { wg_wait<1>(); if (elect()) mbar_arrive(BAR(B_EMPTY + 20)); }
        if (k & 1) split(P.ulo, 16 + k);
      }
      mbar_wait(BAR(B_FULL + 22));
      wg_fence();
#pragma unroll
      for (int i = 8; i < 12; i++) own(i);
      wg_commit();
      wg_wait<1>();
      if (elect()) mbar_arrive(BAR(B_EMPTY + 21));
      ck = base + OFF_A + wg * ARING + 2048 * w + 516 * (lane >> 3) + 144 * (lane >> 2 & 1) + 32 * (lane & 3);
    }
    uint32_t x1[40];
    if (!wg) {
      REGION_IDS;
      const uint32_t xa = base + (lane >> 4) * 1024 + (lane & 7) * 128 + (((2 * w + ((lane >> 3) & 1)) ^ (lane & 7)) << 4);
      mbar_wait(BAR(B_FULL + 32));
#pragma unroll
      for (int k = 0; k < 10; k++) ldmatrix_x4_t(x1 + 4 * k, xa + (k < 6 ? OFF_X1 + k / 2 * WSLOT + (k & 1) * 2048 : OFF_SX + 2048 * (k - 6)));
    }
#pragma unroll 1
    for (int u = 23; u < (wg ? 32 : LAG2); u++) {
      as = P.hid[wg][u - 23];
      const uint64_t wd = mkdesc(0, 0, bo, 1) | P.w2t[u - 20].x;
      mbar_wait(BAR(B_FULL + u));
      a_tile(as, u - 23, false);
      wg_fence();
#pragma unroll
      for (int kk = 0; kk < 4; kk++) wg_ss160_01(o, mkdesc(abd + as + kk / 2 * 512 + (kk & 1) * 32, 16, 1024, 2), wd + kk * 128, 1);
      wg_commit();
      if (u == 31 && elect()) mbar_arrive(BAR(B_LAG));
      wg_wait<1>();
      if (elect()) mbar_arrive(BAR(B_EMPTY + u - 1));
    }
    int h, j, r;
    ffn_role(h, j, r);
    REGION_IDS;
    const uint32_t xb = base + OFF_XCH + 5120 * w;
    if (wg) {
      const uint32_t rdst = mapa(xb + 16 * lane, h ^ 1), rbar = mapa(BAR(B_FULL), h ^ 1);
      mbar_wait(BAR(B_XFREE));
      wg_wait<0>();
      fence_regs(o);
#pragma unroll
      for (int k = 0; k < 10; k++)
        asm volatile("st.async.shared::cluster.mbarrier::complete_tx::bytes.v4.b32 [%0], {%1,%2,%3,%4}, [%5];" ::"r"(rdst + 512 * k), "r"(pack_bf16(o[8 * k], o[8 * k + 1])),
                     "r"(pack_bf16(o[8 * k + 2], o[8 * k + 3])), "r"(pack_bf16(o[8 * k + 4], o[8 * k + 5])), "r"(pack_bf16(o[8 * k + 6], o[8 * k + 7])), "r"(rbar + 8 * (k / 4)) : "memory");
    } else {
      uint32_t gr[40];
      {
        const float r0 = __uint_as_float(lds32(base + OFF_RT + 64 * w + (lane & 28))), r1 = __uint_as_float(lds32(base + OFF_RT + 64 * w + 32 + (lane & 28)));
        const uint32_t p0 = pack_bf16(r0, r0), p1 = pack_bf16(r1, r1);
        mbar_wait(BAR(B_GB));
#pragma unroll
        for (int k = 0; k < 5; k++) {
          const uint4 g = lds128(base + OFF_GB + 80 * (lane & 3) + 16 * k);
          gr[8 * k] = bmul2(g.x, p0); gr[8 * k + 1] = bmul2(g.x, p1); gr[8 * k + 2] = bmul2(g.y, p0); gr[8 * k + 3] = bmul2(g.y, p1);
          gr[8 * k + 4] = bmul2(g.z, p0); gr[8 * k + 5] = bmul2(g.z, p1); gr[8 * k + 6] = bmul2(g.w, p0); gr[8 * k + 7] = bmul2(g.w, p1);
        }
      }
      wg_wait<0>();
      if (elect()) mbar_arrive(BAR(B_EMPTY + LAG2 - 1));
#pragma unroll 1
      for (int u = LAG2; u < 32; u++) {
        mbar_wait(BAR(B_FULL + u));
        a_tile(P.hid[0][u - 23], u - 23, false);
      }
      auto da = [&](int i) { return mkdesc(DB + hid_at(i / 4 + LAG2 - 23, 0) + (i & 2) * 256 + (i & 1) * 32, 16, 1024, 2); };
      auto db = [&](int i, int b) { return mkdesc(DB + w2_at(i / 4 + LAG2 - 20) + b * w2_step(i / 4 + LAG2 - 20) + (i & 3) * 2048, w2_step(i / 4 + LAG2 - 20), bo, 1); };
      const int row = 128 * r + 64 * h + 16 * w;
      auto merge = [&](int e) {
        if (e % 4 == 0) mbar_wait_cluster(BAR(B_FULL + e / 4), 1);
        const uint4 p = lds128(xb + 16 * lane + 512 * e);
        x1[4 * e] = bfma2(gr[4 * e], p.x, x1[4 * e]); x1[4 * e + 1] = bfma2(gr[4 * e + 1], p.y, x1[4 * e + 1]);
        x1[4 * e + 2] = bfma2(gr[4 * e + 2], p.z, x1[4 * e + 2]); x1[4 * e + 3] = bfma2(gr[4 * e + 3], p.w, x1[4 * e + 3]);
      };
      auto out = [&](int k) {
        const float* v = o + 8 * k;
        uint32_t y[4];
#pragma unroll
        for (int e = 0; e < 4; e++) y[e] = bfma2(gr[4 * k + e], pack_bf16(v[2 * e], v[2 * e + 1]), x1[4 * k + e]);
        stmatrix_x4(k < 8 ? xb + 2048 * (k >> 2) + (lane & 15) * 128 + (((2 * (k & 3) + (lane >> 4)) ^ (lane & 7) ^ 4 * (j & 1)) << 4)
                          : xb + 4096 + (lane & 15) * 64 + (((2 * (k & 1) + (lane >> 4)) ^ (lane >> 1 & 3)) << 4), y[0], y[1], y[2], y[3]);
        if ((k & 3) == 3 || k == 9) {
          fence_async_smem();
          __syncwarp();
          if (lane == 0) tma2d_store(k < 8 ? &maps.outa : &maps.outb, k < 8 ? 128 * j + 64 * (k >> 2) : 512 + 32 * j, row, xb + 2048 * (k >> 2));
        }
      };
      constexpr int ND = 128 - 4 * LAG2;
      mbar_wait(BAR(B_LAG));
      wg_fence();
#pragma unroll
      for (int i = 0; i < ND; i++) wg_ss160_01(o, da(i), db(i, 0), 1);
      wg_commit();
#pragma unroll
      for (int e = 0; e < MG; e++) merge(e);
      __syncwarp();
      wg_wait<0>();
      fence_regs(o);
#pragma unroll
      for (int k = 0; k < 10; k++) {
        if (k >= MG && k % 4 == 0) {
#pragma unroll
          for (int e = k; e < min(k + 4, 10); e++) merge(e);
          __syncwarp();
        }
        out(k);
      }
      if (lane == 0) { bulk_commit(); bulk_wait_read(); }
    }
  }
}

typedef CUresult (*EncFn)(CUtensorMap*, CUtensorMapDataType, cuuint32_t, void*, const cuuint64_t*, const cuuint64_t*, const cuuint32_t*,
                          const cuuint32_t*, CUtensorMapInterleave, CUtensorMapSwizzle, CUtensorMapL2promotion, CUtensorMapFloatOOBfill);
static int enc_err = 0;
static void enc(EncFn fn, CUtensorMap* m, const void* p, int rank, const cuuint64_t* gd, const cuuint64_t* gs, const cuuint32_t* bd, CUtensorMapSwizzle sw) {
  cuuint32_t es[5] = {1, 1, 1, 1, 1};
  enc_err = 2 * enc_err + (fn(m, CU_TENSOR_MAP_DATA_TYPE_BFLOAT16, rank, (void*)p, gd, gs, bd, es, CU_TENSOR_MAP_INTERLEAVE_NONE, sw,
                              CU_TENSOR_MAP_L2_PROMOTION_L2_128B, CU_TENSOR_MAP_FLOAT_OOB_FILL_NONE) != CUDA_SUCCESS);
}

extern "C" void kernel_launch(void* const* d_in, const int* in_sizes, int n_in, void* d_out, int out_size) {
  const bf16 *q = (const bf16*)d_in[0], *k = (const bf16*)d_in[1], *v = (const bf16*)d_in[2], *shift = (const bf16*)d_in[3],
             *ssmk = (const bf16*)d_in[4], *ssmd = (const bf16*)d_in[5], *w1 = (const bf16*)d_in[7], *w3 = (const bf16*)d_in[8],
             *w2 = (const bf16*)d_in[9], *c = (const bf16*)d_in[10], *wmod = (const bf16*)d_in[11];
  EncFn fn = nullptr;
  cudaDriverEntryPointQueryResult qr;
  cudaGetDriverEntryPoint("cuTensorMapEncodeTiled", (void**)&fn, cudaEnableDefault, &qr);
  Scratch* pg;
  cudaGetSymbolAddress((void**)&pg, g_s);
  Maps maps;
  enc_err = 0;
  const CUtensorMapSwizzle S128 = CU_TENSOR_MAP_SWIZZLE_128B;
  { cuuint64_t gd[3] = {D_, S_ / 8, 8}, gs[2] = {D_ * 16, D_ * 2}; cuuint32_t b[3] = {64, 4, 8};
    enc(fn, &maps.km, k, 3, gd, gs, b, S128);
    enc(fn, &maps.v, v, 3, gd, gs, b, S128);
    enc(fn, &maps.q, q, 3, gd, gs, b, S128);
    b[2] = 3;
    enc(fn, &maps.kh, k, 3, gd, gs, b, S128); }
  { cuuint64_t gd[3] = {256, 2, 5}, gs[2] = {512, 1024}; cuuint32_t b[3] = {256, 1, 5};
    enc(fn, &maps.tap, shift, 3, gd, gs, b, CU_TENSOR_MAP_SWIZZLE_NONE); }
  { cuuint64_t gd[3] = {6 * D_, D_, 1}, gs[2] = {6 * D_ * 2, 6 * D_ * 2 * D_}; cuuint32_t b[3] = {64, 64, 1};
    enc(fn, &maps.wm, wmod, 3, gd, gs, b, S128); }
  { cuuint64_t gd[3] = {64, D_, F_ / 64}, gs[2] = {F_ * 2, 128}; cuuint32_t b[3] = {64, 32, 3};
    enc(fn, &maps.w1, w1, 3, gd, gs, b, S128);
    enc(fn, &maps.w3, w3, 3, gd, gs, b, S128);
    b[1] = 16;
    enc(fn, &maps.w1e, w1, 3, gd, gs, b, S128);
    enc(fn, &maps.w3e, w3, 3, gd, gs, b, S128);
    b[1] = 32; b[2] = 1;
    enc(fn, &maps.w1s, w1, 3, gd, gs, b, S128);
    enc(fn, &maps.w3s, w3, 3, gd, gs, b, S128); }
  { cuuint64_t gd[2] = {S_, D_}, gs[1] = {S_ * 2}; cuuint32_t b1[2] = {64, 64}, b2[2] = {64, 32};
    enc(fn, &maps.xs, pg->xs, 2, gd, gs, b1, S128);
    gd[1] = 2 * D_;
    enc(fn, &maps.x1b, pg->x1, 2, gd, gs, b2, S128);
    enc(fn, &maps.x1s, pg->x1, 2, gd, gs, b2, CU_TENSOR_MAP_SWIZZLE_NONE); }
  { cuuint64_t gd[5] = {D_, 2, 4, 4, 48}, gs[4] = {D_ * 2, D_ * 4, D_ * 16, D_ * 64}; cuuint32_t b[5] = {64, 2, 4, 4, 2};
    enc(fn, &maps.w2a, w2, 5, gd, gs, b, S128);
    gs[1] = D_ * 16; gs[2] = D_ * 4;
    enc(fn, &maps.w2b, w2, 5, gd, gs, b, S128); }
  { cuuint64_t gd[2] = {D_, S_}, gs[1] = {D_ * 2}; cuuint32_t b1[2] = {64, 16}, b2[2] = {32, 16};
    enc(fn, &maps.outa, d_out, 2, gd, gs, b1, S128);
    enc(fn, &maps.outb, d_out, 2, gd, gs, b2, CU_TENSOR_MAP_SWIZZLE_64B); }
  if (enc_err) return;
  cudaFuncSetAttribute(k_fused, cudaFuncAttributeMaxDynamicSharedMemorySize, SMEM_BYTES);
  cudaLaunchConfig_t cfg = {132, 512, SMEM_BYTES};
  cudaLaunchAttribute at = {cudaLaunchAttributeClusterDimension};
  at.val.clusterDim.x = 2; at.val.clusterDim.y = at.val.clusterDim.z = 1;
  cfg.attrs = &at; cfg.numAttrs = 1;
  int nc = 0;
  cudaOccupancyMaxActiveClusters(&nc, k_fused, &cfg);
  Ptrs P = {ssmk, c, ssmd, pg, 0x48DCBA9ull, {0x676760, 0x64620F01}, 0, 5000, 19, 48, 100, 0, 0, 1, 1, 0xD7010, 1.f};
  const char* sched = "k10v14f04q04q14q24q34q44k24v24f14k34v34f24k44v44f34f44n04n02n04n06n06n06";
  int t = 1150, pace = 400;
  for (int e = 0; e < NE; e++) {
    const char x = sched[3 * e];
    const int r = sched[3 * e + 1] - '0', kind = x == 'k' ? 0 : x == 'v' ? 1 : x == 'q' ? 2 : x == 'f' ? 3 : 4;
    t += (sched[3 * e + 2] - '0') * pace / 4;
    P.sched[e] = make_uint2(t | kind << 16 | r << 20, (kind < 2 ? tab(T_KV, r) + kind * KV_V : kind == 2 ? OFF_Q + 4096 * r : tab(T_F, r) + F_E) | (r + (kind < 2 ? B_KV : kind == 2 ? B_Q : B_FRAW)) << 18);
  }
  for (int u = 0; u < 5; u++) P.wt[u] = 9000 + 700 * u;
  const int dep[5] = {B_FL + 1, B_FL + 2, B_PFULL + 2, B_G3, B_PEMPTY + 2};
  for (int u = 0; u < 20; u++) P.wdep[u] = u % 5 * WSLOT | (~u & 1) << 12 | (u < 5 ? dep[u] : B_EMPTY + u - 5);
  for (int v = 0; v < 12; v++) P.w2t[v] = make_uint2(w2_desc(v), v ? B_EMPTY + (v > 5 ? 15 + v : v > 3 ? 14 + v : v > 1 ? 16 : 15) : B_UVD);
  for (int m = 0; m < 9; m++) { P.hid[0][m] = hid_at(m, 0) - OFF_A; P.hid[1][m] = hid_at(m, 1) - OFF_A - ARING; P.hid[2][m] = B_EMPTY + 19 + (m > 2 ? m : m / 2); }
  if (nc < 66) { P.boff = 128; k_fused<<<4, 512, SMEM_BYTES, cudaStreamPerThread>>>(P, maps); P.boff = 0; }
  k_fused<<<nc < 66 ? 128 : 132, 512, SMEM_BYTES, cudaStreamPerThread>>>(P, maps);
}
```

```cpp
#include <cuda_runtime.h>
#include <cuda.h>
#include <cuda_bf16.h>
#include <stdint.h>
#include <stdlib.h>

typedef __nv_bfloat16 bf16;
constexpr int S_ = 2048, D_ = 640, F_ = 1536;

struct Scratch {
  uint32_t st1[2][1024];
  uint32_t st2[32][4][128];
  uint2 modc[128][32];
  uint2 modv[3][D_];
  uint32_t uv[8][3072];
  unsigned hint[9][8][32];
  unsigned xsh[5][8][32], hhf[256 * 8];
  uint4 xr[D_ * 256];
  uint4 qt[D_ * 256];
  uint4 xs[D_ * 256];
  uint4 x1[2][D_ * 256];
  uint4 hh[32 * 8 * 1536];
};
__device__ __align__(1024) Scratch g_s;

__device__ __forceinline__ uint32_t smem_u32(const void* p) { return (uint32_t)__cvta_generic_to_shared(p); }
__device__ __forceinline__ void mbar_expect_tx(uint32_t b, uint32_t n) { asm volatile("mbarrier.arrive.expect_tx.shared::cta.b64 _, [%0], %1;" ::"r"(b), "r"(n) : "memory"); }
__device__ __forceinline__ void mbar_arrive(uint32_t b) { asm volatile("mbarrier.arrive.shared::cta.b64 _, [%0];" ::"r"(b) : "memory"); }
__device__ __forceinline__ void mbar_arrive2(uint32_t b) { asm volatile("mbarrier.arrive.shared::cta.b64 _, [%0], 2;" ::"r"(b) : "memory"); }
__device__ __forceinline__ uint32_t mapa(uint32_t a, uint32_t cta) { uint32_t r; asm volatile("mapa.shared::cluster.u32 %0, %1, %2;" : "=r"(r) : "r"(a), "r"(cta)); return r; }
__device__ __forceinline__ void mbar_arrive_remote(uint32_t rb) { asm volatile("mbarrier.arrive.shared::cluster.b64 _, [%0];" ::"r"(rb) : "memory"); }
constexpr int SPIN_LIMIT = 1 << 16;
template <int N> __device__ __forceinline__ void mbar_init(uint32_t b, uint32_t count) {
#pragma unroll
  for (int i = 0; i < N; i++) asm volatile("mbarrier.init.shared::cta.b64 [%0], %1;" ::"r"(b + 8 * i), "r"(count) : "memory");
}
__device__ __forceinline__ bool elect() { uint32_t p; asm volatile("{.reg .pred q; elect.sync _|q, 0xffffffff; selp.u32 %0, 1, 0, q;}" : "=r"(p)); return p; }
__device__ __forceinline__ void arrive1(uint32_t b) { __syncwarp(); if (elect()) mbar_arrive(b); }
__device__ __forceinline__ bool mbar_test(uint32_t b) {
  uint32_t ok;
  asm volatile("{.reg .pred p; mbarrier.test_wait.parity.shared::cta.b64 p, [%1], 0; selp.u32 %0,1,0,p;}" : "=r"(ok) : "r"(b) : "memory");
  return ok;
}
#define WAIT_LOOP(sem) "{.reg .pred p; mov.u32 %0, 0; W: mbarrier.try_wait.parity" sem ".shared::cta.b64 p, [%1], %2; @p bra.uni D; add.u32 %0, %0, 1; setp.lt.u32 p, %0, %3; @p bra.uni W; D:}"
__device__ __forceinline__ void mbar_wait(uint32_t b, uint32_t ph = 0) {
  int it;
  asm volatile(WAIT_LOOP("") : "=&r"(it) : "r"(b), "r"(ph), "n"(SPIN_LIMIT) : "memory");
}
__device__ __forceinline__ void mbar_wait_cluster(uint32_t b, uint32_t ph = 0) {
  int it;
  asm volatile(WAIT_LOOP(".acquire.cluster") : "=&r"(it) : "r"(b), "r"(ph), "n"(SPIN_LIMIT) : "memory");
}
__device__ __forceinline__ void wait_clock(uint32_t t) {
  asm volatile("{.reg .pred p; .reg .s32 d; W: mov.u32 d, %%clock; sub.s32 d, d, %0; setp.lt.s32 p, d, 0; @p bra.uni W;}" ::"r"(t) : "memory");
}
__device__ __forceinline__ void tma2d(uint32_t dst, const CUtensorMap* m, int c0, int c1, uint32_t bar) {
  asm volatile("cp.async.bulk.tensor.2d.shared::cluster.global.mbarrier::complete_tx::bytes [%0], [%1, {%3,%4}], [%2];" ::"r"(dst), "l"(m), "r"(bar), "r"(c0), "r"(c1) : "memory");
}
__device__ __forceinline__ void tma3d(uint32_t dst, const CUtensorMap* m, int c0, int c1, int c2, uint32_t bar) {
  asm volatile("cp.async.bulk.tensor.3d.shared::cluster.global.mbarrier::complete_tx::bytes [%0], [%1, {%3,%4,%5}], [%2];" ::"r"(dst), "l"(m), "r"(bar), "r"(c0), "r"(c1), "r"(c2) : "memory");
}
__device__ __forceinline__ void tma5d(uint32_t dst, const CUtensorMap* m, int c0, int c4, uint32_t bar) {
  asm volatile("cp.async.bulk.tensor.5d.shared::cluster.global.mbarrier::complete_tx::bytes [%0], [%1, {%4,%3,%3,%3,%5}], [%2];" ::"r"(dst), "l"(m), "r"(bar), "r"(0), "r"(c0), "r"(c4) : "memory");
}
__device__ __forceinline__ void tma2d_store(const CUtensorMap* m, int c0, int c1, uint32_t src) {
  asm volatile("cp.async.bulk.tensor.2d.global.shared::cta.bulk_group [%0, {%2,%3}], [%1];" ::"l"(m), "r"(src), "r"(c0), "r"(c1) : "memory");
}
__device__ __forceinline__ void bulk_load(uint32_t dst, const void* src, uint32_t bytes, uint32_t bar) {
  asm volatile("cp.async.bulk.shared::cluster.global.mbarrier::complete_tx::bytes [%0], [%1], %2, [%3];" ::"r"(dst), "l"(src), "r"(bytes), "r"(bar) : "memory");
}
__device__ __forceinline__ void prefetch_map(const CUtensorMap* m) { asm volatile("prefetch.tensormap [%0];" ::"l"(m) : "memory"); }
__device__ __forceinline__ void bulk_commit() { asm volatile("cp.async.bulk.commit_group;" ::: "memory"); }
__device__ __forceinline__ void bulk_wait_read() { asm volatile("cp.async.bulk.wait_group.read 0;" ::: "memory"); }
__device__ __forceinline__ void fence_async_smem() { asm volatile("fence.proxy.async.shared::cta;" ::: "memory"); }
__device__ __forceinline__ void fence_async_all() { asm volatile("fence.proxy.async.global;" ::: "memory"); }
__device__ __forceinline__ void named_bar(int id, int n) { asm volatile("bar.sync %0, %1;" ::"r"(id), "r"(n) : "memory"); }
__device__ __forceinline__ bool bar_all(int id, bool v) {
  uint32_t r;
  asm volatile("{.reg .pred p, q; setp.ne.u32 p, %2, 0; bar.red.and.pred q, %1, 128, p; selp.u32 %0, 1, 0, q;}" : "=r"(r) : "r"(id), "r"((uint32_t)v) : "memory");
  return __all_sync(~0u, r);
}
__device__ __forceinline__ void cluster_wait() { asm volatile("barrier.cluster.wait.aligned;" ::: "memory"); }
__device__ __forceinline__ void wg_fence() { asm volatile("wgmma.fence.sync.aligned;" ::: "memory"); }
__device__ __forceinline__ void wg_commit() { asm volatile("wgmma.commit_group.sync.aligned;" ::: "memory"); }
template <int N> __device__ __forceinline__ void wg_wait() { asm volatile("wgmma.wait_group.sync.aligned %0;" ::"n"(N) : "memory"); }
template <int N> __device__ __forceinline__ void fence_regs(float (&a)[N]) {
#pragma unroll
  for (int i = 0; i < N; i++) asm volatile("" : "+f"(a[i])::"memory");
}
template <int N> __device__ __forceinline__ void fence_n(float* a) {
#pragma unroll
  for (int i = 0; i < N; i++) asm volatile("" : "+f"(a[i])::"memory");
}
__device__ __forceinline__ uint64_t mkdesc(uint32_t addr, uint32_t lbo, uint32_t sbo, uint32_t swz) {
  uint32_t lo = (addr >> 4) | ((lbo >> 4) << 16), hi = (sbo >> 4) | (swz << 30);
  return ((uint64_t)hi << 32) | lo;
}
__device__ __forceinline__ void stmatrix_x4(uint32_t a, uint32_t r0, uint32_t r1, uint32_t r2, uint32_t r3) {
  asm volatile("stmatrix.sync.aligned.m8n8.x4.shared.b16 [%0], {%1,%2,%3,%4};" ::"r"(a), "r"(r0), "r"(r1), "r"(r2), "r"(r3) : "memory");
}
__device__ __forceinline__ void stmatrix_x4_t(uint32_t a, uint32_t r0, uint32_t r1, uint32_t r2, uint32_t r3) {
  asm volatile("stmatrix.sync.aligned.m8n8.x4.trans.shared.b16 [%0], {%1,%2,%3,%4};" ::"r"(a), "r"(r0), "r"(r1), "r"(r2), "r"(r3) : "memory");
}
__device__ __forceinline__ void ldmatrix_x4_t(uint32_t* r, uint32_t a) {
  asm volatile("ldmatrix.sync.aligned.m8n8.x4.trans.shared.b16 {%0,%1,%2,%3}, [%4];" : "=r"(r[0]), "=r"(r[1]), "=r"(r[2]), "=r"(r[3]) : "r"(a) : "memory");
}
__device__ __forceinline__ uint32_t lds32(uint32_t a) { uint32_t v; asm volatile("ld.shared.b32 %0, [%1];" : "=r"(v) : "r"(a) : "memory"); return v; }
__device__ __forceinline__ uint2 lds64(uint32_t a) { uint2 v; asm volatile("ld.shared.v2.b32 {%0,%1}, [%2];" : "=r"(v.x), "=r"(v.y) : "r"(a) : "memory"); return v; }
__device__ __forceinline__ uint4 lds128(uint32_t a) { uint4 v; asm volatile("ld.shared.v4.b32 {%0,%1,%2,%3}, [%4];" : "=r"(v.x), "=r"(v.y), "=r"(v.z), "=r"(v.w) : "r"(a) : "memory"); return v; }
__device__ __forceinline__ void sts32(uint32_t a, uint32_t v) { asm volatile("st.shared.b32 [%0], %1;" ::"r"(a), "r"(v) : "memory"); }
__device__ __forceinline__ void sts64(uint32_t a, uint32_t x, uint32_t y) { asm volatile("st.shared.v2.b32 [%0], {%1,%2};" ::"r"(a), "r"(x), "r"(y) : "memory"); }
__device__ __forceinline__ void sts128(uint32_t a, uint32_t x, uint32_t y, uint32_t z, uint32_t w) { asm volatile("st.shared.v4.b32 [%0], {%1,%2,%3,%4};" ::"r"(a), "r"(x), "r"(y), "r"(z), "r"(w) : "memory"); }
__device__ __forceinline__ uint4 ld_relaxed128(const void* p) { uint4 v; asm volatile("ld.relaxed.gpu.global.v4.u32 {%0,%1,%2,%3}, [%4];" : "=r"(v.x), "=r"(v.y), "=r"(v.z), "=r"(v.w) : "l"(p) : "memory"); return v; }
__device__ __forceinline__ uint2 ld_relaxed64(const void* p) { uint2 v; asm volatile("ld.relaxed.gpu.global.v2.u32 {%0,%1}, [%2];" : "=r"(v.x), "=r"(v.y) : "l"(p) : "memory"); return v; }
__device__ __forceinline__ uint32_t ld_relaxed32(const void* p) { uint32_t v; asm volatile("ld.relaxed.gpu.global.u32 %0, [%1];" : "=r"(v) : "l"(p) : "memory"); return v; }
__device__ __forceinline__ void st_relaxed128(void* p, uint32_t x, uint32_t y, uint32_t z, uint32_t w) { asm volatile("st.relaxed.gpu.global.v4.u32 [%0], {%1,%2,%3,%4};" ::"l"(p), "r"(x), "r"(y), "r"(z), "r"(w) : "memory"); }
__device__ __forceinline__ void st_relaxed32(void* p, uint32_t x) { asm volatile("st.relaxed.gpu.global.u32 [%0], %1;" ::"l"(p), "r"(x) : "memory"); }
__device__ __forceinline__ void red_hint(unsigned* p) { asm volatile("red.relaxed.gpu.global.add.u32 [%0], 1;" ::"l"(p) : "memory"); }
__device__ __forceinline__ void publish(uint32_t* p, uint32_t x) { asm volatile("{.reg .b32 t; atom.relaxed.gpu.global.exch.b32 t, [%0], %1;}" ::"l"(p), "r"(x) : "memory"); }
__device__ __forceinline__ uint32_t ldg32(const void* p) { uint32_t v; asm volatile("ld.global.nc.L1::no_allocate.b32 %0, [%1];" : "=r"(v) : "l"(p)); return v; }
__device__ __forceinline__ uint32_t pack_bf16(float lo, float hi) { uint32_t r; asm("cvt.rn.bf16x2.f32 %0, %1, %2;" : "=r"(r) : "f"(hi), "f"(lo)); return r; }
__device__ __forceinline__ float bf_lo(uint32_t v) { return __uint_as_float(v << 16); }
__device__ __forceinline__ float bf_hi(uint32_t v) { return __uint_as_float(v & 0xFFFF0000u); }
__device__ __forceinline__ uint32_t bmul2(uint32_t a, uint32_t b) { uint32_t r; asm("mul.rn.bf16x2 %0, %1, %2;" : "=r"(r) : "r"(a), "r"(b)); return r; }
__device__ __forceinline__ uint32_t badd2(uint32_t a, uint32_t b) { uint32_t r; asm("add.rn.bf16x2 %0, %1, %2;" : "=r"(r) : "r"(a), "r"(b)); return r; }
__device__ __forceinline__ uint32_t bfma2(uint32_t a, uint32_t b, uint32_t c) { uint32_t r; asm("fma.rn.bf16x2 %0, %1, %2, %3;" : "=r"(r) : "r"(a), "r"(b), "r"(c)); return r; }
__device__ __forceinline__ uint32_t set_tag(uint32_t x, uint32_t mask, uint32_t e) { uint32_t r; asm("lop3.b32 %0, %1, %2, %3, 0xB8;" : "=r"(r) : "r"(x), "r"(mask), "r"(e)); return r; }
__device__ __forceinline__ uint32_t opaque(uint32_t x) { asm volatile("" : "+r"(x)); return x; }
__device__ __forceinline__ float rbf(float x) { return __bfloat162float(__float2bfloat16(x)); }
__device__ __forceinline__ float silu_f(float x) {
  float e, r;
  asm("ex2.approx.ftz.f32 %0, %1;" : "=f"(e) : "f"(x * -1.4426950408889634f));
  asm("rcp.approx.ftz.f32 %0, %1;" : "=f"(r) : "f"(1.f + e));
  return x * r;
}
__device__ __forceinline__ float silu2(float x) {
  float t;
  asm("tanh.approx.f32 %0, %1;" : "=f"(t) : "f"(x));
  return fmaf(x, t, x);
}
__device__ __forceinline__ void pin(int off, uint32_t x) { asm volatile("{.reg .pred p; setp.lt.s32 p, %0, 0; @p st.shared.b32 [%0], %1;}" ::"r"(off), "r"(x) : "memory"); }
__device__ __forceinline__ void pin4(int off, const uint32_t* x) { asm volatile("{.reg .pred p; setp.lt.s32 p, %0, 0; @p st.shared.v4.b32 [%0], {%1,%2,%3,%4};}" ::"r"(off), "r"(x[0]), "r"(x[1]), "r"(x[2]), "r"(x[3]) : "memory"); }
__device__ __forceinline__ void split(int x, int n) { asm volatile("{.reg .pred p; setp.eq.s32 p, %0, %1; @p trap;}" ::"r"(x), "r"(~n) : "memory"); }
__device__ __forceinline__ void ln_final(float s, float q, float& m, float& sd) {
  m = s * (1.f / D_);
  asm("sqrt.approx.f32 %0, %1;" : "=f"(sd) : "f"(rbf(rbf(fmaxf(fmaf(-m, m, q * (1.f / D_)), 0.f)) + 1e-5f)));
  sd = rbf(sd);
}
__device__ __forceinline__ float rcpf(float x) { float r; asm("rcp.approx.f32 %0, %1;" : "=f"(r) : "f"(x)); return r; }

__device__ __forceinline__ void wg_rs16_0(float* d, const uint32_t* a, uint64_t db, int sc) {
  asm volatile("{.reg .pred p; setp.ne.b32 p, %13, 0; wgmma.mma_async.sync.aligned.m64n16k16.f32.bf16.bf16 {%0,%1,%2,%3,%4,%5,%6,%7}, {%8,%9,%10,%11}, %12, p, 1, 1, 0;}"
    : "+f"(d[0]),"+f"(d[1]),"+f"(d[2]),"+f"(d[3]),"+f"(d[4]),"+f"(d[5]),"+f"(d[6]),"+f"(d[7]) : "r"(a[0]),"r"(a[1]),"r"(a[2]),"r"(a[3]),"l"(db),"r"(sc));
}
__device__ __forceinline__ void wg_rs32_0(float* d, const uint32_t* a, uint64_t db, int sc) {
  asm volatile("{.reg .pred p; setp.ne.b32 p, %21, 0; wgmma.mma_async.sync.aligned.m64n32k16.f32.bf16.bf16 {%0,%1,%2,%3,%4,%5,%6,%7,%8,%9,%10,%11,%12,%13,%14,%15}, {%16,%17,%18,%19}, %20, p, 1, 1, 0;}"
    : "+f"(d[0]),"+f"(d[1]),"+f"(d[2]),"+f"(d[3]),"+f"(d[4]),"+f"(d[5]),"+f"(d[6]),"+f"(d[7]),"+f"(d[8]),"+f"(d[9]),"+f"(d[10]),"+f"(d[11]),"+f"(d[12]),"+f"(d[13]),"+f"(d[14]),"+f"(d[15]) : "r"(a[0]),"r"(a[1]),"r"(a[2]),"r"(a[3]),"l"(db),"r"(sc));
}
__device__ __forceinline__ void wg_rs48_0(float* d, const uint32_t* a, uint64_t db, int sc) {
  asm volatile("{.reg .pred p; setp.ne.b32 p, %29, 0; wgmma.mma_async.sync.aligned.m64n48k16.f32.bf16.bf16 {%0,%1,%2,%3,%4,%5,%6,%7,%8,%9,%10,%11,%12,%13,%14,%15,%16,%17,%18,%19,%20,%21,%22,%23}, {%24,%25,%26,%27}, %28, p, 1, 1, 0;}"
    : "+f"(d[0]),"+f"(d[1]),"+f"(d[2]),"+f"(d[3]),"+f"(d[4]),"+f"(d[5]),"+f"(d[6]),"+f"(d[7]),"+f"(d[8]),"+f"(d[9]),"+f"(d[10]),"+f"(d[11]),"+f"(d[12]),"+f"(d[13]),"+f"(d[14]),"+f"(d[15]),"+f"(d[16]),"+f"(d[17]),"+f"(d[18]),"+f"(d[19]),"+f"(d[20]),"+f"(d[21]),"+f"(d[22]),"+f"(d[23]) : "r"(a[0]),"r"(a[1]),"r"(a[2]),"r"(a[3]),"l"(db),"r"(sc));
}
__device__ __forceinline__ void wg_rs64_0(float* d, const uint32_t* a, uint64_t db, int sc) {
  asm volatile("{.reg .pred p; setp.ne.b32 p, %37, 0; wgmma.mma_async.sync.aligned.m64n64k16.f32.bf16.bf16 {%0,%1,%2,%3,%4,%5,%6,%7,%8,%9,%10,%11,%12,%13,%14,%15,%16,%17,%18,%19,%20,%21,%22,%23,%24,%25,%26,%27,%28,%29,%30,%31}, {%32,%33,%34,%35}, %36, p, 1, 1, 0;}"
    : "+f"(d[0]),"+f"(d[1]),"+f"(d[2]),"+f"(d[3]),"+f"(d[4]),"+f"(d[5]),"+f"(d[6]),"+f"(d[7]),"+f"(d[8]),"+f"(d[9]),"+f"(d[10]),"+f"(d[11]),"+f"(d[12]),"+f"(d[13]),"+f"(d[14]),"+f"(d[15]),"+f"(d[16]),"+f"(d[17]),"+f"(d[18]),"+f"(d[19]),"+f"(d[20]),"+f"(d[21]),"+f"(d[22]),"+f"(d[23]),"+f"(d[24]),"+f"(d[25]),"+f"(d[26]),"+f"(d[27]),"+f"(d[28]),"+f"(d[29]),"+f"(d[30]),"+f"(d[31]) : "r"(a[0]),"r"(a[1]),"r"(a[2]),"r"(a[3]),"l"(db),"r"(sc));
}
__device__ __forceinline__ void wg_rs80_0(float* d, const uint32_t* a, uint64_t db, int sc) {
  asm volatile("{.reg .pred p; setp.ne.b32 p, %45, 0; wgmma.mma_async.sync.aligned.m64n80k16.f32.bf16.bf16 {%0,%1,%2,%3,%4,%5,%6,%7,%8,%9,%10,%11,%12,%13,%14,%15,%16,%17,%18,%19,%20,%21,%22,%23,%24,%25,%26,%27,%28,%29,%30,%31,%32,%33,%34,%35,%36,%37,%38,%39}, {%40,%41,%42,%43}, %44, p, 1, 1, 0;}"
    : "+f"(d[0]),"+f"(d[1]),"+f"(d[2]),"+f"(d[3]),"+f"(d[4]),"+f"(d[5]),"+f"(d[6]),"+f"(d[7]),"+f"(d[8]),"+f"(d[9]),"+f"(d[10]),"+f"(d[11]),"+f"(d[12]),"+f"(d[13]),"+f"(d[14]),"+f"(d[15]),"+f"(d[16]),"+f"(d[17]),"+f"(d[18]),"+f"(d[19]),"+f"(d[20]),"+f"(d[21]),"+f"(d[22]),"+f"(d[23]),"+f"(d[24]),"+f"(d[25]),"+f"(d[26]),"+f"(d[27]),"+f"(d[28]),"+f"(d[29]),"+f"(d[30]),"+f"(d[31]),"+f"(d[32]),"+f"(d[33]),"+f"(d[34]),"+f"(d[35]),"+f"(d[36]),"+f"(d[37]),"+f"(d[38]),"+f"(d[39]) : "r"(a[0]),"r"(a[1]),"r"(a[2]),"r"(a[3]),"l"(db),"r"(sc));
}
__device__ __forceinline__ void wg_rs96_0(float* d, const uint32_t* a, uint64_t db, int sc) {
  asm volatile("{.reg .pred p; setp.ne.b32 p, %53, 0; wgmma.mma_async.sync.aligned.m64n96k16.f32.bf16.bf16 {%0,%1,%2,%3,%4,%5,%6,%7,%8,%9,%10,%11,%12,%13,%14,%15,%16,%17,%18,%19,%20,%21,%22,%23,%24,%25,%26,%27,%28,%29,%30,%31,%32,%33,%34,%35,%36,%37,%38,%39,%40,%41,%42,%43,%44,%45,%46,%47}, {%48,%49,%50,%51}, %52, p, 1, 1, 0;}"
    : "+f"(d[0]),"+f"(d[1]),"+f"(d[2]),"+f"(d[3]),"+f"(d[4]),"+f"(d[5]),"+f"(d[6]),"+f"(d[7]),"+f"(d[8]),"+f"(d[9]),"+f"(d[10]),"+f"(d[11]),"+f"(d[12]),"+f"(d[13]),"+f"(d[14]),"+f"(d[15]),"+f"(d[16]),"+f"(d[17]),"+f"(d[18]),"+f"(d[19]),"+f"(d[20]),"+f"(d[21]),"+f"(d[22]),"+f"(d[23]),"+f"(d[24]),"+f"(d[25]),"+f"(d[26]),"+f"(d[27]),"+f"(d[28]),"+f"(d[29]),"+f"(d[30]),"+f"(d[31]),"+f"(d[32]),"+f"(d[33]),"+f"(d[34]),"+f"(d[35]),"+f"(d[36]),"+f"(d[37]),"+f"(d[38]),"+f"(d[39]),"+f"(d[40]),"+f"(d[41]),"+f"(d[42]),"+f"(d[43]),"+f"(d[44]),"+f"(d[45]),"+f"(d[46]),"+f"(d[47]) : "r"(a[0]),"r"(a[1]),"r"(a[2]),"r"(a[3]),"l"(db),"r"(sc));
}
__device__ __forceinline__ void wg_rs112_0(float* d, const uint32_t* a, uint64_t db, int sc) {
  asm volatile("{.reg .pred p; setp.ne.b32 p, %61, 0; wgmma.mma_async.sync.aligned.m64n112k16.f32.bf16.bf16 {%0,%1,%2,%3,%4,%5,%6,%7,%8,%9,%10,%11,%12,%13,%14,%15,%16,%17,%18,%19,%20,%21,%22,%23,%24,%25,%26,%27,%28,%29,%30,%31,%32,%33,%34,%35,%36,%37,%38,%39,%40,%41,%42,%43,%44,%45,%46,%47,%48,%49,%50,%51,%52,%53,%54,%55}, {%56,%57,%58,%59}, %60, p, 1, 1, 0;}"
    : "+f"(d[0]),"+f"(d[1]),"+f"(d[2]),"+f"(d[3]),"+f"(d[4]),"+f"(d[5]),"+f"(d[6]),"+f"(d[7]),"+f"(d[8]),"+f"(d[9]),"+f"(d[10]),"+f"(d[11]),"+f"(d[12]),"+f"(d[13]),"+f"(d[14]),"+f"(d[15]),"+f"(d[16]),"+f"(d[17]),"+f"(d[18]),"+f"(d[19]),"+f"(d[20]),"+f"(d[21]),"+f"(d[22]),"+f"(d[23]),"+f"(d[24]),"+f"(d[25]),"+f"(d[26]),"+f"(d[27]),"+f"(d[28]),"+f"(d[29]),"+f"(d[30]),"+f"(d[31]),"+f"(d[32]),"+f"(d[33]),"+f"(d[34]),"+f"(d[35]),"+f"(d[36]),"+f"(d[37]),"+f"(d[38]),"+f"(d[39]),"+f"(d[40]),"+f"(d[41]),"+f"(d[42]),"+f"(d[43]),"+f"(d[44]),"+f"(d[45]),"+f"(d[46]),"+f"(d[47]),"+f"(d[48]),"+f"(d[49]),"+f"(d[50]),"+f"(d[51]),"+f"(d[52]),"+f"(d[53]),"+f"(d[54]),"+f"(d[55]) : "r"(a[0]),"r"(a[1]),"r"(a[2]),"r"(a[3]),"l"(db),"r"(sc));
}
__device__ __forceinline__ void wg_rs128_0(float* d, const uint32_t* a, uint64_t db, int sc) {
  asm volatile("{.reg .pred p; setp.ne.b32 p, %69, 0; wgmma.mma_async.sync.aligned.m64n128k16.f32.bf16.bf16 {%0,%1,%2,%3,%4,%5,%6,%7,%8,%9,%10,%11,%12,%13,%14,%15,%16,%17,%18,%19,%20,%21,%22,%23,%24,%25,%26,%27,%28,%29,%30,%31,%32,%33,%34,%35,%36,%37,%38,%39,%40,%41,%42,%43,%44,%45,%46,%47,%48,%49,%50,%51,%52,%53,%54,%55,%56,%57,%58,%59,%60,%61,%62,%63}, {%64,%65,%66,%67}, %68, p, 1, 1, 0;}"
    : "+f"(d[0]),"+f"(d[1]),"+f"(d[2]),"+f"(d[3]),"+f"(d[4]),"+f"(d[5]),"+f"(d[6]),"+f"(d[7]),"+f"(d[8]),"+f"(d[9]),"+f"(d[10]),"+f"(d[11]),"+f"(d[12]),"+f"(d[13]),"+f"(d[14]),"+f"(d[15]),"+f"(d[16]),"+f"(d[17]),"+f"(d[18]),"+f"(d[19]),"+f"(d[20]),"+f"(d[21]),"+f"(d[22]),"+f"(d[23]),"+f"(d[24]),"+f"(d[25]),"+f"(d[26]),"+f"(d[27]),"+f"(d[28]),"+f"(d[29]),"+f"(d[30]),"+f"(d[31]),"+f"(d[32]),"+f"(d[33]),"+f"(d[34]),"+f"(d[35]),"+f"(d[36]),"+f"(d[37]),"+f"(d[38]),"+f"(d[39]),"+f"(d[40]),"+f"(d[41]),"+f"(d[42]),"+f"(d[43]),"+f"(d[44]),"+f"(d[45]),"+f"(d[46]),"+f"(d[47]),"+f"(d[48]),"+f"(d[49]),"+f"(d[50]),"+f"(d[51]),"+f"(d[52]),"+f"(d[53]),"+f"(d[54]),"+f"(d[55]),"+f"(d[56]),"+f"(d[57]),"+f"(d[58]),"+f"(d[59]),"+f"(d[60]),"+f"(d[61]),"+f"(d[62]),"+f"(d[63]) : "r"(a[0]),"r"(a[1]),"r"(a[2]),"r"(a[3]),"l"(db),"r"(sc));
}
__device__ __forceinline__ void wg_rs144_0(float* d, const uint32_t* a, uint64_t db, int sc) {
  asm volatile("{.reg .pred p; setp.ne.b32 p, %77, 0; wgmma.mma_async.sync.aligned.m64n144k16.f32.bf16.bf16 {%0,%1,%2,%3,%4,%5,%6,%7,%8,%9,%10,%11,%12,%13,%14,%15,%16,%17,%18,%19,%20,%21,%22,%23,%24,%25,%26,%27,%28,%29,%30,%31,%32,%33,%34,%35,%36,%37,%38,%39,%40,%41,%42,%43,%44,%45,%46,%47,%48,%49,%50,%51,%52,%53,%54,%55,%56,%57,%58,%59,%60,%61,%62,%63,%64,%65,%66,%67,%68,%69,%70,%71}, {%72,%73,%74,%75}, %76, p, 1, 1, 0;}"
    : "+f"(d[0]),"+f"(d[1]),"+f"(d[2]),"+f"(d[3]),"+f"(d[4]),"+f"(d[5]),"+f"(d[6]),"+f"(d[7]),"+f"(d[8]),"+f"(d[9]),"+f"(d[10]),"+f"(d[11]),"+f"(d[12]),"+f"(d[13]),"+f"(d[14]),"+f"(d[15]),"+f"(d[16]),"+f"(d[17]),"+f"(d[18]),"+f"(d[19]),"+f"(d[20]),"+f"(d[21]),"+f"(d[22]),"+f"(d[23]),"+f"(d[24]),"+f"(d[25]),"+f"(d[26]),"+f"(d[27]),"+f"(d[28]),"+f"(d[29]),"+f"(d[30]),"+f"(d[31]),"+f"(d[32]),"+f"(d[33]),"+f"(d[34]),"+f"(d[35]),"+f"(d[36]),"+f"(d[37]),"+f"(d[38]),"+f"(d[39]),"+f"(d[40]),"+f"(d[41]),"+f"(d[42]),"+f"(d[43]),"+f"(d[44]),"+f"(d[45]),"+f"(d[46]),"+f"(d[47]),"+f"(d[48]),"+f"(d[49]),"+f"(d[50]),"+f"(d[51]),"+f"(d[52]),"+f"(d[53]),"+f"(d[54]),"+f"(d[55]),"+f"(d[56]),"+f"(d[57]),"+f"(d[58]),"+f"(d[59]),"+f"(d[60]),"+f"(d[61]),"+f"(d[62]),"+f"(d[63]),"+f"(d[64]),"+f"(d[65]),"+f"(d[66]),"+f"(d[67]),"+f"(d[68]),"+f"(d[69]),"+f"(d[70]),"+f"(d[71]) : "r"(a[0]),"r"(a[1]),"r"(a[2]),"r"(a[3]),"l"(db),"r"(sc));
}
__device__ __forceinline__ void wg_rs160_0(float* d, const uint32_t* a, uint64_t db, int sc) {
  asm volatile("{.reg .pred p; setp.ne.b32 p, %85, 0; wgmma.mma_async.sync.aligned.m64n160k16.f32.bf16.bf16 {%0,%1,%2,%3,%4,%5,%6,%7,%8,%9,%10,%11,%12,%13,%14,%15,%16,%17,%18,%19,%20,%21,%22,%23,%24,%25,%26,%27,%28,%29,%30,%31,%32,%33,%34,%35,%36,%37,%38,%39,%40,%41,%42,%43,%44,%45,%46,%47,%48,%49,%50,%51,%52,%53,%54,%55,%56,%57,%58,%59,%60,%61,%62,%63,%64,%65,%66,%67,%68,%69,%70,%71,%72,%73,%74,%75,%76,%77,%78,%79}, {%80,%81,%82,%83}, %84, p, 1, 1, 0;}"
    : "+f"(d[0]),"+f"(d[1]),"+f"(d[2]),"+f"(d[3]),"+f"(d[4]),"+f"(d[5]),"+f"(d[6]),"+f"(d[7]),"+f"(d[8]),"+f"(d[9]),"+f"(d[10]),"+f"(d[11]),"+f"(d[12]),"+f"(d[13]),"+f"(d[14]),"+f"(d[15]),"+f"(d[16]),"+f"(d[17]),"+f"(d[18]),"+f"(d[19]),"+f"(d[20]),"+f"(d[21]),"+f"(d[22]),"+f"(d[23]),"+f"(d[24]),"+f"(d[25]),"+f"(d[26]),"+f"(d[27]),"+f"(d[28]),"+f"(d[29]),"+f"(d[30]),"+f"(d[31]),"+f"(d[32]),"+f"(d[33]),"+f"(d[34]),"+f"(d[35]),"+f"(d[36]),"+f"(d[37]),"+f"(d[38]),"+f"(d[39]),"+f"(d[40]),"+f"(d[41]),"+f"(d[42]),"+f"(d[43]),"+f"(d[44]),"+f"(d[45]),"+f"(d[46]),"+f"(d[47]),"+f"(d[48]),"+f"(d[49]),"+f"(d[50]),"+f"(d[51]),"+f"(d[52]),"+f"(d[53]),"+f"(d[54]),"+f"(d[55]),"+f"(d[56]),"+f"(d[57]),"+f"(d[58]),"+f"(d[59]),"+f"(d[60]),"+f"(d[61]),"+f"(d[62]),"+f"(d[63]),"+f"(d[64]),"+f"(d[65]),"+f"(d[66]),"+f"(d[67]),"+f"(d[68]),"+f"(d[69]),"+f"(d[70]),"+f"(d[71]),"+f"(d[72]),"+f"(d[73]),"+f"(d[74]),"+f"(d[75]),"+f"(d[76]),"+f"(d[77]),"+f"(d[78]),"+f"(d[79]) : "r"(a[0]),"r"(a[1]),"r"(a[2]),"r"(a[3]),"l"(db),"r"(sc));
}
__device__ __forceinline__ void wg_rs176_0(float* d, const uint32_t* a, uint64_t db, int sc) {
  asm volatile("{.reg .pred p; setp.ne.b32 p, %93, 0; wgmma.mma_async.sync.aligned.m64n176k16.f32.bf16.bf16 {%0,%1,%2,%3,%4,%5,%6,%7,%8,%9,%10,%11,%12,%13,%14,%15,%16,%17,%18,%19,%20,%21,%22,%23,%24,%25,%26,%27,%28,%29,%30,%31,%32,%33,%34,%35,%36,%37,%38,%39,%40,%41,%42,%43,%44,%45,%46,%47,%48,%49,%50,%51,%52,%53,%54,%55,%56,%57,%58,%59,%60,%61,%62,%63,%64,%65,%66,%67,%68,%69,%70,%71,%72,%73,%74,%75,%76,%77,%78,%79,%80,%81,%82,%83,%84,%85,%86,%87}, {%88,%89,%90,%91}, %92, p, 1, 1, 0;}"
    : "+f"(d[0]),"+f"(d[1]),"+f"(d[2]),"+f"(d[3]),"+f"(d[4]),"+f"(d[5]),"+f"(d[6]),"+f"(d[7]),"+f"(d[8]),"+f"(d[9]),"+f"(d[10]),"+f"(d[11]),"+f"(d[12]),"+f"(d[13]),"+f"(d[14]),"+f"(d[15]),"+f"(d[16]),"+f"(d[17]),"+f"(d[18]),"+f"(d[19]),"+f"(d[20]),"+f"(d[21]),"+f"(d[22]),"+f"(d[23]),"+f"(d[24]),"+f"(d[25]),"+f"(d[26]),"+f"(d[27]),"+f"(d[28]),"+f"(d[29]),"+f"(d[30]),"+f"(d[31]),"+f"(d[32]),"+f"(d[33]),"+f"(d[34]),"+f"(d[35]),"+f"(d[36]),"+f"(d[37]),"+f"(d[38]),"+f"(d[39]),"+f"(d[40]),"+f"(d[41]),"+f"(d[42]),"+f"(d[43]),"+f"(d[44]),"+f"(d[45]),"+f"(d[46]),"+f"(d[47]),"+f"(d[48]),"+f"(d[49]),"+f"(d[50]),"+f"(d[51]),"+f"(d[52]),"+f"(d[53]),"+f"(d[54]),"+f"(d[55]),"+f"(d[56]),"+f"(d[57]),"+f"(d[58]),"+f"(d[59]),"+f"(d[60]),"+f"(d[61]),"+f"(d[62]),"+f"(d[63]),"+f"(d[64]),"+f"(d[65]),"+f"(d[66]),"+f"(d[67]),"+f"(d[68]),"+f"(d[69]),"+f"(d[70]),"+f"(d[71]),"+f"(d[72]),"+f"(d[73]),"+f"(d[74]),"+f"(d[75]),"+f"(d[76]),"+f"(d[77]),"+f"(d[78]),"+f"(d[79]),"+f"(d[80]),"+f"(d[81]),"+f"(d[82]),"+f"(d[83]),"+f"(d[84]),"+f"(d[85]),"+f"(d[86]),"+f"(d[87]) : "r"(a[0]),"r"(a[1]),"r"(a[2]),"r"(a[3]),"l"(db),"r"(sc));
}
__device__ __forceinline__ void wg_rs192_0(float* d, const uint32_t* a, uint64_t db, int sc) {
  asm volatile("{.reg .pred p; setp.ne.b32 p, %101, 0; wgmma.mma_async.sync.aligned.m64n192k16.f32.bf16.bf16 {%0,%1,%2,%3,%4,%5,%6,%7,%8,%9,%10,%11,%12,%13,%14,%15,%16,%17,%18,%19,%20,%21,%22,%23,%24,%25,%26,%27,%28,%29,%30,%31,%32,%33,%34,%35,%36,%37,%38,%39,%40,%41,%42,%43,%44,%45,%46,%47,%48,%49,%50,%51,%52,%53,%54,%55,%56,%57,%58,%59,%60,%61,%62,%63,%64,%65,%66,%67,%68,%69,%70,%71,%72,%73,%74,%75,%76,%77,%78,%79,%80,%81,%82,%83,%84,%85,%86,%87,%88,%89,%90,%91,%92,%93,%94,%95}, {%96,%97,%98,%99}, %100, p, 1, 1, 0;}"
    : "+f"(d[0]),"+f"(d[1]),"+f"(d[2]),"+f"(d[3]),"+f"(d[4]),"+f"(d[5]),"+f"(d[6]),"+f"(d[7]),"+f"(d[8]),"+f"(d[9]),"+f"(d[10]),"+f"(d[11]),"+f"(d[12]),"+f"(d[13]),"+f"(d[14]),"+f"(d[15]),"+f"(d[16]),"+f"(d[17]),"+f"(d[18]),"+f"(d[19]),"+f"(d[20]),"+f"(d[21]),"+f"(d[22]),"+f"(d[23]),"+f"(d[24]),"+f"(d[25]),"+f"(d[26]),"+f"(d[27]),"+f"(d[28]),"+f"(d[29]),"+f"(d[30]),"+f"(d[31]),"+f"(d[32]),"+f"(d[33]),"+f"(d[34]),"+f"(d[35]),"+f"(d[36]),"+f"(d[37]),"+f"(d[38]),"+f"(d[39]),"+f"(d[40]),"+f"(d[41]),"+f"(d[42]),"+f"(d[43]),"+f"(d[44]),"+f"(d[45]),"+f"(d[46]),"+f"(d[47]),"+f"(d[48]),"+f"(d[49]),"+f"(d[50]),"+f"(d[51]),"+f"(d[52]),"+f"(d[53]),"+f"(d[54]),"+f"(d[55]),"+f"(d[56]),"+f"(d[57]),"+f"(d[58]),"+f"(d[59]),"+f"(d[60]),"+f"(d[61]),"+f"(d[62]),"+f"(d[63]),"+f"(d[64]),"+f"(d[65]),"+f"(d[66]),"+f"(d[67]),"+f"(d[68]),"+f"(d[69]),"+f"(d[70]),"+f"(d[71]),"+f"(d[72]),"+f"(d[73]),"+f"(d[74]),"+f"(d[75]),"+f"(d[76]),"+f"(d[77]),"+f"(d[78]),"+f"(d[79]),"+f"(d[80]),"+f"(d[81]),"+f"(d[82]),"+f"(d[83]),"+f"(d[84]),"+f"(d[85]),"+f"(d[86]),"+f"(d[87]),"+f"(d[88]),"+f"(d[89]),"+f"(d[90]),"+f"(d[91]),"+f"(d[92]),"+f"(d[93]),"+f"(d[94]),"+f"(d[95]) : "r"(a[0]),"r"(a[1]),"r"(a[2]),"r"(a[3]),"l"(db),"r"(sc));
}
__device__ __forceinline__ void wg_ss192_11(float* d, uint64_t da, uint64_t db, int sc) {
  asm volatile("{.reg .pred p; setp.ne.b32 p, %98, 0; wgmma.mma_async.sync.aligned.m64n192k16.f32.bf16.bf16 {%0,%1,%2,%3,%4,%5,%6,%7,%8,%9,%10,%11,%12,%13,%14,%15,%16,%17,%18,%19,%20,%21,%22,%23,%24,%25,%26,%27,%28,%29,%30,%31,%32,%33,%34,%35,%36,%37,%38,%39,%40,%41,%42,%43,%44,%45,%46,%47,%48,%49,%50,%51,%52,%53,%54,%55,%56,%57,%58,%59,%60,%61,%62,%63,%64,%65,%66,%67,%68,%69,%70,%71,%72,%73,%74,%75,%76,%77,%78,%79,%80,%81,%82,%83,%84,%85,%86,%87,%88,%89,%90,%91,%92,%93,%94,%95}, %96, %97, p, 1, 1, 1, 1;}"
    : "+f"(d[0]),"+f"(d[1]),"+f"(d[2]),"+f"(d[3]),"+f"(d[4]),"+f"(d[5]),"+f"(d[6]),"+f"(d[7]),"+f"(d[8]),"+f"(d[9]),"+f"(d[10]),"+f"(d[11]),"+f"(d[12]),"+f"(d[13]),"+f"(d[14]),"+f"(d[15]),"+f"(d[16]),"+f"(d[17]),"+f"(d[18]),"+f"(d[19]),"+f"(d[20]),"+f"(d[21]),"+f"(d[22]),"+f"(d[23]),"+f"(d[24]),"+f"(d[25]),"+f"(d[26]),"+f"(d[27]),"+f"(d[28]),"+f"(d[29]),"+f"(d[30]),"+f"(d[31]),"+f"(d[32]),"+f"(d[33]),"+f"(d[34]),"+f"(d[35]),"+f"(d[36]),"+f"(d[37]),"+f"(d[38]),"+f"(d[39]),"+f"(d[40]),"+f"(d[41]),"+f"(d[42]),"+f"(d[43]),"+f"(d[44]),"+f"(d[45]),"+f"(d[46]),"+f"(d[47]),"+f"(d[48]),"+f"(d[49]),"+f"(d[50]),"+f"(d[51]),"+f"(d[52]),"+f"(d[53]),"+f"(d[54]),"+f"(d[55]),"+f"(d[56]),"+f"(d[57]),"+f"(d[58]),"+f"(d[59]),"+f"(d[60]),"+f"(d[61]),"+f"(d[62]),"+f"(d[63]),"+f"(d[64]),"+f"(d[65]),"+f"(d[66]),"+f"(d[67]),"+f"(d[68]),"+f"(d[69]),"+f"(d[70]),"+f"(d[71]),"+f"(d[72]),"+f"(d[73]),"+f"(d[74]),"+f"(d[75]),"+f"(d[76]),"+f"(d[77]),"+f"(d[78]),"+f"(d[79]),"+f"(d[80]),"+f"(d[81]),"+f"(d[82]),"+f"(d[83]),"+f"(d[84]),"+f"(d[85]),"+f"(d[86]),"+f"(d[87]),"+f"(d[88]),"+f"(d[89]),"+f"(d[90]),"+f"(d[91]),"+f"(d[92]),"+f"(d[93]),"+f"(d[94]),"+f"(d[95]) : "l"(da),"l"(db),"r"(sc));
}
__device__ __forceinline__ void wg_ss192_01(float* d, uint64_t da, uint64_t db, int sc) {
  asm volatile("{.reg .pred p; setp.ne.b32 p, %98, 0; wgmma.mma_async.sync.aligned.m64n192k16.f32.bf16.bf16 {%0,%1,%2,%3,%4,%5,%6,%7,%8,%9,%10,%11,%12,%13,%14,%15,%16,%17,%18,%19,%20,%21,%22,%23,%24,%25,%26,%27,%28,%29,%30,%31,%32,%33,%34,%35,%36,%37,%38,%39,%40,%41,%42,%43,%44,%45,%46,%47,%48,%49,%50,%51,%52,%53,%54,%55,%56,%57,%58,%59,%60,%61,%62,%63,%64,%65,%66,%67,%68,%69,%70,%71,%72,%73,%74,%75,%76,%77,%78,%79,%80,%81,%82,%83,%84,%85,%86,%87,%88,%89,%90,%91,%92,%93,%94,%95}, %96, %97, p, 1, 1, 0, 1;}"
    : "+f"(d[0]),"+f"(d[1]),"+f"(d[2]),"+f"(d[3]),"+f"(d[4]),"+f"(d[5]),"+f"(d[6]),"+f"(d[7]),"+f"(d[8]),"+f"(d[9]),"+f"(d[10]),"+f"(d[11]),"+f"(d[12]),"+f"(d[13]),"+f"(d[14]),"+f"(d[15]),"+f"(d[16]),"+f"(d[17]),"+f"(d[18]),"+f"(d[19]),"+f"(d[20]),"+f"(d[21]),"+f"(d[22]),"+f"(d[23]),"+f"(d[24]),"+f"(d[25]),"+f"(d[26]),"+f"(d[27]),"+f"(d[28]),"+f"(d[29]),"+f"(d[30]),"+f"(d[31]),"+f"(d[32]),"+f"(d[33]),"+f"(d[34]),"+f"(d[35]),"+f"(d[36]),"+f"(d[37]),"+f"(d[38]),"+f"(d[39]),"+f"(d[40]),"+f"(d[41]),"+f"(d[42]),"+f"(d[43]),"+f"(d[44]),"+f"(d[45]),"+f"(d[46]),"+f"(d[47]),"+f"(d[48]),"+f"(d[49]),"+f"(d[50]),"+f"(d[51]),"+f"(d[52]),"+f"(d[53]),"+f"(d[54]),"+f"(d[55]),"+f"(d[56]),"+f"(d[57]),"+f"(d[58]),"+f"(d[59]),"+f"(d[60]),"+f"(d[61]),"+f"(d[62]),"+f"(d[63]),"+f"(d[64]),"+f"(d[65]),"+f"(d[66]),"+f"(d[67]),"+f"(d[68]),"+f"(d[69]),"+f"(d[70]),"+f"(d[71]),"+f"(d[72]),"+f"(d[73]),"+f"(d[74]),"+f"(d[75]),"+f"(d[76]),"+f"(d[77]),"+f"(d[78]),"+f"(d[79]),"+f"(d[80]),"+f"(d[81]),"+f"(d[82]),"+f"(d[83]),"+f"(d[84]),"+f"(d[85]),"+f"(d[86]),"+f"(d[87]),"+f"(d[88]),"+f"(d[89]),"+f"(d[90]),"+f"(d[91]),"+f"(d[92]),"+f"(d[93]),"+f"(d[94]),"+f"(d[95]) : "l"(da),"l"(db),"r"(sc));
}
__device__ __forceinline__ void wg_ss160_01(float* d, uint64_t da, uint64_t db, int sc) {
  asm volatile("{.reg .pred p; setp.ne.b32 p, %82, 0; wgmma.mma_async.sync.aligned.m64n160k16.f32.bf16.bf16 {%0,%1,%2,%3,%4,%5,%6,%7,%8,%9,%10,%11,%12,%13,%14,%15,%16,%17,%18,%19,%20,%21,%22,%23,%24,%25,%26,%27,%28,%29,%30,%31,%32,%33,%34,%35,%36,%37,%38,%39,%40,%41,%42,%43,%44,%45,%46,%47,%48,%49,%50,%51,%52,%53,%54,%55,%56,%57,%58,%59,%60,%61,%62,%63,%64,%65,%66,%67,%68,%69,%70,%71,%72,%73,%74,%75,%76,%77,%78,%79}, %80, %81, p, 1, 1, 0, 1;}"
    : "+f"(d[0]),"+f"(d[1]),"+f"(d[2]),"+f"(d[3]),"+f"(d[4]),"+f"(d[5]),"+f"(d[6]),"+f"(d[7]),"+f"(d[8]),"+f"(d[9]),"+f"(d[10]),"+f"(d[11]),"+f"(d[12]),"+f"(d[13]),"+f"(d[14]),"+f"(d[15]),"+f"(d[16]),"+f"(d[17]),"+f"(d[18]),"+f"(d[19]),"+f"(d[20]),"+f"(d[21]),"+f"(d[22]),"+f"(d[23]),"+f"(d[24]),"+f"(d[25]),"+f"(d[26]),"+f"(d[27]),"+f"(d[28]),"+f"(d[29]),"+f"(d[30]),"+f"(d[31]),"+f"(d[32]),"+f"(d[33]),"+f"(d[34]),"+f"(d[35]),"+f"(d[36]),"+f"(d[37]),"+f"(d[38]),"+f"(d[39]),"+f"(d[40]),"+f"(d[41]),"+f"(d[42]),"+f"(d[43]),"+f"(d[44]),"+f"(d[45]),"+f"(d[46]),"+f"(d[47]),"+f"(d[48]),"+f"(d[49]),"+f"(d[50]),"+f"(d[51]),"+f"(d[52]),"+f"(d[53]),"+f"(d[54]),"+f"(d[55]),"+f"(d[56]),"+f"(d[57]),"+f"(d[58]),"+f"(d[59]),"+f"(d[60]),"+f"(d[61]),"+f"(d[62]),"+f"(d[63]),"+f"(d[64]),"+f"(d[65]),"+f"(d[66]),"+f"(d[67]),"+f"(d[68]),"+f"(d[69]),"+f"(d[70]),"+f"(d[71]),"+f"(d[72]),"+f"(d[73]),"+f"(d[74]),"+f"(d[75]),"+f"(d[76]),"+f"(d[77]),"+f"(d[78]),"+f"(d[79]) : "l"(da),"l"(db),"r"(sc));
}
__device__ __forceinline__ void wg_ss96_01(float* d, uint64_t da, uint64_t db, int sc) {
  asm volatile("{.reg .pred p; setp.ne.b32 p, %50, 0; wgmma.mma_async.sync.aligned.m64n96k16.f32.bf16.bf16 {%0,%1,%2,%3,%4,%5,%6,%7,%8,%9,%10,%11,%12,%13,%14,%15,%16,%17,%18,%19,%20,%21,%22,%23,%24,%25,%26,%27,%28,%29,%30,%31,%32,%33,%34,%35,%36,%37,%38,%39,%40,%41,%42,%43,%44,%45,%46,%47}, %48, %49, p, 1, 1, 0, 1;}"
    : "+f"(d[0]),"+f"(d[1]),"+f"(d[2]),"+f"(d[3]),"+f"(d[4]),"+f"(d[5]),"+f"(d[6]),"+f"(d[7]),"+f"(d[8]),"+f"(d[9]),"+f"(d[10]),"+f"(d[11]),"+f"(d[12]),"+f"(d[13]),"+f"(d[14]),"+f"(d[15]),"+f"(d[16]),"+f"(d[17]),"+f"(d[18]),"+f"(d[19]),"+f"(d[20]),"+f"(d[21]),"+f"(d[22]),"+f"(d[23]),"+f"(d[24]),"+f"(d[25]),"+f"(d[26]),"+f"(d[27]),"+f"(d[28]),"+f"(d[29]),"+f"(d[30]),"+f"(d[31]),"+f"(d[32]),"+f"(d[33]),"+f"(d[34]),"+f"(d[35]),"+f"(d[36]),"+f"(d[37]),"+f"(d[38]),"+f"(d[39]),"+f"(d[40]),"+f"(d[41]),"+f"(d[42]),"+f"(d[43]),"+f"(d[44]),"+f"(d[45]),"+f"(d[46]),"+f"(d[47]) : "l"(da),"l"(db),"r"(sc));
}
__device__ __forceinline__ void wg_ss64_01(float* d, uint64_t da, uint64_t db, int sc) {
  asm volatile("{.reg .pred p; setp.ne.b32 p, %34, 0; wgmma.mma_async.sync.aligned.m64n64k16.f32.bf16.bf16 {%0,%1,%2,%3,%4,%5,%6,%7,%8,%9,%10,%11,%12,%13,%14,%15,%16,%17,%18,%19,%20,%21,%22,%23,%24,%25,%26,%27,%28,%29,%30,%31}, %32, %33, p, 1, 1, 0, 1;}"
    : "+f"(d[0]),"+f"(d[1]),"+f"(d[2]),"+f"(d[3]),"+f"(d[4]),"+f"(d[5]),"+f"(d[6]),"+f"(d[7]),"+f"(d[8]),"+f"(d[9]),"+f"(d[10]),"+f"(d[11]),"+f"(d[12]),"+f"(d[13]),"+f"(d[14]),"+f"(d[15]),"+f"(d[16]),"+f"(d[17]),"+f"(d[18]),"+f"(d[19]),"+f"(d[20]),"+f"(d[21]),"+f"(d[22]),"+f"(d[23]),"+f"(d[24]),"+f"(d[25]),"+f"(d[26]),"+f"(d[27]),"+f"(d[28]),"+f"(d[29]),"+f"(d[30]),"+f"(d[31]) : "l"(da),"l"(db),"r"(sc));
}
__device__ __forceinline__ void wg_rs160_1(float* d, const uint32_t* a, uint64_t db, int sc) {
  asm volatile("{.reg .pred p; setp.ne.b32 p, %85, 0; wgmma.mma_async.sync.aligned.m64n160k16.f32.bf16.bf16 {%0,%1,%2,%3,%4,%5,%6,%7,%8,%9,%10,%11,%12,%13,%14,%15,%16,%17,%18,%19,%20,%21,%22,%23,%24,%25,%26,%27,%28,%29,%30,%31,%32,%33,%34,%35,%36,%37,%38,%39,%40,%41,%42,%43,%44,%45,%46,%47,%48,%49,%50,%51,%52,%53,%54,%55,%56,%57,%58,%59,%60,%61,%62,%63,%64,%65,%66,%67,%68,%69,%70,%71,%72,%73,%74,%75,%76,%77,%78,%79}, {%80,%81,%82,%83}, %84, p, 1, 1, 1;}"
    : "+f"(d[0]),"+f"(d[1]),"+f"(d[2]),"+f"(d[3]),"+f"(d[4]),"+f"(d[5]),"+f"(d[6]),"+f"(d[7]),"+f"(d[8]),"+f"(d[9]),"+f"(d[10]),"+f"(d[11]),"+f"(d[12]),"+f"(d[13]),"+f"(d[14]),"+f"(d[15]),"+f"(d[16]),"+f"(d[17]),"+f"(d[18]),"+f"(d[19]),"+f"(d[20]),"+f"(d[21]),"+f"(d[22]),"+f"(d[23]),"+f"(d[24]),"+f"(d[25]),"+f"(d[26]),"+f"(d[27]),"+f"(d[28]),"+f"(d[29]),"+f"(d[30]),"+f"(d[31]),"+f"(d[32]),"+f"(d[33]),"+f"(d[34]),"+f"(d[35]),"+f"(d[36]),"+f"(d[37]),"+f"(d[38]),"+f"(d[39]),"+f"(d[40]),"+f"(d[41]),"+f"(d[42]),"+f"(d[43]),"+f"(d[44]),"+f"(d[45]),"+f"(d[46]),"+f"(d[47]),"+f"(d[48]),"+f"(d[49]),"+f"(d[50]),"+f"(d[51]),"+f"(d[52]),"+f"(d[53]),"+f"(d[54]),"+f"(d[55]),"+f"(d[56]),"+f"(d[57]),"+f"(d[58]),"+f"(d[59]),"+f"(d[60]),"+f"(d[61]),"+f"(d[62]),"+f"(d[63]),"+f"(d[64]),"+f"(d[65]),"+f"(d[66]),"+f"(d[67]),"+f"(d[68]),"+f"(d[69]),"+f"(d[70]),"+f"(d[71]),"+f"(d[72]),"+f"(d[73]),"+f"(d[74]),"+f"(d[75]),"+f"(d[76]),"+f"(d[77]),"+f"(d[78]),"+f"(d[79]) : "r"(a[0]),"r"(a[1]),"r"(a[2]),"r"(a[3]),"l"(db),"r"(sc));
}
__device__ __forceinline__ void wg_ss8_10(float* d, uint64_t da, uint64_t db, int sc) {
  asm volatile("{.reg .pred p; setp.ne.b32 p, %6, 0; wgmma.mma_async.sync.aligned.m64n8k16.f32.bf16.bf16 {%0,%1,%2,%3}, %4, %5, p, 1, 1, 1, 0;}"
    : "+f"(d[0]),"+f"(d[1]),"+f"(d[2]),"+f"(d[3]) : "l"(da),"l"(db),"r"(sc));
}

constexpr uint32_t DB = 1024;
constexpr int WSLOT = 24576, NW = 6, ASLOT = 8192, ARING = 4 * ASLOT;
constexpr int OFF_A = NW * WSLOT;
constexpr int OFF_PB = OFF_A + 2 * ARING;
constexpr int OFF_CV = OFF_PB + 16384, OFF_ST = OFF_CV + 768, OFF_TS = OFF_ST + 256, OFF_MODR = OFF_TS + 512, OFF_BAR = OFF_MODR + 80, SMEM_BYTES = OFF_BAR + 1168;
constexpr int OFF_BX = OFF_PB, OFF_AX = OFF_BX + 12288, OFF_RT = OFF_AX + 2048, OFF_GB = OFF_RT + 512, OFF_CO = OFF_CV;
constexpr int OFF_UV = 5 * WSLOT, OFF_UVE = OFF_PB, OFF_SX = OFF_A + ARING + 3 * ASLOT, OFF_X1 = 2 * WSLOT + ASLOT, OFF_XCH = WSLOT;
constexpr int OFF_Q = 0, KV_V = 4096, KV_H = 8192, F_E = 16, F_O = 4176, OFF_WM = 3 * WSLOT, OFF_TAP = 168576, OFF_MR = OFF_A + 3 * ASLOT;
constexpr uint64_t pk5(int a, int b, int c, int d, int e) { return (uint64_t)(a / 128) | (uint64_t)(b / 128) << 12 | (uint64_t)(c / 128) << 24 | (uint64_t)(d / 128) << 36 | (uint64_t)(e / 128) << 48; }
constexpr uint64_t T_KV = pk5(20480, 30720, 40960, 180224, 190464), T_F = pk5(51200, 59648, 200192, 147456, 155904), T_X = pk5(208512, 164352, 68096, 208512, 164352),
                   T_P = pk5(131072, OFF_PB, 114688, 131072, OFF_PB);
__host__ __device__ __forceinline__ uint32_t tab(uint64_t t, int c) { return ((uint32_t)(t >> (12 * c)) & 0xFFF) << 7; }
enum { B_KV = 0, B_FRAW = 5, B_Q = 10, B_WM = 15, B_XR, B_MR = B_XR + 5, B_QTOK, B_ST1, B_MODR, B_S3 = B_MODR + 5, B_FIN, B_FL = 32, B_PFULL = B_FL + 5, B_PEMPTY = B_PFULL + 5, B_FRDY = B_PEMPTY + 5,
       B_G3 = B_FRDY + 5, B_EXT, B_QTD, B_LAG, B_GB, B_UVD, B_TURN, B_FULL = 60, B_RETRY = B_FULL + 33, B_XFREE = B_RETRY + 9, B_BX, B_UVB, B_UVE, B_SX, B_EMPTY = 109 };
static_assert(B_MODR + 5 <= B_FL && B_UVD < B_FULL && B_SX + 2 == B_EMPTY - 1, "barrier groups");
#define BAR(i) (base + OFF_BAR + 8 * (i))

constexpr int NE = 24;
struct Maps { CUtensorMap km, v, q, kh, tap, wm, w1s, w3s, xs, w1, w3, w1e, w3e, x1s, x1b, w2a, w2b, outa, outb; };
struct Ptrs { const bf16 *ssmk, *c, *ssmd; Scratch* g; uint64_t prog, cprog[2]; int boff, th, wms, ulo, uhi; uint32_t c0, fin, turn, mr2, m3, seq; float one; uint2 sched[NE]; uint32_t wdep[20], wt[5]; uint2 w2t[12]; int hid[3][9]; };

#define REGION_IDS int tid, lane, bid; \
  asm volatile("mov.u32 %0, %%tid.x;" : "=r"(tid)); asm volatile("mov.u32 %0, %%laneid;" : "=r"(lane)); asm volatile("mov.u32 %0, %%ctaid.x;" : "=r"(bid)); \
  const int i0 = tid & 127; (void)i0; (void)lane; (void)bid

__device__ __forceinline__ void ffn_role(int& h, int& j, int& r) {
  uint32_t b;
  asm volatile("mov.u32 %0, %%ctaid.x;" : "=r"(b));
  const uint32_t c = b >> 1, q = (c - 36) * 37 >> 8, e = c - 36 - 7 * q;
  h = b & 1;
  const uint32_t k = c < 4 ? 0 : c < 36 ? (c - 4) & 7 : e + 1, p = c < 4 ? c : c < 36 ? (c - 4) >> 3 : q, up = c - 4 >= 32;
  j = 2 * (k & 1) + up;
  r = 2 * (k & 6) + p;
}
__device__ __forceinline__ int fslice(int j, int e) { return e == 2 ? j ^ 1 : (~j & 2) + e; }
__device__ __forceinline__ int mod_ch(int p) { return p < 40 ? (p >> 3) * 128 + (p & 1) * 64 : 64 * (p < 50 ? p - 40 : p - 50); }
__device__ __forceinline__ int mod_col(int p) { return mod_ch(p) + 640 * (p < 40 ? 0x4210 >> (2 * (p & 6)) & 7 : p < 50 ? 3 : 5); }
__device__ __forceinline__ uint32_t mod_sum(uint2 v) { return pack_bf16(0.f, __uint_as_float(v.x) + __uint_as_float(v.y)); }

constexpr int NT = 3, LAG2 = 29, MG = 4;
__device__ __forceinline__ int w_block(int up, int m) { return m == 1 ? 2 + 3 * up : 3 * (m >> 1) + up; }
__host__ __device__ constexpr int w2_at(int v) { return 8192 * (v ? 0x0613030008ull >> v % 5 * 8 & 255 : 15); }
__host__ __device__ constexpr int w2_step(int v) { return 8192 * (v ? 0x32113 >> v % 5 * 4 & 15 : 1); }
__host__ __device__ constexpr int hid_at(int m, int g) { return 8192 * ((g ? 0x0D07110F1816ull : 0x0A19101A1412ull) >> m % 6 * 8 & 255); }
__host__ __device__ constexpr uint32_t w2_desc(int v) { return (DB + w2_at(v)) >> 4 | w2_step(v) << 12; }
__device__ __forceinline__ int next_slot(int s) { return s >= 4 * WSLOT ? 0 : s + WSLOT; }

template <int U> __device__ __forceinline__ void cstep(float* acc, const uint32_t* A, uint64_t db) {
  const uint32_t* a = A + 4 * U;
  const uint64_t d = db + 16 * U;
  if (U == 4) { wg_rs64_0(acc + 96, A, db + 192, 0); wg_rs48_0(acc + 96, A + 4, db + 208, 1); wg_rs32_0(acc + 96, A + 8, db + 224, 1); wg_rs16_0(acc + 96, A + 12, db + 240, 1); }
  if (U <= 4) wg_rs192_0(acc, a, d, U);
  if (U == 5) wg_rs176_0(acc, a, d, 1);
  if (U == 6) wg_rs160_0(acc, a, d, 1);
  if (U == 7) wg_rs144_0(acc, a, d, 1);
  if (U == 8) wg_rs128_0(acc, a, d, 1);
  if (U == 9) wg_rs112_0(acc, a, d, 1);
  if (U == 10) wg_rs96_0(acc, a, d, 1);
  if (U == 11) wg_rs80_0(acc, a, d, 1);
  if (U == 12) wg_rs64_0(acc, a, d, 1);
  if (U == 13) wg_rs48_0(acc, a, d, 1);
  if (U == 14) wg_rs32_0(acc, a, d, 1);
  if (U == 15) wg_rs16_0(acc, a, d, 1);
}
template <int U0, int U1> __device__ __forceinline__ void csteps(float* acc, const uint32_t* A, uint64_t db) {
  cstep<U0>(acc, A, db);
  if constexpr (U0 > U1) csteps<U0 - 1, U1>(acc, A, db);
}
template <int U0, int U1> __device__ __forceinline__ void cload(uint32_t* A, uint32_t fa) {
  asm volatile("{ld.shared.b32 %0, [%4+%5]; ld.shared.b32 %1, [%4+%5+128]; ld.shared.b32 %2, [%4+%5+16]; ld.shared.b32 %3, [%4+%5+144];}"
               : "=r"(A[4 * U0]), "=r"(A[4 * U0 + 1]), "=r"(A[4 * U0 + 2]), "=r"(A[4 * U0 + 3]) : "r"(fa), "n"(256 * U0) : "memory");
  if constexpr (U0 > U1) cload<U0 - 1, U1>(A, fa);
}

__device__ __forceinline__ void mod_gemv(Scratch* G, uint32_t wm, int unit, int w, int lane, uint32_t par) {
  float d[4] = {};
  fence_regs(d);
  wg_fence();
#pragma unroll 1
  for (int k = 0; k < 20; k += 2) {
    wg_ss8_10(d, mkdesc(DB + wm + 2048 * k, 16, 1024, 1), mkdesc(DB + OFF_CV + 32 * k, 16, 128, 0), 1);
    wg_ss8_10(d, mkdesc(DB + wm + 2048 * k + 2048, 16, 1024, 1), mkdesc(DB + OFF_CV + 32 * k + 32, 16, 128, 0), 1);
  }
  wg_commit();
  const int p = unit >> 1, ch = mod_ch(p) + 16 * w + (lane >> 2);
  uint32_t* dst = (uint32_t*)(p < 40 ? &G->modc[ch & 127][8 + (p >> 1)] : &G->modv[p >= 50][ch]) + (unit & 1);
  wg_wait<0>();
  fence_regs(d);
  if (!(lane & 3)) {
    publish(dst, (__float_as_uint(d[0]) & ~1u) | par);
    publish(dst + (p < 40 ? 512 : 16), (__float_as_uint(d[2]) & ~1u) | par);
    if (p < 40 && (p & 6) == 6) {
      dst = (uint32_t*)&G->modv[2][ch] + (unit & 1);
      publish(dst, (__float_as_uint(d[0]) & ~1u) | par);
      publish(dst + 16, (__float_as_uint(d[2]) & ~1u) | par);
    }
  }
}
__device__ __forceinline__ void silu_vector(const bf16* c, uint32_t base) {
  REGION_IDS;
  const uint32_t c0 = ldg32(c + 320 * (bid & 1) + 2 * i0), c1 = ldg32(c + 320 * (bid & 1) + 256 + 2 * lane);
  sts32(base + OFF_CV + 4 * i0, pack_bf16(silu_f(bf_lo(c0)), silu_f(bf_hi(c0))));
  sts32(base + OFF_CV + 512 + 4 * lane, pack_bf16(silu_f(bf_lo(c1)), silu_f(bf_hi(c1))));
  fence_async_smem();
}

__device__ __forceinline__ void mod_poll(Scratch* G, uint32_t base, int c, int n, uint32_t epoch) {
  REGION_IDS;
  const int e = 4 * c + (lane & (4 * n - 1));
  uint2 m;
  int it = 0;
#pragma unroll 1
  do m = ld_relaxed64(&G->modc[bid][8 + e]); while (__any_sync(~0u, ((m.x ^ epoch) | (m.y ^ epoch)) & 1) && ++it < SPIN_LIMIT);
  sts32(base + OFF_MODR + 4 * e, __byte_perm(badd2(mod_sum(m), (lane & 1) * 0x3F800000u), 0, 0x3232));
  __syncwarp();
  if (elect()) { mbar_arrive(BAR(B_MODR + c)); if (n > 1) mbar_arrive(BAR(B_MODR + c + 1)); }
}
__device__ __forceinline__ void row_stats(Scratch* G, uint32_t base, uint32_t epoch) {
  REGION_IDS;
  mbar_wait_cluster(BAR(B_ST1));
  if (lane < 8) red_hint(G->hint[5][lane]);
  const uint2 x = lds64(base + OFF_ST + 8 * (lane & 15)), y = lds64(base + OFF_ST + 128 + 8 * (lane & 15));
  float m, sd;
  ln_final(__uint_as_float(x.x) + __uint_as_float(y.x), __uint_as_float(x.y) + __uint_as_float(y.y), m, sd);
  sd = rbf(rcpf(sd));
  const uint32_t mr = pack_bf16(sd, -rbf(m) * sd), tg = lane & 7 ? 0 : lane & 8 ? 1 : 0x8000;
  const uint32_t o = __byte_perm(__shfl_sync(~0u, mr, 2 * lane & 14), __shfl_sync(~0u, mr, (2 * lane & 14) + 1), (lane & 8) ? 0x7632 : 0x5410);
  if (lane < 16) st_relaxed32(&G->st1[lane >> 3][8 * bid + (lane & 7)], (o & ~tg) | ((epoch & 1) * tg));
  if (elect()) mbar_arrive(BAR(B_FIN));
}
template <int B, int NEXT> __device__ __forceinline__ void strip(Scratch* G, const CUtensorMap* map, uint32_t base, int c, uint32_t epoch, uint32_t& ph, uint32_t& pre, float4& s) {
  REGION_IDS;
  int h, j, r, it = 0;
  ffn_role(h, j, r);
  const uint32_t buf = base + OFF_SX + 4096 * B, a = buf + 32 * lane;
#pragma unroll 1
  while (__any_sync(~0u, pre != 64 * epoch) && ++it < SPIN_LIMIT) pre = ld_relaxed32(G->xsh[c][(r & 6) + (j >> 1)]);
#pragma unroll 1
  for (it = 0; it < SPIN_LIMIT; it++) {
    if (elect()) { mbar_expect_tx(BAR(B_SX + B), 4096); tma2d(buf, map, 128 * r + 64 * h, D_ * (epoch & 1) + 128 * c + 32 * j, BAR(B_SX + B)); }
    mbar_wait(BAR(B_SX + B), ph);
    ph ^= 1;
    if (__all_sync(~0u, min(min(lds32(a), lds32(a + 1024)), min(lds32(a + 2048), lds32(a + 3072))))) break;
  }
  pre = 0;
  if (c == NEXT - 1 || c == NEXT - 2) pre = ld_relaxed32(G->xsh[c + 1][(r & 6) + (j >> 1)]);
#pragma unroll 1
  for (uint32_t o = buf + 4 * lane; o < buf + 4096; o += 1024) {
    uint32_t x[8];
#pragma unroll
    for (int i = 0; i < 8; i++) x[i] = lds32(o + 128 * i);
#pragma unroll
    for (int i = 0; i < 8; i++) { const float lo = bf_lo(x[i]), hi = bf_hi(x[i]); s.x += lo; s.y = fmaf(lo, lo, s.y); s.z += hi; s.w = fmaf(hi, hi, s.w); }
  }
}
__device__ __forceinline__ void mr_poll(Scratch* G, uint32_t base, uint32_t epoch) {
  int it = 0;
#pragma unroll 1
  while (__any_sync(~0u, ld_relaxed32(G->hint[5][4 * (blockIdx.x >> 6) + (blockIdx.x >> 3 & 3)]) != epoch << 7) && ++it < SPIN_LIMIT);
  if (elect()) { mbar_expect_tx(BAR(B_MR), 8192); bulk_load(base + OFF_MR, G->st1, 8192, BAR(B_MR)); mbar_arrive(BAR(B_QTOK)); }
}

__global__ void __cluster_dims__(2, 1, 1) __launch_bounds__(512, 1) k_fused(const __grid_constant__ Ptrs P, const __grid_constant__ Maps maps) {
  Scratch* const G = P.g;
  extern __shared__ __align__(1024) uint8_t smem_raw[];
  const uint32_t t_start = clock();
  const uint32_t base = __shfl_sync(~0u, smem_u32(smem_raw), 0);
  uint32_t t_iss = 0;
  if (threadIdx.x < 32 && blockIdx.x < 128) {
    mbar_init<1>(BAR(0), 1);
    if (elect()) {
      const int c0 = 64 * (blockIdx.x & 1), c1 = 2 * (blockIdx.x & 126);
      mbar_expect_tx(BAR(B_KV), 12288);
      tma3d(base + tab(T_KV, 0), &maps.km, c0, c1, 0, BAR(B_KV));
      tma3d(base + tab(T_KV, 0) + KV_V, &maps.v, c0, c1, 0, BAR(B_KV));
      tma3d(base + tab(T_KV, 0) + KV_H, &maps.kh, c0, c1 - 1, 5, BAR(B_KV));
      tma3d(base + OFF_TAP, &maps.tap, 0, blockIdx.x & 1, 0, BAR(B_KV));
    }
    if (P.boff) mbar_wait(BAR(0));
  }
  if ((base & 0xFFFFFFu) != DB) __trap();
  const int wid = __shfl_sync(~0u, threadIdx.x >> 5, 0), wg = wid >> 2, w = wid & 3;
  if (blockIdx.x + P.boff >= 128) {
    REGION_IDS;
    const int nu = 30 - (P.uhi - P.ulo) / 4;
    auto tile = [&](int n) { return 2 * (n < P.ulo / 4 ? n : n + 30 - nu) + (blockIdx.x >> 1 & 1); };
    auto fetch = [&](int n, int b) {
      if (elect()) {
        mbar_expect_tx(BAR(n), 40960);
#pragma unroll
        for (int k = 0; k < 5; k++) tma3d(base + 40960 * b + 8192 * k, &maps.wm, mod_col(tile(n)), 320 * (blockIdx.x & 1) + 64 * k, 0, BAR(n));
      }
    };
    if (P.boff) __syncthreads();
    if (wid == 12) {
      mbar_init<4>(BAR(0), 1);
#pragma unroll 1
      for (int n = 0; n < 4; n++) fetch(n, n);
      mbar_init<26>(BAR(4), 1);
      mbar_init<60>(BAR(32), 4);
    }
    const uint32_t par = ~ld_relaxed32(G->hint[7][0]) >> 7 & 1;
    silu_vector(P.c, base);
    __syncthreads();
    if (wid == 12) {
      wait_clock(t_start + P.th);
#pragma unroll 1
      for (int n = 4, b = 4; n < nu; n++) {
        if (n >= 5) mbar_wait(BAR(27 + n));
        fetch(n, b);
        b = b == 4 ? 0 : b + 1;
      }
    } else if (wg < 2) {
#pragma unroll 1
      for (int n = wg; n < nu; n += 2) {
        const uint32_t wm = 40960 * (n % 5);
        float d[20] = {};
        mbar_wait(BAR(n));
        fence_regs(d);
        wg_fence();
#pragma unroll 1
        for (int k = 0; k < 20; k += 5) {
#pragma unroll
          for (int e = 0; e < 5; e++) wg_ss8_10(d + 4 * e, mkdesc(DB + wm + 2048 * (k + e), 16, 1024, 1), mkdesc(DB + OFF_CV + 32 * (k + e), 16, 128, 0), 1);
        }
        wg_commit();
        wg_wait<0>();
        fence_regs(d);
        if (elect()) mbar_arrive(BAR(32 + n));
        if (!(lane & 3)) {
          sts32(base + 204800 + 256 * n + 64 * w + lane, __float_as_uint(d[0] + d[4] + d[8] + (d[12] + d[16])));
          sts32(base + 204800 + 256 * n + 64 * w + lane + 32, __float_as_uint(d[2] + d[6] + d[10] + (d[14] + d[18])));
        }
        arrive1(BAR(62 + n));
      }
    } else if (wg == 2) {
#pragma unroll 1
      for (int n = w; n < nu; n += 4) {
        const int t = tile(n), ch = mod_ch(t) + lane;
        uint32_t* q = (uint32_t*)(t < 40 ? &G->modc[ch & 127][8 + (t >> 1)] : &G->modv[t >= 50][ch]) + (bid & 1);
        mbar_wait(BAR(62 + n));
        const uint32_t x = (lds32(base + 204800 + 256 * n + 4 * lane) & ~1u) | par, y = (lds32(base + 204928 + 256 * n + 4 * lane) & ~1u) | par;
        publish(q, x);
        publish(q + (t < 40 ? 2048 : 64), y);
        if (t < 40 && (t & 6) == 6) {
          q = (uint32_t*)&G->modv[2][ch] + (bid & 1);
          publish(q, x);
          publish(q + 64, y);
        }
      }
    }
    return;
  }
  if (wid < 15) mbar_init<4>(BAR(4 * wid + (wid == 0)), wid < 8 ? 1 : 4);
  asm volatile("fence.mbarrier_init.release.cluster; bar.sync 0, 512;" ::: "memory");
  asm volatile("barrier.cluster.arrive.relaxed.aligned;" ::: "memory");
#define LAUNCHES const uint32_t launches = ld_relaxed32(G->hint[7][blockIdx.x >> 4])
#define EPOCH ((__shfl_sync(~0u, launches, 0) >> 7) + 1)
  if (wg == 3) {
    asm volatile("setmaxnreg.dec.sync.aligned.u32 24;");
    if (w == 1) {
      {
        REGION_IDS;
        const int c1 = 2 * (bid & 126), ws = bid >= P.ulo && bid < P.uhi ? P.wms : 99;
#pragma unroll 1
        for (int e = 0; e < NE; e++) {
          const uint2 x = P.sched[e];
          const uint32_t kind = x.x >> 16 & 15, ch = x.x >> 13 & 0x380, dst = base + (x.y & 0x3FFFF), b = BAR(x.y >> 18);
          wait_clock(t_start + (x.x & 0xFFFF));
          if (kind < 3 && elect()) tma3d(dst, &maps.km + kind, ch + 64 * (bid & 1), c1, 0, b);
          if (kind == 0 && elect()) tma3d(dst + KV_H, &maps.kh, ch + 64 * (bid & 1), c1 - 1, 5, b);
          if (kind == 3 && elect()) bulk_load(dst, P.ssmk + (ch + bid) * S_, 4096, b);
          if ((uint32_t)(e - ws) < 5 && elect()) tma3d(base + OFF_WM + 8192 * (e - ws), &maps.wm, mod_col(bid >> 1), 320 * (bid & 1) + 64 * (e - ws), 0, BAR(B_WM));
          if ((uint32_t)(e - 8) < 13 && elect()) prefetch_map(&maps.w1s + (e - 8));
        }
      }
      cluster_wait();
      int h, j, r;
      ffn_role(h, j, r);
      mbar_wait(BAR(B_QTD));
      mbar_wait(BAR(B_FL));
#pragma unroll 1
      for (int u = 0; u < 20; u++) {
        const uint32_t x = P.wdep[u], s = base + (x & ~8191u);
        if (u < 5) wait_clock(t_start + P.wt[u]);
        mbar_wait(BAR(opaque(x & 255)));
        if (elect()) {
          mbar_expect_tx(BAR(B_FULL + u), WSLOT + 4 * (x & 4096));
#pragma unroll
          for (int k = 0; k < 6; k++) tma3d(s + 4096 * w_block(k & 1, k >> 1), &maps.w1s + (k & 1), 0, 32 * u, 3 * (4 * h + j) + (k >> 1), BAR(B_FULL + u));
        }
      }
#pragma unroll 1
      for (int v = 0; v < 12; v++) {
        const int q = v * 11 >> 5, e = v - 3 * q, k32 = 24 * h + (q ? 6 * fslice(j, e) + 2 * q - 2 : 6 * j + 2 * e);
        const uint2 x = P.w2t[v];
        mbar_wait(BAR(x.y));
        if (elect()) {
          mbar_expect_tx(BAR(B_FULL + 20 + v), q ? WSLOT + 2 * ASLOT : WSLOT);
#pragma unroll
          for (int k = 0; k < 3; k++) tma5d(base - DB + 16 * ((x.x & 0xFFFF) + k * (x.x >> 16)), &maps.w2a + (q > 0), k < 2 ? 128 * j + 64 * k : 512 + 32 * (j & 2), k32, BAR(B_FULL + 20 + v));
        }
      }
    } else if (w == 0) {
      LAUNCHES;
      uint32_t epoch;
      {
        REGION_IDS;
        const unsigned* hp = G->hint[0][4 * (bid >> 6) + (bid >> 3 & 3)];
        uint32_t v = ld_relaxed32(hp + 256 * min(lane, 5));
        if (lane < 3) sts128(base + tab(T_X, lane) + 4096, 0, 0, 0, 0);
        if (lane && lane <= B_WM) mbar_expect_tx(BAR(lane), lane < B_FRAW ? 9728 : lane == B_WM ? 40960 : 4096);
        epoch = EPOCH;
        fence_async_smem();
        const uint32_t rdy = __ballot_sync(~0u, v == epoch << 6);
        uint32_t nx = 0, nm = 0;
#pragma unroll 1
        for (uint32_t seq = P.seq; seq; seq >>= 2) {
          int it = 0;
          if (seq & 1) {
            if (!(seq & 2)) mod_poll(G, base, nm, 1 + (seq == 13), epoch);
            nm++;
          } else if (seq & 2) {
            mr_poll(G, base, epoch);
          } else {
            if (!(rdy >> nx & 1)) {
#pragma unroll 1
              while (__any_sync(~0u, ld_relaxed32(hp + 256 * nx) != epoch << 6) && ++it < SPIN_LIMIT);
            }
            if (nx >= 3) mbar_wait(BAR(B_PFULL - 3 + nx));
            if (elect()) { mbar_expect_tx(BAR(B_XR + nx), 4096); bulk_load(base + tab(T_X, nx), G->xr + (128 * nx + bid) * 256, 4096, BAR(B_XR + nx)); }
            nx++;
          }
        }
      }
      REGION_IDS;
      int h, j, r;
      ffn_role(h, j, r);
      mbar_wait(BAR(B_G3));
      {
        const uint2* mp = &G->modv[lane & 4 ? 0 : 2][40 * (r & 14) + (lane & 24) + 2 * (lane & 3)];
        uint4 v[3];
        int it = 0;
#pragma unroll 1
        do {
          v[0] = ld_relaxed128(mp); v[1] = ld_relaxed128(mp + 32); v[2] = ld_relaxed128(mp + 64 - (lane & 16));
        } while (__any_sync(~0u, ((v[0].x ^ epoch) | (v[0].y ^ epoch) | (v[0].z ^ epoch) | (v[0].w ^ epoch) | (v[1].x ^ epoch) | (v[1].y ^ epoch) | (v[1].z ^ epoch) | (v[1].w ^ epoch) |
                                  (v[2].x ^ epoch) | (v[2].y ^ epoch) | (v[2].z ^ epoch) | (v[2].w ^ epoch)) & 1) && ++it < SPIN_LIMIT);
#pragma unroll
        for (int i = 0; i < 3; i++)
          sts32(base + OFF_CO + 128 * i + 4 * lane, badd2(pack_bf16(__uint_as_float(v[i].x) + __uint_as_float(v[i].y), __uint_as_float(v[i].z) + __uint_as_float(v[i].w)), lane & 4 ? 0 : 0x3F803F80u));
      }
      fence_async_smem();
      __syncwarp();
      ffn_role(h, j, r);
      mbar_wait(BAR(B_PEMPTY + 3));
      if (elect()) {
        mbar_expect_tx(BAR(B_UVB), WSLOT);
        tma3d(base + OFF_UV, &maps.w1 + (r & 1), 0, 40 * (r & 14), 3 * (4 * h + j), BAR(B_UVB));
        tma3d(base + OFF_UV + 12288, &maps.w1 + (r & 1), 0, 40 * (r & 14) + 32, 3 * (4 * h + j), BAR(B_UVB));
      }
      {
        float4 s = {};
        uint32_t ph = 0, pre = 0;
#pragma unroll 1
        for (int c = 2; c < 4; c++) strip<1, 3>(G, &maps.x1s, base, c, epoch, ph, pre, s);
        __syncwarp();
        sts128(base + OFF_SX + 4096 + 16 * lane, __float_as_uint(s.x), __float_as_uint(s.y), __float_as_uint(s.z), __float_as_uint(s.w));
        arrive1(BAR(B_S3));
      }
      ffn_role(h, j, r);
      cluster_wait();
      mbar_wait(BAR(B_UVD));
      asm volatile("fence.acq_rel.gpu;" ::: "memory");
      if (lane < 8) red_hint(G->hint[7][lane]);
      unsigned x;
      int it = 0;
#pragma unroll 1
      do { asm volatile("ld.acquire.gpu.global.u32 %0, [%1];" : "=r"(x) : "l"(G->hint[7][bid >> 4]) : "memory"); } while (__any_sync(~0u, x != 128 * epoch) && ++it < SPIN_LIMIT);
      fence_async_all();
      const int ch = D_ * (epoch & 1);
      mbar_wait(BAR(B_EXT));
      mbar_wait(BAR(B_EMPTY + 18));
      if (elect()) {
        mbar_expect_tx(BAR(B_FULL + 32), 20480);
#pragma unroll
        for (int k = 0; k < 4; k++) tma2d(base + (k < 3 ? OFF_X1 + k * WSLOT : OFF_SX), &maps.x1b, 128 * r + 64 * h, ch + 128 * j + 32 * (k ^ (j & 1)), BAR(B_FULL + 32));
        tma2d(base + OFF_SX + 4096, &maps.x1b, 128 * r + 64 * h, ch + 512 + 32 * j, BAR(B_FULL + 32));
        mbar_expect_tx(BAR(B_FULL), 8192); mbar_expect_tx(BAR(B_FULL + 1), 8192); mbar_expect_tx(BAR(B_FULL + 2), 4096);
      }
      mbar_wait(BAR(B_EMPTY + 27));
      if (elect()) mbar_arrive_remote(mapa(BAR(B_XFREE), h ^ 1));
    } else {
      LAUNCHES;
      uint32_t epoch;
      {
        REGION_IDS;
        uint32_t dv;
        asm volatile("ld.global.nc.u16 %0, [%1];" : "=r"(dv) : "l"(P.ssmd + 128 * (lane & 7) % D_ + bid));
        if (lane < 5) sts128(base + tab(T_F, lane) + (w & 1) * (F_O - 16), 0, 0, 0, 0);
        epoch = EPOCH;
        __syncwarp();
#pragma unroll 1
        for (int c = 0; c < 5; c++) {
          const float d = i0 == 64 ? bf_lo(dv) : 0.f;
          dv = __shfl_down_sync(~0u, dv, 1);
          const uint32_t a = base + tab(T_F, c) + 16 * (i0 - 64);
          mbar_wait(BAR(B_FRAW + c));
#pragma unroll
          for (int k = 0; k < 4; k++) {
            uint4 x = lds128(a + F_E + 1024 * k);
            const uint32_t pv = lds32(a + F_E - 4 + 1024 * k);
            if (k == 0) { x.x = pack_bf16(bf_lo(x.x) + d, bf_hi(x.x)); sts32(a + F_E, x.x); }
            sts128(a + F_O + 1024 * k, __byte_perm(pv, x.x, 0x5432), __byte_perm(x.x, x.y, 0x5432), __byte_perm(x.y, x.z, 0x5432), __byte_perm(x.z, x.w, 0x5432));
          }
          __syncwarp();
          if (elect()) mbar_arrive2(BAR(B_FRDY + c));
          if (c == 0 && w == P.fin) row_stats(G, base, epoch);
        }
      }
      REGION_IDS;
      int h, j, r;
      ffn_role(h, j, r);
      cluster_wait();
      if (w == 2) {
        const unsigned* fp = G->xsh[lane < 10 ? lane >> 1 : 0][(r & 6) + (lane & 1)];
        uint32_t rdy = 0, s = 0;
        mbar_wait(BAR(B_QTD));
        mbar_wait(BAR(B_FL + 2));
#pragma unroll 1
        for (int n = 0; n < 10; n++) {
          mbar_wait(BAR(n < 2 ? B_FL + 3 + n : n == 2 ? B_PFULL + 4 : B_EMPTY + 2 * n - 5));
#pragma unroll 1
          for (int it = 0; !(rdy >> n & 1) && it < SPIN_LIMIT; it++) rdy = __ballot_sync(~0u, ld_relaxed32(fp) == 64 * epoch);
          if (elect()) {
            tma2d(base + OFF_A + s, &maps.xs, 128 * r + 64 * h, 64 * n, BAR(B_FULL + 2 * n));
            tma2d(base + OFF_A + ARING + s, &maps.xs, 128 * r + 64 - 64 * h, 64 * n, BAR(B_FULL + 2 * n));
          }
          s = s == 2 * ASLOT ? 0 : s + ASLOT;
        }
      } else {
        if (P.m3 < 5) mod_poll(G, base, P.m3, 1, epoch);
        float4 s = {};
        uint32_t ph = 0, pre = 0;
        mbar_wait(BAR(B_FL + 2));
        mbar_wait(BAR(B_PFULL + 3));
#pragma unroll 1
        for (int c = 0; c < 5; c = c == 1 ? 4 : c + 1) {
          if (c == 4) {
            ffn_role(h, j, r);
            mbar_wait(BAR(B_PEMPTY + 4));
            if (elect()) {
              mbar_expect_tx(BAR(B_UVE), 6144);
              tma3d(base + OFF_UVE, &maps.w1e + (r & 1), 0, 40 * (r & 14) + 64, 3 * (4 * h + j), BAR(B_UVE));
            }
          }
          strip<0, 1>(G, &maps.x1s, base, c, epoch, ph, pre, s);
        }
        mbar_wait(BAR(B_S3));
        const uint4 y = lds128(base + OFF_SX + 4096 + 16 * lane);
        const float s0 = s.x + __uint_as_float(y.x), q0 = s.y + __uint_as_float(y.y), s1 = s.z + __uint_as_float(y.z), q1 = s.w + __uint_as_float(y.w);
        ffn_role(h, j, r);
        asm volatile("{.reg .b128 t, x; .reg .b64 a, b; mov.b64 a, {%1,%2}; mov.b64 b, {%3,%4}; mov.b128 x, {a,b}; atom.relaxed.gpu.global.exch.b128 t, [%0], x;}"
                     ::"l"(&G->st2[2 * r + h][j][4 * lane]), "r"((__float_as_uint(s0) & ~1u) | (epoch & 1)), "f"(q0), "r"((__float_as_uint(s1) & ~1u) | (epoch & 1)), "f"(q1) : "memory");
        uint4* z = G->x1[~epoch & 1] + 1280 * bid + lane;
#pragma unroll 1
        for (int k = 0; k < 40; k++) st_relaxed128(z + 32 * k, 0, 0, 0, 0);
      }
    }
  } else if (wg == 2) {
    asm volatile("setmaxnreg.dec.sync.aligned.u32 40;");
    mbar_init<12>(BAR(B_FULL + 12 * w), 1);
    mbar_init<9>(BAR(B_EMPTY - 1 + 9 * w), 8);
    asm volatile("fence.mbarrier_init.release.cluster;" ::: "memory");
    LAUNCHES;
    const uint32_t epoch = EPOCH;
    cluster_wait();
#pragma unroll 1
    for (uint64_t prog = P.prog; prog; prog >>= 4) {
      REGION_IDS;
      const int s = (prog & 7) - 1;
      if (!(prog & 8)) {
        const uint32_t a = base + tab(T_KV, s) + 128 * (lane & 3) + ((w ^ (lane & 3)) << 4) + 4 * (lane & 16) + (lane & 12), keep = ~(lane & 1), bit = epoch & lane & 1;
        uint4* dst = G->xr + (128 * s + 64 * (bid & 1) + 8 * w + 2 * (lane & 16) + (lane >> 1 & 6)) * 256 + 255 - 4 * (bid >> 1) - (lane & 3);
        mbar_wait(BAR(B_KV));
        mbar_wait(BAR(B_KV + s));
        const uint4 wv = lds128(base + OFF_TAP + 512 * s + 64 * w + 16 * (lane & 16) + 4 * (lane & 12));
        uint32_t kk[11], r[8];
#pragma unroll
        for (int k = 0; k < 11; k++) kk[k] = k < 3 ? lds32((a ^ (64 * (k & 1))) + KV_H + 512 * k) : lds32((a ^ (64 * (~k & 1))) + 512 * (k - 3));
        if (elect()) red_hint(G->hint[s][4 * (bid & 1) + w]);
#pragma unroll
        for (int k = 0; k < 8; k++) r[k] = lds32((a ^ (64 * (k & 1))) + KV_V + 512 * k);
        const uint32_t w0 = __byte_perm(wv.x, wv.z, 0x5410), w1 = __byte_perm(wv.x, wv.z, 0x7632),
                       w2 = __byte_perm(wv.y, wv.w, 0x5410), w3 = __byte_perm(wv.y, wv.w, 0x7632);
#pragma unroll
        for (int k = 0; k < 8; k++) r[k] = bmul2(bfma2(kk[k + 3], w0, bfma2(kk[k + 2], w1, bfma2(kk[k + 1], w2, bmul2(kk[k], w3)))), r[k]);
        st_relaxed128(dst, (__byte_perm(r[7], r[6], 0x5410) & keep) | bit, __byte_perm(r[5], r[4], 0x5410), __byte_perm(r[3], r[2], 0x5410), __byte_perm(r[1], r[0], 0x5410));
        st_relaxed128(dst + 256, (__byte_perm(r[7], r[6], 0x7632) & keep) | bit, __byte_perm(r[5], r[4], 0x7632), __byte_perm(r[3], r[2], 0x7632), __byte_perm(r[1], r[0], 0x7632));
      } else if (s >= 0) {
        const int tr = 4 * (lane & 1) + (lane >> 1 & 3);
        const uint32_t a = base + OFF_Q + 4096 * s + 128 * ((lane & 24) + tr) + ((w ^ tr) << 4);
        uint4* dst = G->qt + (128 * s + 64 * (bid & 1) + 8 * w + (lane >> 2)) * 256 + 4 * (bid >> 1) + (lane & 3);
        mbar_wait(BAR(B_Q + s));
#pragma unroll
        for (int k = 0; k < 2; k++) {
          uint32_t x[4];
          ldmatrix_x4_t(x, a ^ (64 * k));
          st_relaxed128(dst + 8192 * k, set_tag(x[0], ~lane & 1, epoch), x[1], x[2], x[3]);
        }
      } else if (w == 3) {
        row_stats(G, base, epoch);
      }
    }
    arrive1(BAR(B_QTD));
    {
      REGION_IDS;
      const uint32_t tag = opaque(~lane & 1);
      const uint32_t io = 16 * i0;
      uint4* gp = (uint4*)((char*)(G->xs + 256 * blockIdx.x) + io);
      constexpr int QO = -D_ * 256;
      const uint32_t sa = base + io;
      uint4 q[2];
      if (w == 0 && P.mr2) mr_poll(G, base, epoch);
      mbar_wait(BAR(B_QTOK));
      q[0] = ld_relaxed128(gp + QO);
      q[1] = ld_relaxed128(gp + QO + 128);
#pragma unroll 1
      for (int it = 0; it < SPIN_LIMIT; it++) {
        mbar_wait(BAR(B_MR), it & 1);
        const uint32_t x = lds32(sa + 16 * i0 + OFF_MR), y = lds32(sa + 16 * i0 + OFF_MR + 4096);
        sts32(sa + 16 * i0 + OFF_MR, x & 0xFFFF7FFFu);
        if (bar_all(3, !(((x >> 15 ^ epoch) | (y ^ epoch)) & 1))) break;
        if (w == 0 && elect()) { fence_async_smem(); mbar_expect_tx(BAR(B_MR), 8192); bulk_load(base + OFF_MR, G->st1, 8192, BAR(B_MR)); }
      }
#pragma unroll 1
      for (int c = 0; c < 5; c++) {
        mbar_wait(BAR(B_MODR + c));
        uint4 co = lds128(base + OFF_MODR + 16 * c);
        co.x = bmul2(co.x, co.z); co.y = bmul2(co.y, co.z);
        mbar_wait(BAR(B_PFULL + c));
        const uint32_t pb = io + (base + tab(T_P, c));
        gp = (uint4*)((char*)(G->xs + 256 * blockIdx.x + 32768 * c) + io);
#pragma unroll
        for (int hf = 0; hf < 2; hf++) {
#pragma unroll 1
          for (int it = 0; __any_sync(~0u, set_tag(q[hf].x, tag, epoch) != q[hf].x) && it < SPIN_LIMIT; it++) {
            q[hf] = ld_relaxed128(gp + QO + 128 * hf);
          }
          uint4 y = lds128(pb + 2048 * hf), z = lds128(pb + 2048 * hf + 4096);
          y.x = badd2(y.x, z.x); y.y = badd2(y.y, z.y); y.z = badd2(y.z, z.z); y.w = badd2(y.w, z.w);
          z = lds128(pb + 2048 * hf + 8192);
          uint4 m = lds128(pb + 2048 * hf + 12288);
          y.x = badd2(y.x, badd2(z.x, m.x)); y.y = badd2(y.y, badd2(z.y, m.y)); y.z = badd2(y.z, badd2(z.z, m.z)); y.w = badd2(y.w, badd2(z.w, m.w));
          z = lds128(sa + OFF_MR + 2048 * hf);
          m = lds128(sa + OFF_MR + 2048 * hf + 4096);
          y.x = bfma2(bfma2(bfma2(q[hf].x, z.x, m.x), co.y, co.x), y.x, q[hf].x);
          if (hf) {
            __syncwarp();
            asm volatile("{.reg .pred p; elect.sync _|p, 0xffffffff; @p red.relaxed.gpu.global.add.u32 [%0], 1; @p mbarrier.arrive.shared::cta.b64 _, [%1];}"
                         ::"l"(G->xsh[c][2 * w + (blockIdx.x >> 6)]), "r"(BAR(B_PEMPTY + c)), "r"(y.x) : "memory");
          }
          y.y = bfma2(bfma2(bfma2(q[hf].y, z.y, m.y), co.y, co.x), y.y, q[hf].y);
          y.z = bfma2(bfma2(bfma2(q[hf].z, z.z, m.z), co.y, co.x), y.z, q[hf].z);
          y.w = bfma2(bfma2(bfma2(q[hf].w, z.w, m.w), co.y, co.x), y.w, q[hf].w);
          st_relaxed128(gp + 128 * hf, set_tag(bmul2(y.x, co.w), tag, epoch), bmul2(y.y, co.w), bmul2(y.z, co.w), bmul2(y.w, co.w));
          asm volatile("{.reg .pred p; .reg .b32 t; setp.ne.u32 p, %5, 0; max.u32 t, %1, 1; @!p st.relaxed.gpu.global.v4.u32 [%0+%6], {t,%2,%3,%4}; @p st.relaxed.gpu.global.v4.u32 [%0+%7], {t,%2,%3,%4};}"
                       ::"l"(gp + 128 * hf), "r"(y.x), "r"(y.y), "r"(y.z), "r"(y.w), "r"(epoch & 1), "n"(D_ * 4096), "n"(D_ * 8192) : "memory");
          if (c < 4) q[hf] = ld_relaxed128(gp + QO + 32768 + 128 * hf);
        }
      }
    }
    int h, j, r;
    ffn_role(h, j, r);
    {
      REGION_IDS;
      mbar_wait(BAR(B_UVB));
      float d[12] = {};
      fence_regs(d);
      wg_fence();
#pragma unroll
      for (int k = 0; k < 15; k++) {
        if (k == 12) { wg_commit(); mbar_wait(BAR(B_UVE)); wg_fence(); }
        wg_ss8_10(d + 4 * (k % 3), mkdesc(DB + (k < 12 ? OFF_UV + 12288 * (k / 6) + 4096 * (k % 3) + 2048 * (k / 3 & 1) : OFF_UVE + 2048 * (k % 3)), 16, 1024, 1),
                  mkdesc(DB + OFF_CO + 64 * (k / 3), 32, 128, 0), 1);
      }
      wg_commit();
      const int row = (r & 14) + (lane >> 2 & 1);
      uint32_t* dst = &G->uv[4 * h + j][32 * row + 4 * ((2 * w ^ row) & 6) + (lane & 3)];
      const uint32_t tag = !(lane & 3);
      wg_wait<0>();
      fence_regs(d);
      if (elect()) { red_hint(G->hint[8][4 * h + j]); mbar_arrive(BAR(B_UVD)); }
      uint32_t x[6];
#pragma unroll
      for (int k = 0; k < 6; k++) asm volatile("movmatrix.sync.aligned.m8n8.trans.b16 %0, %1;" : "=r"(x[k]) : "r"(pack_bf16(d[2 * k], d[2 * k + 1])));
      if (lane < 8) {
#pragma unroll
        for (int k = 0; k < 6; k++) st_relaxed32(dst + 512 * w_block(r & 1, k >> 1) + ((4 * k ^ lane) & 4), set_tag(x[k], tag, epoch));
      }
    }
    {
      REGION_IDS;
      if (w == 0) {
        int it = 0;
#pragma unroll 1
        while (__any_sync(~0u, ld_relaxed32(G->hint[8][4 * h + j]) != 64 * epoch) && ++it < SPIN_LIMIT);
        if (elect()) { mbar_expect_tx(BAR(B_BX), 12288); bulk_load(base + OFF_BX, G->uv[4 * h + j], 12288, BAR(B_BX)); }
      }
      const uint32_t* sp = &G->st2[2 * r + (h ^ (w >> 1))][0][2 * (i0 & 63)];
      uint2 x[4];
      int it = 0;
#pragma unroll 1
      do {
#pragma unroll
        for (int k = 0; k < 4; k++) x[k] = ld_relaxed64(sp + 128 * k);
      } while (__any_sync(~0u, ((x[0].x ^ epoch) | (x[1].x ^ epoch) | (x[2].x ^ epoch) | (x[3].x ^ epoch)) & 1) && ++it < SPIN_LIMIT);
      float m, sd;
      ln_final((__uint_as_float(x[0].x) + __uint_as_float(x[1].x)) + (__uint_as_float(x[2].x) + __uint_as_float(x[3].x)),
               (__uint_as_float(x[0].y) + __uint_as_float(x[1].y)) + (__uint_as_float(x[2].y) + __uint_as_float(x[3].y)), m, sd);
      const uint32_t e = pack_bf16(-m, sd);
      sts128(base + OFF_AX + 16 * i0, e, e, e, e);
      sts32(base + OFF_RT + 4 * i0, __float_as_uint(rcpf(sd)));
      fence_async_smem();
#pragma unroll 1
      for (it = 0; it < SPIN_LIMIT; it++) {
        mbar_wait(BAR(B_BX), it & 1);
        uint32_t y = 0;
#pragma unroll
        for (int k = 0; k < 6; k++) y |= lds32(base + OFF_BX + 16 * i0 + 2048 * k) ^ epoch;
        if (bar_all(3, !(y & 1))) break;
        if (w == 0 && elect()) { mbar_expect_tx(BAR(B_BX), 12288); bulk_load(base + OFF_BX, G->uv[4 * h + j], 12288, BAR(B_BX)); }
      }
      arrive1(BAR(B_EXT));
      {
        uint2 g0, g1;
        int it = 0;
#pragma unroll 1
        do {
          g0 = ld_relaxed64(&G->modv[1][128 * j + i0]);
          g1 = ld_relaxed64(&G->modv[1][512 + 32 * j + lane]);
        } while (__any_sync(~0u, ((g0.x ^ epoch) | (g0.y ^ epoch) | (g1.x ^ epoch) | (g1.y ^ epoch)) & 1) && ++it < SPIN_LIMIT);
        const uint32_t ga = base + OFF_GB + 80 * (lane >> 1 & 3) + 2 * (lane & 1) + (lane >> 3) * 4;
        asm volatile("st.shared.u16 [%0], %1;" ::"r"(ga + 16 * (w ^ (j & 1))), "h"((uint16_t)(mod_sum(g0) >> 16)) : "memory");
        asm volatile("st.shared.u16 [%0], %1;" ::"r"(ga + 64), "h"((uint16_t)(mod_sum(g1) >> 16)) : "memory");
        arrive1(BAR(B_GB));
      }
      const int id = 16 * r + 4 * h + fslice(j, w);
#pragma unroll 1
      for (int q = w == 3 ? 3 : 0; q < 3; q++) {
        const int m = 3 * q + w;
        const uint4* src = G->hh + id * 1536 + 512 * q;
        it = 0;
#pragma unroll 1
        while (__any_sync(~0u, ld_relaxed32(&G->hhf[8 * id + 64 * (lane & 1) + q]) != 4 * epoch) && ++it < SPIN_LIMIT);
        mbar_wait(BAR(P.hid[2][m]));
        if (elect()) {
          bulk_load(base + OFF_A + h * ARING + P.hid[h][m], src, ASLOT, BAR(B_FULL + 23 + m));
          bulk_load(base + OFF_A + ARING - h * ARING + P.hid[h ^ 1][m], src + 8 * 1536, ASLOT, BAR(B_FULL + 23 + m));
        }
      }
    }
  } else {
    asm volatile("setmaxnreg.inc.sync.aligned.u32 224;");
    LAUNCHES;
    if (wg == 1) silu_vector(P.c, base);
    uint32_t par = EPOCH & 1;
    cluster_wait();
    {
      float acc[128];
      uint32_t A[64];
#pragma unroll
      for (int i = 0; i < 64; i++) A[i] = 0;
      int c = wg;
#pragma unroll 1
      for (uint64_t prog = P.cprog[wg]; prog; prog >>= 8) {
        REGION_IDS;
        const int s = prog & 7;
        if (s < 5) {
          const uint32_t a = base + tab(T_KV, s) + 128 * (lane & 3) + ((w ^ (lane & 3)) << 4) + 4 * (lane & 16) + (lane & 12), keep = ~(lane & 1), bit = par & lane;
          uint4* dst = G->xr + (128 * s + 64 * (bid & 1) + 8 * w + 2 * (lane & 16) + (lane >> 1 & 6)) * 256 + 255 - 4 * (bid >> 1) - (lane & 3);
          mbar_wait(BAR(B_KV));
          mbar_wait(BAR(B_KV + s));
          const uint4 wv = lds128(base + OFF_TAP + 512 * s + 64 * w + 16 * (lane & 16) + 4 * (lane & 12));
          uint32_t kk[11], r[8];
#pragma unroll
          for (int k = 0; k < 11; k++) kk[k] = k < 3 ? lds32((a ^ (64 * (k & 1))) + KV_H + 512 * k) : lds32((a ^ (64 * (~k & 1))) + 512 * (k - 3));
          if (elect()) red_hint(G->hint[s][4 * (bid & 1) + w]);
#pragma unroll
          for (int k = 0; k < 8; k++) r[k] = lds32((a ^ (64 * (k & 1))) + KV_V + 512 * k);
          const uint32_t w0 = __byte_perm(wv.x, wv.z, 0x5410), w1 = __byte_perm(wv.x, wv.z, 0x7632),
                         w2 = __byte_perm(wv.y, wv.w, 0x5410), w3 = __byte_perm(wv.y, wv.w, 0x7632);
#pragma unroll
          for (int k = 0; k < 8; k++) r[k] = bmul2(bfma2(kk[k + 3], w0, bfma2(kk[k + 2], w1, bfma2(kk[k + 1], w2, bmul2(kk[k], w3)))), r[k]);
          st_relaxed128(dst, (__byte_perm(r[7], r[6], 0x5410) & keep) | bit, __byte_perm(r[5], r[4], 0x5410), __byte_perm(r[3], r[2], 0x5410), __byte_perm(r[1], r[0], 0x5410));
          st_relaxed128(dst + 256, (__byte_perm(r[7], r[6], 0x7632) & keep) | bit, __byte_perm(r[5], r[4], 0x7632), __byte_perm(r[3], r[2], 0x7632), __byte_perm(r[1], r[0], 0x7632));
        }
        if (prog & 8) {
          float s0 = 0.f, s1 = 0.f, q0 = 0.f, q1 = 0.f;
          const uint32_t a = OFF_Q + 1024 * w + 128 * (lane & 7) + (((lane >> 3) ^ (lane & 7)) << 4);
          const uint32_t ra = mapa(base + OFF_ST + 128 * (bid & 1) + 64 * (lane & 1) + 16 * w + 8 * (lane >> 2), lane >> 1 & 1), rb = mapa(BAR(B_ST1), lane >> 1 & 1);
          if (w == 3 && elect()) mbar_expect_tx(BAR(B_ST1), 256);
#pragma unroll 1
          for (int k = 0; k < 5; k++) {
            mbar_wait(BAR(B_Q + k));
            const uint32_t o = opaque(base + 4096 * k);
            const uint4 x = lds128(o + a), y = lds128(o + (a ^ 64));
            const uint32_t e[8] = {x.x, x.y, x.z, x.w, y.x, y.y, y.z, y.w};
#pragma unroll
            for (int i = 0; i < 8; i++) { const float lo = bf_lo(e[i]), hi = bf_hi(e[i]); s0 += lo; s1 += hi; q0 = fmaf(lo, lo, q0); q1 = fmaf(hi, hi, q1); }
          }
          s0 += s1; q0 += q1;
          s0 += __shfl_xor_sync(~0u, s0, 8); q0 += __shfl_xor_sync(~0u, q0, 8);
          s0 += __shfl_xor_sync(~0u, s0, 16); q0 += __shfl_xor_sync(~0u, q0, 16);
          if (lane < 8) asm volatile("st.async.shared::cluster.mbarrier::complete_tx::bytes.v2.b32 [%0], {%1,%2}, [%3];" ::"r"(ra), "r"(__float_as_uint(s0)), "r"(__float_as_uint(q0)), "r"(rb) : "memory");
        }
        if (prog & 32) {
          const int L = 16 * w + (lane >> 2) + 2 * (lane & 3) - 7;
          const uint32_t fo = base + ((L & 1) ? F_O + 2 * (L + 1) : F_E + 2 * L);
          mbar_wait(BAR(B_FRDY + c));
          cload<0, 0>(A, fo + tab(T_F, c));
          cload<15, 1>(A, fo + tab(T_F, c));
          arrive1(BAR(B_FL + c));
        }
        if (!(prog & 64)) continue;
        uint32_t xo;
        if (P.turn >> c & 1) mbar_wait(BAR(B_TURN - 3 + c));
        if (c == 0) mbar_wait(BAR(P.c0));
#pragma unroll 1
        for (int it = 0; it < SPIN_LIMIT; it++) {
          xo = tab(T_X, opaque(c));
          mbar_wait(BAR(B_XR + c), it & 1);
          const uint32_t tag = lds32(base + xo + 32 * i0);
          wg_fence();
          csteps<0, 0>(acc, A, mkdesc(DB + xo, 16, 128, 0));
          csteps<15, 6>(acc, A, mkdesc(DB + xo, 16, 128, 0));
          wg_commit();
          if (bar_all(1 + wg, !((tag ^ par) & 1))) break;
          wg_wait<0>();
          if (w == 0 && elect()) { mbar_expect_tx(BAR(B_XR + c), 4096); bulk_load(base + xo, G->xr + (128 * c + bid) * 256, 4096, BAR(B_XR + c)); }
        }
        wg_fence();
        csteps<5, 1>(acc, A, mkdesc(DB + tab(T_X, opaque(c)), 16, 128, 0));
        wg_commit();
        if (c >= 2 && c < 4 && elect()) mbar_arrive(BAR(B_TURN - 2 + c));
        if (c >= 3) mbar_wait(BAR(B_PEMPTY + c - 3));
        wg_wait<0>();
        fence_regs(acc);
        const uint32_t pb = base + tab(T_P, c) + 4096 * w;
#pragma unroll
        for (int k = 0; k < 8; k++) {
          uint32_t p[4];
#pragma unroll
          for (int e = 0; e < 4; e++) { const int i = 4 * k + e; p[e] = i < 31 ? pack_bf16(acc[4 * i] + acc[4 * i + 6], acc[4 * i + 1] + acc[4 * i + 7]) : pack_bf16(acc[124], acc[125]); }
          if (k == 0 && (lane & 3) < w) p[0] = 0;
          stmatrix_x4_t(k == 0 ? pb + 16 * ((255 - lane + 2 * w) & 255) : pb + 16 * (255 - lane + 2 * w) - 512 * k, p[0], p[1], p[2], p[3]);
        }
        arrive1(BAR(B_PFULL + c));
        c += 2;
      }
    }
    if (wg) {
      REGION_IDS;
      if (bid >= P.ulo && bid < P.uhi) {
        named_bar(2, 128);
        mbar_wait(BAR(B_WM));
        mod_gemv(G, OFF_WM, bid, w, lane, par);
      }
      arrive1(BAR(B_G3));
    }
    uint32_t ck;
    { REGION_IDS; ck = base + OFF_A + wg * ARING + lane * 128 + (((2 * w) ^ (lane & 7)) << 4); }
    const uint32_t abd = DB + OFF_A + wg * ARING;
    auto a_tile = [&](int as, int n, bool first) {
#pragma unroll 1
      for (int it = 0; __any_sync(~0u, ((lds32(ck + as) ^ par) | (lds32(ck + as + (first ? 4096 : 256)) ^ par)) & 1) && it < SPIN_LIMIT; it++) {
        int h, j, r;
        ffn_role(h, j, r);
        if (elect()) {
          const uint32_t dst = base + OFF_A + wg * ARING + as;
          mbar_expect_tx(BAR(B_RETRY + wid), ASLOT);
          if (first) tma2d(dst, &maps.xs, 128 * r + 64 * (h ^ wg), 64 * n, BAR(B_RETRY + wid));
          else bulk_load(dst, G->hh + ((2 * r + (h ^ wg)) * 8 + 4 * h + fslice(j, n % 3)) * 1536 + (n / 3) * 512, ASLOT, BAR(B_RETRY + wid));
        }
        mbar_wait(BAR(B_RETRY + wid), par >> 1);
        par ^= 2;
      }
    };
    float acc[192];
    int ws = 0, as = 0;
#pragma unroll 1
    for (int u = 0; u < 20 - NT; u++) {
      mbar_wait(BAR(B_FULL + u));
      if (!(u & 1)) a_tile(as, u >> 1, true);
      wg_fence();
#pragma unroll
      for (int k = 0; k < 4; k++) wg_ss192_11(acc + 96 * (k & 1), mkdesc(abd + as + k / 2 * 2048, 16, 1024, 1), mkdesc(DB + ws + 12288 * (k & 1) + k / 2 * 2048, 4096, 1024, 1), u + k / 2);
      wg_commit();
      wg_wait<1>();
      if (elect()) mbar_arrive(BAR(B_EMPTY + u - 1));
      ws = next_slot(ws);
      as = as == 5 * ASLOT / 2 ? 0 : as + ASLOT / 2;
    }
    auto tail = [&](int v, int i) {
      const int u = 20 - NT + i / 2;
      if (i < 2 * NT) wg_ss192_11(acc + 96 * v, mkdesc(opaque(abd) + u % 6 * 4096 + (i & 1) * 2048, 16, 1024, 1), mkdesc(DB + u % 5 * WSLOT + (i & 1) * 2048 + 12288 * v, 4096, 1024, 1), 1);
      if (i == 2 * NT) wg_ss192_01(acc + 96 * v, mkdesc(DB + OFF_AX + 1024 * opaque(wg), 0, 128, 0), mkdesc(DB + OFF_BX + 6144 * v, 2048, 1024, 1), 1);
    };
#pragma unroll
    for (int u = 20 - NT; u <= 20; u++) {
      mbar_wait(BAR(u < 20 ? B_FULL + u : B_EXT));
      if (u == 16 || u == 18) a_tile(u % 6 * 4096, u >> 1, true);
      wg_fence();
      tail(0, 2 * (u + NT - 20));
      tail(0, 2 * (u + NT - 20) + 1);
      wg_commit();
      if (u == 20 - NT) { wg_wait<1>(); if (elect()) mbar_arrive(BAR(B_EMPTY + u - 1)); }
    }
    float o[80];
    uint32_t fr[3][16], bo;
    {
      int h, j, r;
      ffn_role(h, j, r);
      REGION_IDS;
      const float r0 = 0.5f * __uint_as_float(lds32(base + OFF_RT + 256 * wg + 64 * w + (lane & 28))), r1 = 0.5f * __uint_as_float(lds32(base + OFF_RT + 256 * wg + 64 * w + 32 + (lane & 28)));
      const int id = (2 * r + (h ^ wg)) * 8 + 4 * h + j;
      uint4* const hdst = G->hh + id * 1536 + 128 * w + (lane ^ lane >> 3);
      const uint32_t keep = ~(~lane & 1), bit = par & ~keep;
      bo = 1024 + ((j & 1) << 23);
      auto own = [&](int i) { wg_rs160_1(o, fr[i >> 2] + 4 * (i & 3), mkdesc(DB + (5 + i / 4) % 6 * WSLOT + (i & 3) * 2048, 8192, bo, 1), i); };
      auto gate = [&](float* g, int d) {
#pragma unroll
        for (int e = 0; e < 4; e++) { g[e] *= e < 2 ? r0 : r1; g[e + d] *= g[e]; asm("tanh.approx.f32 %0, %0;" : "+f"(g[e])); }
      };
      auto mix = [&](uint32_t* x, const float* g, int d) {
        x[0] = pack_bf16(fmaf(g[d], g[0], g[d]), fmaf(g[d + 1], g[1], g[d + 1]));
        x[1] = pack_bf16(fmaf(g[d + 2], g[2], g[d + 2]), fmaf(g[d + 3], g[3], g[d + 3]));
      };
      auto hint = [&](int v) { asm volatile("{.reg .pred p; setp.eq.u32 p, %1, 0; @p red.relaxed.gpu.global.add.u32 [%0], 1;}" ::"l"(&G->hhf[id * 8 + v]), "r"(lane) : "memory"); };
      auto put = [&](int v, int k) {
        uint32_t* x = fr[v] + 2 * k;
        const uint32_t t0 = (x[k / 2] & keep) | bit, t1 = (x[5 + k / 2] & keep) | bit;
        if (!v) { x[k / 2] = t0; x[5 + k / 2] = t1; }
        st_relaxed128(hdst + 512 * v + 8 * k, k ? x[0] : t0, k ? t0 : x[2], x[4], x[6]);
        st_relaxed128(hdst + 512 * v + 8 * k + 64, x[1], x[3], k ? x[5] : t1, k ? t1 : x[7]);
      };
      auto move = [&](uint32_t* x) {
#pragma unroll
        for (int k = 0; k < 16; k++) asm volatile("mul.rn.f32 %0, %0, %1;" : "+r"(x[k]) : "f"(P.one));
      };
      wg_fence();
      tail(1, 0);
      tail(1, 1);
      wg_commit();
      wg_wait<1>();
#pragma unroll
      for (int k = 0; k < 96; k++) asm volatile("" : "+f"(acc[k])::"memory");
      if (elect()) mbar_arrive(BAR(B_EMPTY + 18));
      gate(acc + 28, 32);
#pragma unroll
      for (int k = 7; k >= 0; k--) {
        if (k >= 8 - 2 * NT) split(P.ulo, k);
        if (k > 8 - 2 * NT) tail(1, 9 - k);
        if (k == 9 - 2 * NT) wg_commit();
        if (k) gate(acc + 4 * k - 4, 32);
        mix(fr[0] + 2 * k, acc + 4 * k, 32);
        if (k == 1) hint(0);
        if (!(k & 3)) put(0, k);
      }
      move(fr[0]);
      split(P.ulo, 14);
      wg_wait<0>();
#pragma unroll
      for (int k = 96; k < 192; k++) asm volatile("" : "+f"(acc[k])::"memory");
      if (elect()) mbar_arrive(BAR(B_EMPTY + 19));
#pragma unroll
      for (int k = 7; k >= 0; k--) gate(acc + 64 + 4 * k, 96);
      mbar_wait(BAR(B_FULL + 20));
      mbar_wait(BAR(B_FULL + 21));
#pragma unroll
      for (int k = 7; k >= 0; k--) mix(fr[1] + 2 * k, acc + 64 + 4 * k, 96);
#pragma unroll
      for (int k = 0; k < 4; k++) pin4(P.ulo, fr[1] + 4 * k);
      wg_fence();
      own(0);
      own(1);
      split(P.ulo, 15);
      put(1, 4);
      hint(1);
      own(2);
      put(1, 0);
      own(3);
      wg_commit();
      gate(acc + 124, 32);
#pragma unroll
      for (int k = 7; k >= 0; k--) {
        if (k & 1 || k == 6) split(P.ulo, 16 + k);
        if (!(k & 1)) own(7 - k / 2);
        if (k == 4 || k == 0) wg_commit();
        if (k == 4) { wg_wait<1>(); if (elect()) mbar_arrive(BAR(B_EMPTY + 20)); }
        if (k) gate(acc + 92 + 4 * k, 32);
        mix(fr[2] + 2 * k, acc + 96 + 4 * k, 32);
        if (k == 1) hint(2);
        if (!(k & 3)) put(2, k);
      }
      mbar_wait(BAR(B_FULL + 22));
      wg_fence();
#pragma unroll
      for (int i = 8; i < 12; i++) own(i);
      wg_commit();
      wg_wait<1>();
      if (elect()) mbar_arrive(BAR(B_EMPTY + 21));
      ck = base + OFF_A + wg * ARING + 2048 * w + 516 * (lane >> 3) + 144 * (lane >> 2 & 1) + 32 * (lane & 3);
    }
    uint32_t x1[40];
    if (!wg) {
      REGION_IDS;
      const uint32_t xa = base + (lane >> 4) * 1024 + (lane & 7) * 128 + (((2 * w + ((lane >> 3) & 1)) ^ (lane & 7)) << 4);
      mbar_wait(BAR(B_FULL + 32));
#pragma unroll
      for (int k = 0; k < 10; k++) ldmatrix_x4_t(x1 + 4 * k, xa + (k < 6 ? OFF_X1 + k / 2 * WSLOT + (k & 1) * 2048 : OFF_SX + 2048 * (k - 6)));
    }
#pragma unroll 1
    for (int u = 23; u < (wg ? 32 : LAG2); u++) {
      as = P.hid[wg][u - 23];
      const uint64_t wd = mkdesc(0, 0, bo, 1) | P.w2t[u - 20].x;
      mbar_wait(BAR(B_FULL + u));
      a_tile(as, u - 23, false);
      wg_fence();
#pragma unroll
      for (int kk = 0; kk < 4; kk++) wg_ss160_01(o, mkdesc(abd + as + kk / 2 * 512 + (kk & 1) * 32, 16, 1024, 2), wd + kk * 128, 1);
      wg_commit();
      if (u == 31 && elect()) mbar_arrive(BAR(B_LAG));
      wg_wait<1>();
      if (elect()) mbar_arrive(BAR(B_EMPTY + u - 1));
    }
    int h, j, r;
    ffn_role(h, j, r);
    REGION_IDS;
    const uint32_t xb = base + OFF_XCH + 5120 * w;
    if (wg) {
      const uint32_t rdst = mapa(xb + 16 * lane, h ^ 1), rbar = mapa(BAR(B_FULL), h ^ 1);
      mbar_wait(BAR(B_XFREE));
      wg_wait<0>();
      fence_regs(o);
#pragma unroll
      for (int k = 0; k < 10; k++)
        asm volatile("st.async.shared::cluster.mbarrier::complete_tx::bytes.v4.b32 [%0], {%1,%2,%3,%4}, [%5];" ::"r"(rdst + 512 * k), "r"(pack_bf16(o[8 * k], o[8 * k + 1])),
                     "r"(pack_bf16(o[8 * k + 2], o[8 * k + 3])), "r"(pack_bf16(o[8 * k + 4], o[8 * k + 5])), "r"(pack_bf16(o[8 * k + 6], o[8 * k + 7])), "r"(rbar + 8 * (k / 4)) : "memory");
    } else {
      uint32_t gr[40];
      {
        const float r0 = __uint_as_float(lds32(base + OFF_RT + 64 * w + (lane & 28))), r1 = __uint_as_float(lds32(base + OFF_RT + 64 * w + 32 + (lane & 28)));
        const uint32_t p0 = pack_bf16(r0, r0), p1 = pack_bf16(r1, r1);
        mbar_wait(BAR(B_GB));
#pragma unroll
        for (int k = 0; k < 5; k++) {
          const uint4 g = lds128(base + OFF_GB + 80 * (lane & 3) + 16 * k);
          gr[8 * k] = bmul2(g.x, p0); gr[8 * k + 1] = bmul2(g.x, p1); gr[8 * k + 2] = bmul2(g.y, p0); gr[8 * k + 3] = bmul2(g.y, p1);
          gr[8 * k + 4] = bmul2(g.z, p0); gr[8 * k + 5] = bmul2(g.z, p1); gr[8 * k + 6] = bmul2(g.w, p0); gr[8 * k + 7] = bmul2(g.w, p1);
        }
      }
      wg_wait<0>();
      if (elect()) mbar_arrive(BAR(B_EMPTY + LAG2 - 1));
#pragma unroll 1
      for (int u = LAG2; u < 32; u++) {
        mbar_wait(BAR(B_FULL + u));
        a_tile(P.hid[0][u - 23], u - 23, false);
      }
      auto da = [&](int i) { return mkdesc(DB + hid_at(i / 4 + LAG2 - 23, 0) + (i & 2) * 256 + (i & 1) * 32, 16, 1024, 2); };
      auto db = [&](int i, int b) { return mkdesc(DB + w2_at(i / 4 + LAG2 - 20) + b * w2_step(i / 4 + LAG2 - 20) + (i & 3) * 2048, w2_step(i / 4 + LAG2 - 20), bo, 1); };
      const int row = 128 * r + 64 * h + 16 * w;
      auto merge = [&](int e) {
        if (e % 4 == 0) mbar_wait_cluster(BAR(B_FULL + e / 4), 1);
        const uint4 p = lds128(xb + 16 * lane + 512 * e);
        x1[4 * e] = bfma2(gr[4 * e], p.x, x1[4 * e]); x1[4 * e + 1] = bfma2(gr[4 * e + 1], p.y, x1[4 * e + 1]);
        x1[4 * e + 2] = bfma2(gr[4 * e + 2], p.z, x1[4 * e + 2]); x1[4 * e + 3] = bfma2(gr[4 * e + 3], p.w, x1[4 * e + 3]);
      };
      auto out = [&](int k) {
        const float* v = o + 8 * k;
        uint32_t y[4];
#pragma unroll
        for (int e = 0; e < 4; e++) y[e] = bfma2(gr[4 * k + e], pack_bf16(v[2 * e], v[2 * e + 1]), x1[4 * k + e]);
        stmatrix_x4(k < 8 ? xb + 2048 * (k >> 2) + (lane & 15) * 128 + (((2 * (k & 3) + (lane >> 4)) ^ (lane & 7) ^ 4 * (j & 1)) << 4)
                          : xb + 4096 + (lane & 15) * 64 + (((2 * (k & 1) + (lane >> 4)) ^ (lane >> 1 & 3)) << 4), y[0], y[1], y[2], y[3]);
        if ((k & 3) == 3 || k == 9) {
          fence_async_smem();
          __syncwarp();
          if (lane == 0) tma2d_store(k < 8 ? &maps.outa : &maps.outb, k < 8 ? 128 * j + 64 * (k >> 2) : 512 + 32 * j, row, xb + 2048 * (k >> 2));
        }
      };
      constexpr int ND = 128 - 4 * LAG2;
      mbar_wait(BAR(B_LAG));
      wg_fence();
#pragma unroll
      for (int i = 0; i < ND; i++) wg_ss160_01(o, da(i), db(i, 0), 1);
      wg_commit();
#pragma unroll
      for (int e = 0; e < MG; e++) merge(e);
      __syncwarp();
      wg_wait<0>();
      fence_regs(o);
#pragma unroll
      for (int k = 0; k < 10; k++) {
        if (k >= MG && k % 4 == 0) {
#pragma unroll
          for (int e = k; e < min(k + 4, 10); e++) merge(e);
          __syncwarp();
        }
        out(k);
      }
      if (lane == 0) { bulk_commit(); bulk_wait_read(); }
    }
  }
}

typedef CUresult (*EncFn)(CUtensorMap*, CUtensorMapDataType, cuuint32_t, void*, const cuuint64_t*, const cuuint64_t*, const cuuint32_t*,
                          const cuuint32_t*, CUtensorMapInterleave, CUtensorMapSwizzle, CUtensorMapL2promotion, CUtensorMapFloatOOBfill);
static int enc_err = 0;
static void enc(EncFn fn, CUtensorMap* m, const void* p, int rank, const cuuint64_t* gd, const cuuint64_t* gs, const cuuint32_t* bd, CUtensorMapSwizzle sw) {
  cuuint32_t es[5] = {1, 1, 1, 1, 1};
  enc_err = 2 * enc_err + (fn(m, CU_TENSOR_MAP_DATA_TYPE_BFLOAT16, rank, (void*)p, gd, gs, bd, es, CU_TENSOR_MAP_INTERLEAVE_NONE, sw,
                              CU_TENSOR_MAP_L2_PROMOTION_L2_128B, CU_TENSOR_MAP_FLOAT_OOB_FILL_NONE) != CUDA_SUCCESS);
}

extern "C" void kernel_launch(void* const* d_in, const int* in_sizes, int n_in, void* d_out, int out_size) {
  const bf16 *q = (const bf16*)d_in[0], *k = (const bf16*)d_in[1], *v = (const bf16*)d_in[2], *shift = (const bf16*)d_in[3],
             *ssmk = (const bf16*)d_in[4], *ssmd = (const bf16*)d_in[5], *w1 = (const bf16*)d_in[7], *w3 = (const bf16*)d_in[8],
             *w2 = (const bf16*)d_in[9], *c = (const bf16*)d_in[10], *wmod = (const bf16*)d_in[11];
  EncFn fn = nullptr;
  cudaDriverEntryPointQueryResult qr;
  cudaGetDriverEntryPoint("cuTensorMapEncodeTiled", (void**)&fn, cudaEnableDefault, &qr);
  Scratch* pg;
  cudaGetSymbolAddress((void**)&pg, g_s);
  Maps maps;
  enc_err = 0;
  const CUtensorMapSwizzle S128 = CU_TENSOR_MAP_SWIZZLE_128B;
  { cuuint64_t gd[3] = {D_, S_ / 8, 8}, gs[2] = {D_ * 16, D_ * 2}; cuuint32_t b[3] = {64, 4, 8};
    enc(fn, &maps.km, k, 3, gd, gs, b, S128);
    enc(fn, &maps.v, v, 3, gd, gs, b, S128);
    enc(fn, &maps.q, q, 3, gd, gs, b, S128);
    b[2] = 3;
    enc(fn, &maps.kh, k, 3, gd, gs, b, S128); }
  { cuuint64_t gd[3] = {256, 2, 5}, gs[2] = {512, 1024}; cuuint32_t b[3] = {256, 1, 5};
    enc(fn, &maps.tap, shift, 3, gd, gs, b, CU_TENSOR_MAP_SWIZZLE_NONE); }
  { cuuint64_t gd[3] = {6 * D_, D_, 1}, gs[2] = {6 * D_ * 2, 6 * D_ * 2 * D_}; cuuint32_t b[3] = {64, 64, 1};
    enc(fn, &maps.wm, wmod, 3, gd, gs, b, S128); }
  { cuuint64_t gd[3] = {64, D_, F_ / 64}, gs[2] = {F_ * 2, 128}; cuuint32_t b[3] = {64, 32, 3};
    enc(fn, &maps.w1, w1, 3, gd, gs, b, S128);
    enc(fn, &maps.w3, w3, 3, gd, gs, b, S128);
    b[1] = 16;
    enc(fn, &maps.w1e, w1, 3, gd, gs, b, S128);
    enc(fn, &maps.w3e, w3, 3, gd, gs, b, S128);
    b[1] = 32; b[2] = 1;
    enc(fn, &maps.w1s, w1, 3, gd, gs, b, S128);
    enc(fn, &maps.w3s, w3, 3, gd, gs, b, S128); }
  { cuuint64_t gd[2] = {S_, D_}, gs[1] = {S_ * 2}; cuuint32_t b1[2] = {64, 64}, b2[2] = {64, 32};
    enc(fn, &maps.xs, pg->xs, 2, gd, gs, b1, S128);
    gd[1] = 2 * D_;
    enc(fn, &maps.x1b, pg->x1, 2, gd, gs, b2, S128);
    enc(fn, &maps.x1s, pg->x1, 2, gd, gs, b2, CU_TENSOR_MAP_SWIZZLE_NONE); }
  { cuuint64_t gd[5] = {D_, 2, 4, 4, 48}, gs[4] = {D_ * 2, D_ * 4, D_ * 16, D_ * 64}; cuuint32_t b[5] = {64, 2, 4, 4, 2};
    enc(fn, &maps.w2a, w2, 5, gd, gs, b, S128);
    gs[1] = D_ * 16; gs[2] = D_ * 4;
    enc(fn, &maps.w2b, w2, 5, gd, gs, b, S128); }
  { cuuint64_t gd[2] = {D_, S_}, gs[1] = {D_ * 2}; cuuint32_t b1[2] = {64, 16}, b2[2] = {32, 16};
    enc(fn, &maps.outa, d_out, 2, gd, gs, b1, S128);
    enc(fn, &maps.outb, d_out, 2, gd, gs, b2, CU_TENSOR_MAP_SWIZZLE_64B); }
  if (enc_err) return;
  cudaFuncSetAttribute(k_fused, cudaFuncAttributeMaxDynamicSharedMemorySize, SMEM_BYTES);
  cudaLaunchConfig_t cfg = {132, 512, SMEM_BYTES};
  cudaLaunchAttribute at = {cudaLaunchAttributeClusterDimension};
  at.val.clusterDim.x = 2; at.val.clusterDim.y = at.val.clusterDim.z = 1;
  cfg.attrs = &at; cfg.numAttrs = 1;
  int nc = 0;
  cudaOccupancyMaxActiveClusters(&nc, k_fused, &cfg);
  Ptrs P = {ssmk, c, ssmd, pg, 0x48DCBA9ull, {0x676760, 0x64620F01}, 0, 5000, 19, 48, 100, B_KV, 0, 8, 1, 1, 0xD7010, 1.f};
  const char* sched = "k10v14f04q04q14q24q34q44k24v24f14k34v34f24k44v44f34f44n04n02n04n06n06n06";
  int t = 1000, pace = 420;
  for (int e = 0; e < NE; e++) {
    const char x = sched[3 * e];
    const int r = sched[3 * e + 1] - '0', kind = x == 'k' ? 0 : x == 'v' ? 1 : x == 'q' ? 2 : x == 'f' ? 3 : 4;
    t += (sched[3 * e + 2] - '0') * pace / 4;
    P.sched[e] = make_uint2(t | kind << 16 | r << 20, (kind < 2 ? tab(T_KV, r) + kind * KV_V : kind == 2 ? OFF_Q + 4096 * r : tab(T_F, r) + F_E) | (r + (kind < 2 ? B_KV : kind == 2 ? B_Q : B_FRAW)) << 18);
  }
  for (int u = 0; u < 5; u++) P.wt[u] = 9000 + 700 * u;
  const int dep[5] = {B_FL + 1, B_FL + 2, B_PFULL + 2, B_G3, B_PEMPTY + 2};
  for (int u = 0; u < 20; u++) P.wdep[u] = u % 5 * WSLOT | (~u & 1) << 12 | (u < 5 ? dep[u] : B_EMPTY + u - 5);
  for (int v = 0; v < 12; v++) P.w2t[v] = make_uint2(w2_desc(v), v ? B_EMPTY + (v > 5 ? 15 + v : v > 3 ? 14 + v : v > 1 ? 16 : 15) : B_UVD);
  for (int m = 0; m < 9; m++) { P.hid[0][m] = hid_at(m, 0) - OFF_A; P.hid[1][m] = hid_at(m, 1) - OFF_A - ARING; P.hid[2][m] = B_EMPTY + 19 + (m > 2 ? m : m / 2); }
  if (nc < 66) { P.boff = 128; k_fused<<<4, 512, SMEM_BYTES, cudaStreamPerThread>>>(P, maps); P.boff = 0; }
  k_fused<<<nc < 66 ? 128 : 132, 512, SMEM_BYTES, cudaStreamPerThread>>>(P, maps);
}
```

```cpp
#include <cuda_runtime.h>
#include <cuda.h>
#include <cuda_bf16.h>
#include <stdint.h>
#include <stdlib.h>

typedef __nv_bfloat16 bf16;
constexpr int S_ = 2048, D_ = 640, F_ = 1536;

struct Scratch {
  uint32_t st1[2][1024];
  uint32_t st2[32][4][128];
  uint2 modc[128][32];
  uint2 modv[3][D_];
  uint32_t uv[8][3072];
  unsigned hint[9][8][32];
  unsigned xsh[5][8][32], hhf[256 * 8];
  uint4 xr[D_ * 256];
  uint4 qt[D_ * 256];
  uint4 xs[D_ * 256];
  uint4 x1[2][D_ * 256];
  uint4 hh[32 * 8 * 1536];
};
__device__ __align__(1024) Scratch g_s;

__device__ __forceinline__ uint32_t smem_u32(const void* p) { return (uint32_t)__cvta_generic_to_shared(p); }
__device__ __forceinline__ void mbar_expect_tx(uint32_t b, uint32_t n) { asm volatile("mbarrier.arrive.expect_tx.shared::cta.b64 _, [%0], %1;" ::"r"(b), "r"(n) : "memory"); }
__device__ __forceinline__ void mbar_arrive(uint32_t b) { asm volatile("mbarrier.arrive.shared::cta.b64 _, [%0];" ::"r"(b) : "memory"); }
__device__ __forceinline__ void mbar_arrive2(uint32_t b) { asm volatile("mbarrier.arrive.shared::cta.b64 _, [%0], 2;" ::"r"(b) : "memory"); }
__device__ __forceinline__ uint32_t mapa(uint32_t a, uint32_t cta) { uint32_t r; asm volatile("mapa.shared::cluster.u32 %0, %1, %2;" : "=r"(r) : "r"(a), "r"(cta)); return r; }
__device__ __forceinline__ void mbar_arrive_remote(uint32_t rb) { asm volatile("mbarrier.arrive.shared::cluster.b64 _, [%0];" ::"r"(rb) : "memory"); }
constexpr int SPIN_LIMIT = 1 << 16;
template <int N> __device__ __forceinline__ void mbar_init(uint32_t b, uint32_t count) {
#pragma unroll
  for (int i = 0; i < N; i++) asm volatile("mbarrier.init.shared::cta.b64 [%0], %1;" ::"r"(b + 8 * i), "r"(count) : "memory");
}
__device__ __forceinline__ bool elect() { uint32_t p; asm volatile("{.reg .pred q; elect.sync _|q, 0xffffffff; selp.u32 %0, 1, 0, q;}" : "=r"(p)); return p; }
__device__ __forceinline__ void arrive1(uint32_t b) { __syncwarp(); if (elect()) mbar_arrive(b); }
__device__ __forceinline__ bool mbar_test(uint32_t b) {
  uint32_t ok;
  asm volatile("{.reg .pred p; mbarrier.test_wait.parity.shared::cta.b64 p, [%1], 0; selp.u32 %0,1,0,p;}" : "=r"(ok) : "r"(b) : "memory");
  return ok;
}
#define WAIT_LOOP(sem) "{.reg .pred p; mov.u32 %0, 0; W: mbarrier.try_wait.parity" sem ".shared::cta.b64 p, [%1], %2; @p bra.uni D; add.u32 %0, %0, 1; setp.lt.u32 p, %0, %3; @p bra.uni W; D:}"
__device__ __forceinline__ void mbar_wait(uint32_t b, uint32_t ph = 0) {
  int it;
  asm volatile(WAIT_LOOP("") : "=&r"(it) : "r"(b), "r"(ph), "n"(SPIN_LIMIT) : "memory");
}
__device__ __forceinline__ void mbar_wait_cluster(uint32_t b, uint32_t ph = 0) {
  int it;
  asm volatile(WAIT_LOOP(".acquire.cluster") : "=&r"(it) : "r"(b), "r"(ph), "n"(SPIN_LIMIT) : "memory");
}
__device__ __forceinline__ void wait_clock(uint32_t t) {
  asm volatile("{.reg .pred p; .reg .s32 d; W: mov.u32 d, %%clock; sub.s32 d, d, %0; setp.lt.s32 p, d, 0; @p bra.uni W;}" ::"r"(t) : "memory");
}
__device__ __forceinline__ void tma2d(uint32_t dst, const CUtensorMap* m, int c0, int c1, uint32_t bar) {
  asm volatile("cp.async.bulk.tensor.2d.shared::cluster.global.mbarrier::complete_tx::bytes [%0], [%1, {%3,%4}], [%2];" ::"r"(dst), "l"(m), "r"(bar), "r"(c0), "r"(c1) : "memory");
}
__device__ __forceinline__ void tma3d(uint32_t dst, const CUtensorMap* m, int c0, int c1, int c2, uint32_t bar) {
  asm volatile("cp.async.bulk.tensor.3d.shared::cluster.global.mbarrier::complete_tx::bytes [%0], [%1, {%3,%4,%5}], [%2];" ::"r"(dst), "l"(m), "r"(bar), "r"(c0), "r"(c1), "r"(c2) : "memory");
}
__device__ __forceinline__ void tma5d(uint32_t dst, const CUtensorMap* m, int c0, int c4, uint32_t bar) {
  asm volatile("cp.async.bulk.tensor.5d.shared::cluster.global.mbarrier::complete_tx::bytes [%0], [%1, {%4,%3,%3,%3,%5}], [%2];" ::"r"(dst), "l"(m), "r"(bar), "r"(0), "r"(c0), "r"(c4) : "memory");
}
__device__ __forceinline__ void tma2d_store(const CUtensorMap* m, int c0, int c1, uint32_t src) {
  asm volatile("cp.async.bulk.tensor.2d.global.shared::cta.bulk_group [%0, {%2,%3}], [%1];" ::"l"(m), "r"(src), "r"(c0), "r"(c1) : "memory");
}
__device__ __forceinline__ void bulk_load(uint32_t dst, const void* src, uint32_t bytes, uint32_t bar) {
  asm volatile("cp.async.bulk.shared::cluster.global.mbarrier::complete_tx::bytes [%0], [%1], %2, [%3];" ::"r"(dst), "l"(src), "r"(bytes), "r"(bar) : "memory");
}
__device__ __forceinline__ void prefetch_map(const CUtensorMap* m) { asm volatile("prefetch.tensormap [%0];" ::"l"(m) : "memory"); }
__device__ __forceinline__ void bulk_commit() { asm volatile("cp.async.bulk.commit_group;" ::: "memory"); }
__device__ __forceinline__ void bulk_wait_read() { asm volatile("cp.async.bulk.wait_group.read 0;" ::: "memory"); }
__device__ __forceinline__ void fence_async_smem() { asm volatile("fence.proxy.async.shared::cta;" ::: "memory"); }
__device__ __forceinline__ void fence_async_all() { asm volatile("fence.proxy.async.global;" ::: "memory"); }
__device__ __forceinline__ void named_bar(int id, int n) { asm volatile("bar.sync %0, %1;" ::"r"(id), "r"(n) : "memory"); }
__device__ __forceinline__ bool bar_all(int id, bool v) {
  uint32_t r;
  asm volatile("{.reg .pred p, q; setp.ne.u32 p, %2, 0; bar.red.and.pred q, %1, 128, p; selp.u32 %0, 1, 0, q;}" : "=r"(r) : "r"(id), "r"((uint32_t)v) : "memory");
  return __all_sync(~0u, r);
}
__device__ __forceinline__ void cluster_wait() { asm volatile("barrier.cluster.wait.aligned;" ::: "memory"); }
__device__ __forceinline__ void wg_fence() { asm volatile("wgmma.fence.sync.aligned;" ::: "memory"); }
__device__ __forceinline__ void wg_commit() { asm volatile("wgmma.commit_group.sync.aligned;" ::: "memory"); }
template <int N> __device__ __forceinline__ void wg_wait() { asm volatile("wgmma.wait_group.sync.aligned %0;" ::"n"(N) : "memory"); }
template <int N> __device__ __forceinline__ void fence_regs(float (&a)[N]) {
#pragma unroll
  for (int i = 0; i < N; i++) asm volatile("" : "+f"(a[i])::"memory");
}
template <int N> __device__ __forceinline__ void fence_n(float* a) {
#pragma unroll
  for (int i = 0; i < N; i++) asm volatile("" : "+f"(a[i])::"memory");
}
__device__ __forceinline__ uint64_t mkdesc(uint32_t addr, uint32_t lbo, uint32_t sbo, uint32_t swz) {
  uint32_t lo = (addr >> 4) | ((lbo >> 4) << 16), hi = (sbo >> 4) | (swz << 30);
  return ((uint64_t)hi << 32) | lo;
}
__device__ __forceinline__ void stmatrix_x4(uint32_t a, uint32_t r0, uint32_t r1, uint32_t r2, uint32_t r3) {
  asm volatile("stmatrix.sync.aligned.m8n8.x4.shared.b16 [%0], {%1,%2,%3,%4};" ::"r"(a), "r"(r0), "r"(r1), "r"(r2), "r"(r3) : "memory");
}
__device__ __forceinline__ void stmatrix_x4_t(uint32_t a, uint32_t r0, uint32_t r1, uint32_t r2, uint32_t r3) {
  asm volatile("stmatrix.sync.aligned.m8n8.x4.trans.shared.b16 [%0], {%1,%2,%3,%4};" ::"r"(a), "r"(r0), "r"(r1), "r"(r2), "r"(r3) : "memory");
}
__device__ __forceinline__ void ldmatrix_x4_t(uint32_t* r, uint32_t a) {
  asm volatile("ldmatrix.sync.aligned.m8n8.x4.trans.shared.b16 {%0,%1,%2,%3}, [%4];" : "=r"(r[0]), "=r"(r[1]), "=r"(r[2]), "=r"(r[3]) : "r"(a) : "memory");
}
__device__ __forceinline__ uint32_t lds32(uint32_t a) { uint32_t v; asm volatile("ld.shared.b32 %0, [%1];" : "=r"(v) : "r"(a) : "memory"); return v; }
__device__ __forceinline__ uint2 lds64(uint32_t a) { uint2 v; asm volatile("ld.shared.v2.b32 {%0,%1}, [%2];" : "=r"(v.x), "=r"(v.y) : "r"(a) : "memory"); return v; }
__device__ __forceinline__ uint4 lds128(uint32_t a) { uint4 v; asm volatile("ld.shared.v4.b32 {%0,%1,%2,%3}, [%4];" : "=r"(v.x), "=r"(v.y), "=r"(v.z), "=r"(v.w) : "r"(a) : "memory"); return v; }
__device__ __forceinline__ void sts32(uint32_t a, uint32_t v) { asm volatile("st.shared.b32 [%0], %1;" ::"r"(a), "r"(v) : "memory"); }
__device__ __forceinline__ void sts64(uint32_t a, uint32_t x, uint32_t y) { asm volatile("st.shared.v2.b32 [%0], {%1,%2};" ::"r"(a), "r"(x), "r"(y) : "memory"); }
__device__ __forceinline__ void sts128(uint32_t a, uint32_t x, uint32_t y, uint32_t z, uint32_t w) { asm volatile("st.shared.v4.b32 [%0], {%1,%2,%3,%4};" ::"r"(a), "r"(x), "r"(y), "r"(z), "r"(w) : "memory"); }
__device__ __forceinline__ uint4 ld_relaxed128(const void* p) { uint4 v; asm volatile("ld.relaxed.gpu.global.v4.u32 {%0,%1,%2,%3}, [%4];" : "=r"(v.x), "=r"(v.y), "=r"(v.z), "=r"(v.w) : "l"(p) : "memory"); return v; }
__device__ __forceinline__ uint2 ld_relaxed64(const void* p) { uint2 v; asm volatile("ld.relaxed.gpu.global.v2.u32 {%0,%1}, [%2];" : "=r"(v.x), "=r"(v.y) : "l"(p) : "memory"); return v; }
__device__ __forceinline__ uint32_t ld_relaxed32(const void* p) { uint32_t v; asm volatile("ld.relaxed.gpu.global.u32 %0, [%1];" : "=r"(v) : "l"(p) : "memory"); return v; }
__device__ __forceinline__ void st_relaxed128(void* p, uint32_t x, uint32_t y, uint32_t z, uint32_t w) { asm volatile("st.relaxed.gpu.global.v4.u32 [%0], {%1,%2,%3,%4};" ::"l"(p), "r"(x), "r"(y), "r"(z), "r"(w) : "memory"); }
__device__ __forceinline__ void st_relaxed32(void* p, uint32_t x) { asm volatile("st.relaxed.gpu.global.u32 [%0], %1;" ::"l"(p), "r"(x) : "memory"); }
__device__ __forceinline__ void red_hint(unsigned* p) { asm volatile("red.relaxed.gpu.global.add.u32 [%0], 1;" ::"l"(p) : "memory"); }
__device__ __forceinline__ void publish(uint32_t* p, uint32_t x) { asm volatile("{.reg .b32 t; atom.relaxed.gpu.global.exch.b32 t, [%0], %1;}" ::"l"(p), "r"(x) : "memory"); }
__device__ __forceinline__ uint32_t ldg32(const void* p) { uint32_t v; asm volatile("ld.global.nc.L1::no_allocate.b32 %0, [%1];" : "=r"(v) : "l"(p)); return v; }
__device__ __forceinline__ uint32_t pack_bf16(float lo, float hi) { uint32_t r; asm("cvt.rn.bf16x2.f32 %0, %1, %2;" : "=r"(r) : "f"(hi), "f"(lo)); return r; }
__device__ __forceinline__ float bf_lo(uint32_t v) { return __uint_as_float(v << 16); }
__device__ __forceinline__ float bf_hi(uint32_t v) { return __uint_as_float(v & 0xFFFF0000u); }
__device__ __forceinline__ uint32_t bmul2(uint32_t a, uint32_t b) { uint32_t r; asm("mul.rn.bf16x2 %0, %1, %2;" : "=r"(r) : "r"(a), "r"(b)); return r; }
__device__ __forceinline__ uint32_t badd2(uint32_t a, uint32_t b) { uint32_t r; asm("add.rn.bf16x2 %0, %1, %2;" : "=r"(r) : "r"(a), "r"(b)); return r; }
__device__ __forceinline__ uint32_t bfma2(uint32_t a, uint32_t b, uint32_t c) { uint32_t r; asm("fma.rn.bf16x2 %0, %1, %2, %3;" : "=r"(r) : "r"(a), "r"(b), "r"(c)); return r; }
__device__ __forceinline__ uint32_t set_tag(uint32_t x, uint32_t mask, uint32_t e) { uint32_t r; asm("lop3.b32 %0, %1, %2, %3, 0xB8;" : "=r"(r) : "r"(x), "r"(mask), "r"(e)); return r; }
__device__ __forceinline__ uint32_t opaque(uint32_t x) { asm volatile("" : "+r"(x)); return x; }
__device__ __forceinline__ float rbf(float x) { return __bfloat162float(__float2bfloat16(x)); }
__device__ __forceinline__ float silu_f(float x) {
  float e, r;
  asm("ex2.approx.ftz.f32 %0, %1;" : "=f"(e) : "f"(x * -1.4426950408889634f));
  asm("rcp.approx.ftz.f32 %0, %1;" : "=f"(r) : "f"(1.f + e));
  return x * r;
}
__device__ __forceinline__ float silu2(float x) {
  float t;
  asm("tanh.approx.f32 %0, %1;" : "=f"(t) : "f"(x));
  return fmaf(x, t, x);
}
__device__ __forceinline__ void pin(int off, uint32_t x) { asm volatile("{.reg .pred p; setp.lt.s32 p, %0, 0; @p st.shared.b32 [%0], %1;}" ::"r"(off), "r"(x) : "memory"); }
__device__ __forceinline__ void pin4(int off, const uint32_t* x) { asm volatile("{.reg .pred p; setp.lt.s32 p, %0, 0; @p st.shared.v4.b32 [%0], {%1,%2,%3,%4};}" ::"r"(off), "r"(x[0]), "r"(x[1]), "r"(x[2]), "r"(x[3]) : "memory"); }
__device__ __forceinline__ void split(int x, int n) { asm volatile("{.reg .pred p; setp.eq.s32 p, %0, %1; @p trap;}" ::"r"(x), "r"(~n) : "memory"); }
__device__ __forceinline__ void ln_final(float s, float q, float& m, float& sd) {
  m = s * (1.f / D_);
  asm("sqrt.approx.f32 %0, %1;" : "=f"(sd) : "f"(rbf(rbf(fmaxf(fmaf(-m, m, q * (1.f / D_)), 0.f)) + 1e-5f)));
  sd = rbf(sd);
}
__device__ __forceinline__ float rcpf(float x) { float r; asm("rcp.approx.f32 %0, %1;" : "=f"(r) : "f"(x)); return r; }

__device__ __forceinline__ void wg_rs16_0(float* d, const uint32_t* a, uint64_t db, int sc) {
  asm volatile("{.reg .pred p; setp.ne.b32 p, %13, 0; wgmma.mma_async.sync.aligned.m64n16k16.f32.bf16.bf16 {%0,%1,%2,%3,%4,%5,%6,%7}, {%8,%9,%10,%11}, %12, p, 1, 1, 0;}"
    : "+f"(d[0]),"+f"(d[1]),"+f"(d[2]),"+f"(d[3]),"+f"(d[4]),"+f"(d[5]),"+f"(d[6]),"+f"(d[7]) : "r"(a[0]),"r"(a[1]),"r"(a[2]),"r"(a[3]),"l"(db),"r"(sc));
}
__device__ __forceinline__ void wg_rs32_0(float* d, const uint32_t* a, uint64_t db, int sc) {
  asm volatile("{.reg .pred p; setp.ne.b32 p, %21, 0; wgmma.mma_async.sync.aligned.m64n32k16.f32.bf16.bf16 {%0,%1,%2,%3,%4,%5,%6,%7,%8,%9,%10,%11,%12,%13,%14,%15}, {%16,%17,%18,%19}, %20, p, 1, 1, 0;}"
    : "+f"(d[0]),"+f"(d[1]),"+f"(d[2]),"+f"(d[3]),"+f"(d[4]),"+f"(d[5]),"+f"(d[6]),"+f"(d[7]),"+f"(d[8]),"+f"(d[9]),"+f"(d[10]),"+f"(d[11]),"+f"(d[12]),"+f"(d[13]),"+f"(d[14]),"+f"(d[15]) : "r"(a[0]),"r"(a[1]),"r"(a[2]),"r"(a[3]),"l"(db),"r"(sc));
}
__device__ __forceinline__ void wg_rs48_0(float* d, const uint32_t* a, uint64_t db, int sc) {
  asm volatile("{.reg .pred p; setp.ne.b32 p, %29, 0; wgmma.mma_async.sync.aligned.m64n48k16.f32.bf16.bf16 {%0,%1,%2,%3,%4,%5,%6,%7,%8,%9,%10,%11,%12,%13,%14,%15,%16,%17,%18,%19,%20,%21,%22,%23}, {%24,%25,%26,%27}, %28, p, 1, 1, 0;}"
    : "+f"(d[0]),"+f"(d[1]),"+f"(d[2]),"+f"(d[3]),"+f"(d[4]),"+f"(d[5]),"+f"(d[6]),"+f"(d[7]),"+f"(d[8]),"+f"(d[9]),"+f"(d[10]),"+f"(d[11]),"+f"(d[12]),"+f"(d[13]),"+f"(d[14]),"+f"(d[15]),"+f"(d[16]),"+f"(d[17]),"+f"(d[18]),"+f"(d[19]),"+f"(d[20]),"+f"(d[21]),"+f"(d[22]),"+f"(d[23]) : "r"(a[0]),"r"(a[1]),"r"(a[2]),"r"(a[3]),"l"(db),"r"(sc));
}
__device__ __forceinline__ void wg_rs64_0(float* d, const uint32_t* a, uint64_t db, int sc) {
  asm volatile("{.reg .pred p; setp.ne.b32 p, %37, 0; wgmma.mma_async.sync.aligned.m64n64k16.f32.bf16.bf16 {%0,%1,%2,%3,%4,%5,%6,%7,%8,%9,%10,%11,%12,%13,%14,%15,%16,%17,%18,%19,%20,%21,%22,%23,%24,%25,%26,%27,%28,%29,%30,%31}, {%32,%33,%34,%35}, %36, p, 1, 1, 0;}"
    : "+f"(d[0]),"+f"(d[1]),"+f"(d[2]),"+f"(d[3]),"+f"(d[4]),"+f"(d[5]),"+f"(d[6]),"+f"(d[7]),"+f"(d[8]),"+f"(d[9]),"+f"(d[10]),"+f"(d[11]),"+f"(d[12]),"+f"(d[13]),"+f"(d[14]),"+f"(d[15]),"+f"(d[16]),"+f"(d[17]),"+f"(d[18]),"+f"(d[19]),"+f"(d[20]),"+f"(d[21]),"+f"(d[22]),"+f"(d[23]),"+f"(d[24]),"+f"(d[25]),"+f"(d[26]),"+f"(d[27]),"+f"(d[28]),"+f"(d[29]),"+f"(d[30]),"+f"(d[31]) : "r"(a[0]),"r"(a[1]),"r"(a[2]),"r"(a[3]),"l"(db),"r"(sc));
}
__device__ __forceinline__ void wg_rs80_0(float* d, const uint32_t* a, uint64_t db, int sc) {
  asm volatile("{.reg .pred p; setp.ne.b32 p, %45, 0; wgmma.mma_async.sync.aligned.m64n80k16.f32.bf16.bf16 {%0,%1,%2,%3,%4,%5,%6,%7,%8,%9,%10,%11,%12,%13,%14,%15,%16,%17,%18,%19,%20,%21,%22,%23,%24,%25,%26,%27,%28,%29,%30,%31,%32,%33,%34,%35,%36,%37,%38,%39}, {%40,%41,%42,%43}, %44, p, 1, 1, 0;}"
    : "+f"(d[0]),"+f"(d[1]),"+f"(d[2]),"+f"(d[3]),"+f"(d[4]),"+f"(d[5]),"+f"(d[6]),"+f"(d[7]),"+f"(d[8]),"+f"(d[9]),"+f"(d[10]),"+f"(d[11]),"+f"(d[12]),"+f"(d[13]),"+f"(d[14]),"+f"(d[15]),"+f"(d[16]),"+f"(d[17]),"+f"(d[18]),"+f"(d[19]),"+f"(d[20]),"+f"(d[21]),"+f"(d[22]),"+f"(d[23]),"+f"(d[24]),"+f"(d[25]),"+f"(d[26]),"+f"(d[27]),"+f"(d[28]),"+f"(d[29]),"+f"(d[30]),"+f"(d[31]),"+f"(d[32]),"+f"(d[33]),"+f"(d[34]),"+f"(d[35]),"+f"(d[36]),"+f"(d[37]),"+f"(d[38]),"+f"(d[39]) : "r"(a[0]),"r"(a[1]),"r"(a[2]),"r"(a[3]),"l"(db),"r"(sc));
}
__device__ __forceinline__ void wg_rs96_0(float* d, const uint32_t* a, uint64_t db, int sc) {
  asm volatile("{.reg .pred p; setp.ne.b32 p, %53, 0; wgmma.mma_async.sync.aligned.m64n96k16.f32.bf16.bf16 {%0,%1,%2,%3,%4,%5,%6,%7,%8,%9,%10,%11,%12,%13,%14,%15,%16,%17,%18,%19,%20,%21,%22,%23,%24,%25,%26,%27,%28,%29,%30,%31,%32,%33,%34,%35,%36,%37,%38,%39,%40,%41,%42,%43,%44,%45,%46,%47}, {%48,%49,%50,%51}, %52, p, 1, 1, 0;}"
    : "+f"(d[0]),"+f"(d[1]),"+f"(d[2]),"+f"(d[3]),"+f"(d[4]),"+f"(d[5]),"+f"(d[6]),"+f"(d[7]),"+f"(d[8]),"+f"(d[9]),"+f"(d[10]),"+f"(d[11]),"+f"(d[12]),"+f"(d[13]),"+f"(d[14]),"+f"(d[15]),"+f"(d[16]),"+f"(d[17]),"+f"(d[18]),"+f"(d[19]),"+f"(d[20]),"+f"(d[21]),"+f"(d[22]),"+f"(d[23]),"+f"(d[24]),"+f"(d[25]),"+f"(d[26]),"+f"(d[27]),"+f"(d[28]),"+f"(d[29]),"+f"(d[30]),"+f"(d[31]),"+f"(d[32]),"+f"(d[33]),"+f"(d[34]),"+f"(d[35]),"+f"(d[36]),"+f"(d[37]),"+f"(d[38]),"+f"(d[39]),"+f"(d[40]),"+f"(d[41]),"+f"(d[42]),"+f"(d[43]),"+f"(d[44]),"+f"(d[45]),"+f"(d[46]),"+f"(d[47]) : "r"(a[0]),"r"(a[1]),"r"(a[2]),"r"(a[3]),"l"(db),"r"(sc));
}
__device__ __forceinline__ void wg_rs112_0(float* d, const uint32_t* a, uint64_t db, int sc) {
  asm volatile("{.reg .pred p; setp.ne.b32 p, %61, 0; wgmma.mma_async.sync.aligned.m64n112k16.f32.bf16.bf16 {%0,%1,%2,%3,%4,%5,%6,%7,%8,%9,%10,%11,%12,%13,%14,%15,%16,%17,%18,%19,%20,%21,%22,%23,%24,%25,%26,%27,%28,%29,%30,%31,%32,%33,%34,%35,%36,%37,%38,%39,%40,%41,%42,%43,%44,%45,%46,%47,%48,%49,%50,%51,%52,%53,%54,%55}, {%56,%57,%58,%59}, %60, p, 1, 1, 0;}"
    : "+f"(d[0]),"+f"(d[1]),"+f"(d[2]),"+f"(d[3]),"+f"(d[4]),"+f"(d[5]),"+f"(d[6]),"+f"(d[7]),"+f"(d[8]),"+f"(d[9]),"+f"(d[10]),"+f"(d[11]),"+f"(d[12]),"+f"(d[13]),"+f"(d[14]),"+f"(d[15]),"+f"(d[16]),"+f"(d[17]),"+f"(d[18]),"+f"(d[19]),"+f"(d[20]),"+f"(d[21]),"+f"(d[22]),"+f"(d[23]),"+f"(d[24]),"+f"(d[25]),"+f"(d[26]),"+f"(d[27]),"+f"(d[28]),"+f"(d[29]),"+f"(d[30]),"+f"(d[31]),"+f"(d[32]),"+f"(d[33]),"+f"(d[34]),"+f"(d[35]),"+f"(d[36]),"+f"(d[37]),"+f"(d[38]),"+f"(d[39]),"+f"(d[40]),"+f"(d[41]),"+f"(d[42]),"+f"(d[43]),"+f"(d[44]),"+f"(d[45]),"+f"(d[46]),"+f"(d[47]),"+f"(d[48]),"+f"(d[49]),"+f"(d[50]),"+f"(d[51]),"+f"(d[52]),"+f"(d[53]),"+f"(d[54]),"+f"(d[55]) : "r"(a[0]),"r"(a[1]),"r"(a[2]),"r"(a[3]),"l"(db),"r"(sc));
}
__device__ __forceinline__ void wg_rs128_0(float* d, const uint32_t* a, uint64_t db, int sc) {
  asm volatile("{.reg .pred p; setp.ne.b32 p, %69, 0; wgmma.mma_async.sync.aligned.m64n128k16.f32.bf16.bf16 {%0,%1,%2,%3,%4,%5,%6,%7,%8,%9,%10,%11,%12,%13,%14,%15,%16,%17,%18,%19,%20,%21,%22,%23,%24,%25,%26,%27,%28,%29,%30,%31,%32,%33,%34,%35,%36,%37,%38,%39,%40,%41,%42,%43,%44,%45,%46,%47,%48,%49,%50,%51,%52,%53,%54,%55,%56,%57,%58,%59,%60,%61,%62,%63}, {%64,%65,%66,%67}, %68, p, 1, 1, 0;}"
    : "+f"(d[0]),"+f"(d[1]),"+f"(d[2]),"+f"(d[3]),"+f"(d[4]),"+f"(d[5]),"+f"(d[6]),"+f"(d[7]),"+f"(d[8]),"+f"(d[9]),"+f"(d[10]),"+f"(d[11]),"+f"(d[12]),"+f"(d[13]),"+f"(d[14]),"+f"(d[15]),"+f"(d[16]),"+f"(d[17]),"+f"(d[18]),"+f"(d[19]),"+f"(d[20]),"+f"(d[21]),"+f"(d[22]),"+f"(d[23]),"+f"(d[24]),"+f"(d[25]),"+f"(d[26]),"+f"(d[27]),"+f"(d[28]),"+f"(d[29]),"+f"(d[30]),"+f"(d[31]),"+f"(d[32]),"+f"(d[33]),"+f"(d[34]),"+f"(d[35]),"+f"(d[36]),"+f"(d[37]),"+f"(d[38]),"+f"(d[39]),"+f"(d[40]),"+f"(d[41]),"+f"(d[42]),"+f"(d[43]),"+f"(d[44]),"+f"(d[45]),"+f"(d[46]),"+f"(d[47]),"+f"(d[48]),"+f"(d[49]),"+f"(d[50]),"+f"(d[51]),"+f"(d[52]),"+f"(d[53]),"+f"(d[54]),"+f"(d[55]),"+f"(d[56]),"+f"(d[57]),"+f"(d[58]),"+f"(d[59]),"+f"(d[60]),"+f"(d[61]),"+f"(d[62]),"+f"(d[63]) : "r"(a[0]),"r"(a[1]),"r"(a[2]),"r"(a[3]),"l"(db),"r"(sc));
}
__device__ __forceinline__ void wg_rs144_0(float* d, const uint32_t* a, uint64_t db, int sc) {
  asm volatile("{.reg .pred p; setp.ne.b32 p, %77, 0; wgmma.mma_async.sync.aligned.m64n144k16.f32.bf16.bf16 {%0,%1,%2,%3,%4,%5,%6,%7,%8,%9,%10,%11,%12,%13,%14,%15,%16,%17,%18,%19,%20,%21,%22,%23,%24,%25,%26,%27,%28,%29,%30,%31,%32,%33,%34,%35,%36,%37,%38,%39,%40,%41,%42,%43,%44,%45,%46,%47,%48,%49,%50,%51,%52,%53,%54,%55,%56,%57,%58,%59,%60,%61,%62,%63,%64,%65,%66,%67,%68,%69,%70,%71}, {%72,%73,%74,%75}, %76, p, 1, 1, 0;}"
    : "+f"(d[0]),"+f"(d[1]),"+f"(d[2]),"+f"(d[3]),"+f"(d[4]),"+f"(d[5]),"+f"(d[6]),"+f"(d[7]),"+f"(d[8]),"+f"(d[9]),"+f"(d[10]),"+f"(d[11]),"+f"(d[12]),"+f"(d[13]),"+f"(d[14]),"+f"(d[15]),"+f"(d[16]),"+f"(d[17]),"+f"(d[18]),"+f"(d[19]),"+f"(d[20]),"+f"(d[21]),"+f"(d[22]),"+f"(d[23]),"+f"(d[24]),"+f"(d[25]),"+f"(d[26]),"+f"(d[27]),"+f"(d[28]),"+f"(d[29]),"+f"(d[30]),"+f"(d[31]),"+f"(d[32]),"+f"(d[33]),"+f"(d[34]),"+f"(d[35]),"+f"(d[36]),"+f"(d[37]),"+f"(d[38]),"+f"(d[39]),"+f"(d[40]),"+f"(d[41]),"+f"(d[42]),"+f"(d[43]),"+f"(d[44]),"+f"(d[45]),"+f"(d[46]),"+f"(d[47]),"+f"(d[48]),"+f"(d[49]),"+f"(d[50]),"+f"(d[51]),"+f"(d[52]),"+f"(d[53]),"+f"(d[54]),"+f"(d[55]),"+f"(d[56]),"+f"(d[57]),"+f"(d[58]),"+f"(d[59]),"+f"(d[60]),"+f"(d[61]),"+f"(d[62]),"+f"(d[63]),"+f"(d[64]),"+f"(d[65]),"+f"(d[66]),"+f"(d[67]),"+f"(d[68]),"+f"(d[69]),"+f"(d[70]),"+f"(d[71]) : "r"(a[0]),"r"(a[1]),"r"(a[2]),"r"(a[3]),"l"(db),"r"(sc));
}
__device__ __forceinline__ void wg_rs160_0(float* d, const uint32_t* a, uint64_t db, int sc) {
  asm volatile("{.reg .pred p; setp.ne.b32 p, %85, 0; wgmma.mma_async.sync.aligned.m64n160k16.f32.bf16.bf16 {%0,%1,%2,%3,%4,%5,%6,%7,%8,%9,%10,%11,%12,%13,%14,%15,%16,%17,%18,%19,%20,%21,%22,%23,%24,%25,%26,%27,%28,%29,%30,%31,%32,%33,%34,%35,%36,%37,%38,%39,%40,%41,%42,%43,%44,%45,%46,%47,%48,%49,%50,%51,%52,%53,%54,%55,%56,%57,%58,%59,%60,%61,%62,%63,%64,%65,%66,%67,%68,%69,%70,%71,%72,%73,%74,%75,%76,%77,%78,%79}, {%80,%81,%82,%83}, %84, p, 1, 1, 0;}"
    : "+f"(d[0]),"+f"(d[1]),"+f"(d[2]),"+f"(d[3]),"+f"(d[4]),"+f"(d[5]),"+f"(d[6]),"+f"(d[7]),"+f"(d[8]),"+f"(d[9]),"+f"(d[10]),"+f"(d[11]),"+f"(d[12]),"+f"(d[13]),"+f"(d[14]),"+f"(d[15]),"+f"(d[16]),"+f"(d[17]),"+f"(d[18]),"+f"(d[19]),"+f"(d[20]),"+f"(d[21]),"+f"(d[22]),"+f"(d[23]),"+f"(d[24]),"+f"(d[25]),"+f"(d[26]),"+f"(d[27]),"+f"(d[28]),"+f"(d[29]),"+f"(d[30]),"+f"(d[31]),"+f"(d[32]),"+f"(d[33]),"+f"(d[34]),"+f"(d[35]),"+f"(d[36]),"+f"(d[37]),"+f"(d[38]),"+f"(d[39]),"+f"(d[40]),"+f"(d[41]),"+f"(d[42]),"+f"(d[43]),"+f"(d[44]),"+f"(d[45]),"+f"(d[46]),"+f"(d[47]),"+f"(d[48]),"+f"(d[49]),"+f"(d[50]),"+f"(d[51]),"+f"(d[52]),"+f"(d[53]),"+f"(d[54]),"+f"(d[55]),"+f"(d[56]),"+f"(d[57]),"+f"(d[58]),"+f"(d[59]),"+f"(d[60]),"+f"(d[61]),"+f"(d[62]),"+f"(d[63]),"+f"(d[64]),"+f"(d[65]),"+f"(d[66]),"+f"(d[67]),"+f"(d[68]),"+f"(d[69]),"+f"(d[70]),"+f"(d[71]),"+f"(d[72]),"+f"(d[73]),"+f"(d[74]),"+f"(d[75]),"+f"(d[76]),"+f"(d[77]),"+f"(d[78]),"+f"(d[79]) : "r"(a[0]),"r"(a[1]),"r"(a[2]),"r"(a[3]),"l"(db),"r"(sc));
}
__device__ __forceinline__ void wg_rs176_0(float* d, const uint32_t* a, uint64_t db, int sc) {
  asm volatile("{.reg .pred p; setp.ne.b32 p, %93, 0; wgmma.mma_async.sync.aligned.m64n176k16.f32.bf16.bf16 {%0,%1,%2,%3,%4,%5,%6,%7,%8,%9,%10,%11,%12,%13,%14,%15,%16,%17,%18,%19,%20,%21,%22,%23,%24,%25,%26,%27,%28,%29,%30,%31,%32,%33,%34,%35,%36,%37,%38,%39,%40,%41,%42,%43,%44,%45,%46,%47,%48,%49,%50,%51,%52,%53,%54,%55,%56,%57,%58,%59,%60,%61,%62,%63,%64,%65,%66,%67,%68,%69,%70,%71,%72,%73,%74,%75,%76,%77,%78,%79,%80,%81,%82,%83,%84,%85,%86,%87}, {%88,%89,%90,%91}, %92, p, 1, 1, 0;}"
    : "+f"(d[0]),"+f"(d[1]),"+f"(d[2]),"+f"(d[3]),"+f"(d[4]),"+f"(d[5]),"+f"(d[6]),"+f"(d[7]),"+f"(d[8]),"+f"(d[9]),"+f"(d[10]),"+f"(d[11]),"+f"(d[12]),"+f"(d[13]),"+f"(d[14]),"+f"(d[15]),"+f"(d[16]),"+f"(d[17]),"+f"(d[18]),"+f"(d[19]),"+f"(d[20]),"+f"(d[21]),"+f"(d[22]),"+f"(d[23]),"+f"(d[24]),"+f"(d[25]),"+f"(d[26]),"+f"(d[27]),"+f"(d[28]),"+f"(d[29]),"+f"(d[30]),"+f"(d[31]),"+f"(d[32]),"+f"(d[33]),"+f"(d[34]),"+f"(d[35]),"+f"(d[36]),"+f"(d[37]),"+f"(d[38]),"+f"(d[39]),"+f"(d[40]),"+f"(d[41]),"+f"(d[42]),"+f"(d[43]),"+f"(d[44]),"+f"(d[45]),"+f"(d[46]),"+f"(d[47]),"+f"(d[48]),"+f"(d[49]),"+f"(d[50]),"+f"(d[51]),"+f"(d[52]),"+f"(d[53]),"+f"(d[54]),"+f"(d[55]),"+f"(d[56]),"+f"(d[57]),"+f"(d[58]),"+f"(d[59]),"+f"(d[60]),"+f"(d[61]),"+f"(d[62]),"+f"(d[63]),"+f"(d[64]),"+f"(d[65]),"+f"(d[66]),"+f"(d[67]),"+f"(d[68]),"+f"(d[69]),"+f"(d[70]),"+f"(d[71]),"+f"(d[72]),"+f"(d[73]),"+f"(d[74]),"+f"(d[75]),"+f"(d[76]),"+f"(d[77]),"+f"(d[78]),"+f"(d[79]),"+f"(d[80]),"+f"(d[81]),"+f"(d[82]),"+f"(d[83]),"+f"(d[84]),"+f"(d[85]),"+f"(d[86]),"+f"(d[87]) : "r"(a[0]),"r"(a[1]),"r"(a[2]),"r"(a[3]),"l"(db),"r"(sc));
}
__device__ __forceinline__ void wg_rs192_0(float* d, const uint32_t* a, uint64_t db, int sc) {
  asm volatile("{.reg .pred p; setp.ne.b32 p, %101, 0; wgmma.mma_async.sync.aligned.m64n192k16.f32.bf16.bf16 {%0,%1,%2,%3,%4,%5,%6,%7,%8,%9,%10,%11,%12,%13,%14,%15,%16,%17,%18,%19,%20,%21,%22,%23,%24,%25,%26,%27,%28,%29,%30,%31,%32,%33,%34,%35,%36,%37,%38,%39,%40,%41,%42,%43,%44,%45,%46,%47,%48,%49,%50,%51,%52,%53,%54,%55,%56,%57,%58,%59,%60,%61,%62,%63,%64,%65,%66,%67,%68,%69,%70,%71,%72,%73,%74,%75,%76,%77,%78,%79,%80,%81,%82,%83,%84,%85,%86,%87,%88,%89,%90,%91,%92,%93,%94,%95}, {%96,%97,%98,%99}, %100, p, 1, 1, 0;}"
    : "+f"(d[0]),"+f"(d[1]),"+f"(d[2]),"+f"(d[3]),"+f"(d[4]),"+f"(d[5]),"+f"(d[6]),"+f"(d[7]),"+f"(d[8]),"+f"(d[9]),"+f"(d[10]),"+f"(d[11]),"+f"(d[12]),"+f"(d[13]),"+f"(d[14]),"+f"(d[15]),"+f"(d[16]),"+f"(d[17]),"+f"(d[18]),"+f"(d[19]),"+f"(d[20]),"+f"(d[21]),"+f"(d[22]),"+f"(d[23]),"+f"(d[24]),"+f"(d[25]),"+f"(d[26]),"+f"(d[27]),"+f"(d[28]),"+f"(d[29]),"+f"(d[30]),"+f"(d[31]),"+f"(d[32]),"+f"(d[33]),"+f"(d[34]),"+f"(d[35]),"+f"(d[36]),"+f"(d[37]),"+f"(d[38]),"+f"(d[39]),"+f"(d[40]),"+f"(d[41]),"+f"(d[42]),"+f"(d[43]),"+f"(d[44]),"+f"(d[45]),"+f"(d[46]),"+f"(d[47]),"+f"(d[48]),"+f"(d[49]),"+f"(d[50]),"+f"(d[51]),"+f"(d[52]),"+f"(d[53]),"+f"(d[54]),"+f"(d[55]),"+f"(d[56]),"+f"(d[57]),"+f"(d[58]),"+f"(d[59]),"+f"(d[60]),"+f"(d[61]),"+f"(d[62]),"+f"(d[63]),"+f"(d[64]),"+f"(d[65]),"+f"(d[66]),"+f"(d[67]),"+f"(d[68]),"+f"(d[69]),"+f"(d[70]),"+f"(d[71]),"+f"(d[72]),"+f"(d[73]),"+f"(d[74]),"+f"(d[75]),"+f"(d[76]),"+f"(d[77]),"+f"(d[78]),"+f"(d[79]),"+f"(d[80]),"+f"(d[81]),"+f"(d[82]),"+f"(d[83]),"+f"(d[84]),"+f"(d[85]),"+f"(d[86]),"+f"(d[87]),"+f"(d[88]),"+f"(d[89]),"+f"(d[90]),"+f"(d[91]),"+f"(d[92]),"+f"(d[93]),"+f"(d[94]),"+f"(d[95]) : "r"(a[0]),"r"(a[1]),"r"(a[2]),"r"(a[3]),"l"(db),"r"(sc));
}
__device__ __forceinline__ void wg_ss192_11(float* d, uint64_t da, uint64_t db, int sc) {
  asm volatile("{.reg .pred p; setp.ne.b32 p, %98, 0; wgmma.mma_async.sync.aligned.m64n192k16.f32.bf16.bf16 {%0,%1,%2,%3,%4,%5,%6,%7,%8,%9,%10,%11,%12,%13,%14,%15,%16,%17,%18,%19,%20,%21,%22,%23,%24,%25,%26,%27,%28,%29,%30,%31,%32,%33,%34,%35,%36,%37,%38,%39,%40,%41,%42,%43,%44,%45,%46,%47,%48,%49,%50,%51,%52,%53,%54,%55,%56,%57,%58,%59,%60,%61,%62,%63,%64,%65,%66,%67,%68,%69,%70,%71,%72,%73,%74,%75,%76,%77,%78,%79,%80,%81,%82,%83,%84,%85,%86,%87,%88,%89,%90,%91,%92,%93,%94,%95}, %96, %97, p, 1, 1, 1, 1;}"
    : "+f"(d[0]),"+f"(d[1]),"+f"(d[2]),"+f"(d[3]),"+f"(d[4]),"+f"(d[5]),"+f"(d[6]),"+f"(d[7]),"+f"(d[8]),"+f"(d[9]),"+f"(d[10]),"+f"(d[11]),"+f"(d[12]),"+f"(d[13]),"+f"(d[14]),"+f"(d[15]),"+f"(d[16]),"+f"(d[17]),"+f"(d[18]),"+f"(d[19]),"+f"(d[20]),"+f"(d[21]),"+f"(d[22]),"+f"(d[23]),"+f"(d[24]),"+f"(d[25]),"+f"(d[26]),"+f"(d[27]),"+f"(d[28]),"+f"(d[29]),"+f"(d[30]),"+f"(d[31]),"+f"(d[32]),"+f"(d[33]),"+f"(d[34]),"+f"(d[35]),"+f"(d[36]),"+f"(d[37]),"+f"(d[38]),"+f"(d[39]),"+f"(d[40]),"+f"(d[41]),"+f"(d[42]),"+f"(d[43]),"+f"(d[44]),"+f"(d[45]),"+f"(d[46]),"+f"(d[47]),"+f"(d[48]),"+f"(d[49]),"+f"(d[50]),"+f"(d[51]),"+f"(d[52]),"+f"(d[53]),"+f"(d[54]),"+f"(d[55]),"+f"(d[56]),"+f"(d[57]),"+f"(d[58]),"+f"(d[59]),"+f"(d[60]),"+f"(d[61]),"+f"(d[62]),"+f"(d[63]),"+f"(d[64]),"+f"(d[65]),"+f"(d[66]),"+f"(d[67]),"+f"(d[68]),"+f"(d[69]),"+f"(d[70]),"+f"(d[71]),"+f"(d[72]),"+f"(d[73]),"+f"(d[74]),"+f"(d[75]),"+f"(d[76]),"+f"(d[77]),"+f"(d[78]),"+f"(d[79]),"+f"(d[80]),"+f"(d[81]),"+f"(d[82]),"+f"(d[83]),"+f"(d[84]),"+f"(d[85]),"+f"(d[86]),"+f"(d[87]),"+f"(d[88]),"+f"(d[89]),"+f"(d[90]),"+f"(d[91]),"+f"(d[92]),"+f"(d[93]),"+f"(d[94]),"+f"(d[95]) : "l"(da),"l"(db),"r"(sc));
}
__device__ __forceinline__ void wg_ss192_01(float* d, uint64_t da, uint64_t db, int sc) {
  asm volatile("{.reg .pred p; setp.ne.b32 p, %98, 0; wgmma.mma_async.sync.aligned.m64n192k16.f32.bf16.bf16 {%0,%1,%2,%3,%4,%5,%6,%7,%8,%9,%10,%11,%12,%13,%14,%15,%16,%17,%18,%19,%20,%21,%22,%23,%24,%25,%26,%27,%28,%29,%30,%31,%32,%33,%34,%35,%36,%37,%38,%39,%40,%41,%42,%43,%44,%45,%46,%47,%48,%49,%50,%51,%52,%53,%54,%55,%56,%57,%58,%59,%60,%61,%62,%63,%64,%65,%66,%67,%68,%69,%70,%71,%72,%73,%74,%75,%76,%77,%78,%79,%80,%81,%82,%83,%84,%85,%86,%87,%88,%89,%90,%91,%92,%93,%94,%95}, %96, %97, p, 1, 1, 0, 1;}"
    : "+f"(d[0]),"+f"(d[1]),"+f"(d[2]),"+f"(d[3]),"+f"(d[4]),"+f"(d[5]),"+f"(d[6]),"+f"(d[7]),"+f"(d[8]),"+f"(d[9]),"+f"(d[10]),"+f"(d[11]),"+f"(d[12]),"+f"(d[13]),"+f"(d[14]),"+f"(d[15]),"+f"(d[16]),"+f"(d[17]),"+f"(d[18]),"+f"(d[19]),"+f"(d[20]),"+f"(d[21]),"+f"(d[22]),"+f"(d[23]),"+f"(d[24]),"+f"(d[25]),"+f"(d[26]),"+f"(d[27]),"+f"(d[28]),"+f"(d[29]),"+f"(d[30]),"+f"(d[31]),"+f"(d[32]),"+f"(d[33]),"+f"(d[34]),"+f"(d[35]),"+f"(d[36]),"+f"(d[37]),"+f"(d[38]),"+f"(d[39]),"+f"(d[40]),"+f"(d[41]),"+f"(d[42]),"+f"(d[43]),"+f"(d[44]),"+f"(d[45]),"+f"(d[46]),"+f"(d[47]),"+f"(d[48]),"+f"(d[49]),"+f"(d[50]),"+f"(d[51]),"+f"(d[52]),"+f"(d[53]),"+f"(d[54]),"+f"(d[55]),"+f"(d[56]),"+f"(d[57]),"+f"(d[58]),"+f"(d[59]),"+f"(d[60]),"+f"(d[61]),"+f"(d[62]),"+f"(d[63]),"+f"(d[64]),"+f"(d[65]),"+f"(d[66]),"+f"(d[67]),"+f"(d[68]),"+f"(d[69]),"+f"(d[70]),"+f"(d[71]),"+f"(d[72]),"+f"(d[73]),"+f"(d[74]),"+f"(d[75]),"+f"(d[76]),"+f"(d[77]),"+f"(d[78]),"+f"(d[79]),"+f"(d[80]),"+f"(d[81]),"+f"(d[82]),"+f"(d[83]),"+f"(d[84]),"+f"(d[85]),"+f"(d[86]),"+f"(d[87]),"+f"(d[88]),"+f"(d[89]),"+f"(d[90]),"+f"(d[91]),"+f"(d[92]),"+f"(d[93]),"+f"(d[94]),"+f"(d[95]) : "l"(da),"l"(db),"r"(sc));
}
__device__ __forceinline__ void wg_ss160_01(float* d, uint64_t da, uint64_t db, int sc) {
  asm volatile("{.reg .pred p; setp.ne.b32 p, %82, 0; wgmma.mma_async.sync.aligned.m64n160k16.f32.bf16.bf16 {%0,%1,%2,%3,%4,%5,%6,%7,%8,%9,%10,%11,%12,%13,%14,%15,%16,%17,%18,%19,%20,%21,%22,%23,%24,%25,%26,%27,%28,%29,%30,%31,%32,%33,%34,%35,%36,%37,%38,%39,%40,%41,%42,%43,%44,%45,%46,%47,%48,%49,%50,%51,%52,%53,%54,%55,%56,%57,%58,%59,%60,%61,%62,%63,%64,%65,%66,%67,%68,%69,%70,%71,%72,%73,%74,%75,%76,%77,%78,%79}, %80, %81, p, 1, 1, 0, 1;}"
    : "+f"(d[0]),"+f"(d[1]),"+f"(d[2]),"+f"(d[3]),"+f"(d[4]),"+f"(d[5]),"+f"(d[6]),"+f"(d[7]),"+f"(d[8]),"+f"(d[9]),"+f"(d[10]),"+f"(d[11]),"+f"(d[12]),"+f"(d[13]),"+f"(d[14]),"+f"(d[15]),"+f"(d[16]),"+f"(d[17]),"+f"(d[18]),"+f"(d[19]),"+f"(d[20]),"+f"(d[21]),"+f"(d[22]),"+f"(d[23]),"+f"(d[24]),"+f"(d[25]),"+f"(d[26]),"+f"(d[27]),"+f"(d[28]),"+f"(d[29]),"+f"(d[30]),"+f"(d[31]),"+f"(d[32]),"+f"(d[33]),"+f"(d[34]),"+f"(d[35]),"+f"(d[36]),"+f"(d[37]),"+f"(d[38]),"+f"(d[39]),"+f"(d[40]),"+f"(d[41]),"+f"(d[42]),"+f"(d[43]),"+f"(d[44]),"+f"(d[45]),"+f"(d[46]),"+f"(d[47]),"+f"(d[48]),"+f"(d[49]),"+f"(d[50]),"+f"(d[51]),"+f"(d[52]),"+f"(d[53]),"+f"(d[54]),"+f"(d[55]),"+f"(d[56]),"+f"(d[57]),"+f"(d[58]),"+f"(d[59]),"+f"(d[60]),"+f"(d[61]),"+f"(d[62]),"+f"(d[63]),"+f"(d[64]),"+f"(d[65]),"+f"(d[66]),"+f"(d[67]),"+f"(d[68]),"+f"(d[69]),"+f"(d[70]),"+f"(d[71]),"+f"(d[72]),"+f"(d[73]),"+f"(d[74]),"+f"(d[75]),"+f"(d[76]),"+f"(d[77]),"+f"(d[78]),"+f"(d[79]) : "l"(da),"l"(db),"r"(sc));
}
__device__ __forceinline__ void wg_ss96_01(float* d, uint64_t da, uint64_t db, int sc) {
  asm volatile("{.reg .pred p; setp.ne.b32 p, %50, 0; wgmma.mma_async.sync.aligned.m64n96k16.f32.bf16.bf16 {%0,%1,%2,%3,%4,%5,%6,%7,%8,%9,%10,%11,%12,%13,%14,%15,%16,%17,%18,%19,%20,%21,%22,%23,%24,%25,%26,%27,%28,%29,%30,%31,%32,%33,%34,%35,%36,%37,%38,%39,%40,%41,%42,%43,%44,%45,%46,%47}, %48, %49, p, 1, 1, 0, 1;}"
    : "+f"(d[0]),"+f"(d[1]),"+f"(d[2]),"+f"(d[3]),"+f"(d[4]),"+f"(d[5]),"+f"(d[6]),"+f"(d[7]),"+f"(d[8]),"+f"(d[9]),"+f"(d[10]),"+f"(d[11]),"+f"(d[12]),"+f"(d[13]),"+f"(d[14]),"+f"(d[15]),"+f"(d[16]),"+f"(d[17]),"+f"(d[18]),"+f"(d[19]),"+f"(d[20]),"+f"(d[21]),"+f"(d[22]),"+f"(d[23]),"+f"(d[24]),"+f"(d[25]),"+f"(d[26]),"+f"(d[27]),"+f"(d[28]),"+f"(d[29]),"+f"(d[30]),"+f"(d[31]),"+f"(d[32]),"+f"(d[33]),"+f"(d[34]),"+f"(d[35]),"+f"(d[36]),"+f"(d[37]),"+f"(d[38]),"+f"(d[39]),"+f"(d[40]),"+f"(d[41]),"+f"(d[42]),"+f"(d[43]),"+f"(d[44]),"+f"(d[45]),"+f"(d[46]),"+f"(d[47]) : "l"(da),"l"(db),"r"(sc));
}
__device__ __forceinline__ void wg_ss64_01(float* d, uint64_t da, uint64_t db, int sc) {
  asm volatile("{.reg .pred p; setp.ne.b32 p, %34, 0; wgmma.mma_async.sync.aligned.m64n64k16.f32.bf16.bf16 {%0,%1,%2,%3,%4,%5,%6,%7,%8,%9,%10,%11,%12,%13,%14,%15,%16,%17,%18,%19,%20,%21,%22,%23,%24,%25,%26,%27,%28,%29,%30,%31}, %32, %33, p, 1, 1, 0, 1;}"
    : "+f"(d[0]),"+f"(d[1]),"+f"(d[2]),"+f"(d[3]),"+f"(d[4]),"+f"(d[5]),"+f"(d[6]),"+f"(d[7]),"+f"(d[8]),"+f"(d[9]),"+f"(d[10]),"+f"(d[11]),"+f"(d[12]),"+f"(d[13]),"+f"(d[14]),"+f"(d[15]),"+f"(d[16]),"+f"(d[17]),"+f"(d[18]),"+f"(d[19]),"+f"(d[20]),"+f"(d[21]),"+f"(d[22]),"+f"(d[23]),"+f"(d[24]),"+f"(d[25]),"+f"(d[26]),"+f"(d[27]),"+f"(d[28]),"+f"(d[29]),"+f"(d[30]),"+f"(d[31]) : "l"(da),"l"(db),"r"(sc));
}
__device__ __forceinline__ void wg_rs160_1(float* d, const uint32_t* a, uint64_t db, int sc) {
  asm volatile("{.reg .pred p; setp.ne.b32 p, %85, 0; wgmma.mma_async.sync.aligned.m64n160k16.f32.bf16.bf16 {%0,%1,%2,%3,%4,%5,%6,%7,%8,%9,%10,%11,%12,%13,%14,%15,%16,%17,%18,%19,%20,%21,%22,%23,%24,%25,%26,%27,%28,%29,%30,%31,%32,%33,%34,%35,%36,%37,%38,%39,%40,%41,%42,%43,%44,%45,%46,%47,%48,%49,%50,%51,%52,%53,%54,%55,%56,%57,%58,%59,%60,%61,%62,%63,%64,%65,%66,%67,%68,%69,%70,%71,%72,%73,%74,%75,%76,%77,%78,%79}, {%80,%81,%82,%83}, %84, p, 1, 1, 1;}"
    : "+f"(d[0]),"+f"(d[1]),"+f"(d[2]),"+f"(d[3]),"+f"(d[4]),"+f"(d[5]),"+f"(d[6]),"+f"(d[7]),"+f"(d[8]),"+f"(d[9]),"+f"(d[10]),"+f"(d[11]),"+f"(d[12]),"+f"(d[13]),"+f"(d[14]),"+f"(d[15]),"+f"(d[16]),"+f"(d[17]),"+f"(d[18]),"+f"(d[19]),"+f"(d[20]),"+f"(d[21]),"+f"(d[22]),"+f"(d[23]),"+f"(d[24]),"+f"(d[25]),"+f"(d[26]),"+f"(d[27]),"+f"(d[28]),"+f"(d[29]),"+f"(d[30]),"+f"(d[31]),"+f"(d[32]),"+f"(d[33]),"+f"(d[34]),"+f"(d[35]),"+f"(d[36]),"+f"(d[37]),"+f"(d[38]),"+f"(d[39]),"+f"(d[40]),"+f"(d[41]),"+f"(d[42]),"+f"(d[43]),"+f"(d[44]),"+f"(d[45]),"+f"(d[46]),"+f"(d[47]),"+f"(d[48]),"+f"(d[49]),"+f"(d[50]),"+f"(d[51]),"+f"(d[52]),"+f"(d[53]),"+f"(d[54]),"+f"(d[55]),"+f"(d[56]),"+f"(d[57]),"+f"(d[58]),"+f"(d[59]),"+f"(d[60]),"+f"(d[61]),"+f"(d[62]),"+f"(d[63]),"+f"(d[64]),"+f"(d[65]),"+f"(d[66]),"+f"(d[67]),"+f"(d[68]),"+f"(d[69]),"+f"(d[70]),"+f"(d[71]),"+f"(d[72]),"+f"(d[73]),"+f"(d[74]),"+f"(d[75]),"+f"(d[76]),"+f"(d[77]),"+f"(d[78]),"+f"(d[79]) : "r"(a[0]),"r"(a[1]),"r"(a[2]),"r"(a[3]),"l"(db),"r"(sc));
}
__device__ __forceinline__ void wg_ss8_10(float* d, uint64_t da, uint64_t db, int sc) {
  asm volatile("{.reg .pred p; setp.ne.b32 p, %6, 0; wgmma.mma_async.sync.aligned.m64n8k16.f32.bf16.bf16 {%0,%1,%2,%3}, %4, %5, p, 1, 1, 1, 0;}"
    : "+f"(d[0]),"+f"(d[1]),"+f"(d[2]),"+f"(d[3]) : "l"(da),"l"(db),"r"(sc));
}

constexpr uint32_t DB = 1024;
constexpr int WSLOT = 24576, NW = 6, ASLOT = 8192, ARING = 4 * ASLOT;
constexpr int OFF_A = NW * WSLOT;
constexpr int OFF_PB = OFF_A + 2 * ARING;
constexpr int OFF_CV = OFF_PB + 16384, OFF_ST = OFF_CV + 768, OFF_TS = OFF_ST + 256, OFF_MODR = OFF_TS + 512, OFF_BAR = OFF_MODR + 80, SMEM_BYTES = OFF_BAR + 1168;
constexpr int OFF_BX = OFF_PB, OFF_AX = OFF_BX + 12288, OFF_RT = OFF_AX + 2048, OFF_GB = OFF_RT + 512, OFF_CO = OFF_CV;
constexpr int OFF_UV = 5 * WSLOT, OFF_UVE = OFF_PB, OFF_SX = OFF_A + ARING + 3 * ASLOT, OFF_X1 = 2 * WSLOT + ASLOT, OFF_XCH = WSLOT;
constexpr int OFF_Q = 0, KV_V = 4096, KV_H = 8192, F_E = 16, F_O = 4176, OFF_WM = 3 * WSLOT, OFF_TAP = 168576, OFF_MR = OFF_A + 3 * ASLOT;
constexpr uint64_t pk5(int a, int b, int c, int d, int e) { return (uint64_t)(a / 128) | (uint64_t)(b / 128) << 12 | (uint64_t)(c / 128) << 24 | (uint64_t)(d / 128) << 36 | (uint64_t)(e / 128) << 48; }
constexpr uint64_t T_KV = pk5(20480, 30720, 40960, 180224, 190464), T_F = pk5(51200, 59648, 200192, 147456, 155904), T_X = pk5(208512, 164352, 68096, 208512, 164352),
                   T_P = pk5(131072, OFF_PB, 114688, 131072, OFF_PB);
__host__ __device__ __forceinline__ uint32_t tab(uint64_t t, int c) { return ((uint32_t)(t >> (12 * c)) & 0xFFF) << 7; }
enum { B_KV = 0, B_FRAW = 5, B_Q = 10, B_WM = 15, B_XR, B_MR = B_XR + 5, B_QTOK, B_ST1, B_MODR, B_S3 = B_MODR + 5, B_FIN, B_FL = 32, B_PFULL = B_FL + 5, B_PEMPTY = B_PFULL + 5, B_FRDY = B_PEMPTY + 5,
       B_G3 = B_FRDY + 5, B_EXT, B_QTD, B_LAG, B_GB, B_UVD, B_TURN, B_FULL = 60, B_RETRY = B_FULL + 33, B_XFREE = B_RETRY + 9, B_BX, B_UVB, B_UVE, B_SX, B_EMPTY = 109 };
static_assert(B_MODR + 5 <= B_FL && B_UVD < B_FULL && B_SX + 2 == B_EMPTY - 1, "barrier groups");
#define BAR(i) (base + OFF_BAR + 8 * (i))

constexpr int NE = 24;
struct Maps { CUtensorMap km, v, q, kh, tap, wm, w1s, w3s, xs, w1, w3, w1e, w3e, x1s, x1b, w2a, w2b, outa, outb; };
struct Ptrs { const bf16 *ssmk, *c, *ssmd; Scratch* g; uint64_t prog, cprog[2]; int boff, th, wms, ulo, uhi; uint32_t c0, fin, turn, mr2, m3, seq; float one; uint2 sched[NE]; uint32_t wdep[20], wt[5]; uint2 w2t[12]; int hid[3][9]; };

#define REGION_IDS int tid, lane, bid; \
  asm volatile("mov.u32 %0, %%tid.x;" : "=r"(tid)); asm volatile("mov.u32 %0, %%laneid;" : "=r"(lane)); asm volatile("mov.u32 %0, %%ctaid.x;" : "=r"(bid)); \
  const int i0 = tid & 127; (void)i0; (void)lane; (void)bid

__device__ __forceinline__ void ffn_role(int& h, int& j, int& r) {
  uint32_t b;
  asm volatile("mov.u32 %0, %%ctaid.x;" : "=r"(b));
  const uint32_t c = b >> 1, q = (c - 36) * 37 >> 8, e = c - 36 - 7 * q;
  h = b & 1;
  const uint32_t k = c < 4 ? 0 : c < 36 ? (c - 4) & 7 : e + 1, p = c < 4 ? c : c < 36 ? (c - 4) >> 3 : q, up = c - 4 >= 32;
  j = 2 * (k & 1) + up;
  r = 2 * (k & 6) + p;
}
__device__ __forceinline__ int fslice(int j, int e) { return e == 2 ? j ^ 1 : (~j & 2) + e; }
__device__ __forceinline__ int mod_ch(int p) { return p < 40 ? (p >> 3) * 128 + (p & 1) * 64 : 64 * (p < 50 ? p - 40 : p - 50); }
__device__ __forceinline__ int mod_col(int p) { return mod_ch(p) + 640 * (p < 40 ? 0x4210 >> (2 * (p & 6)) & 7 : p < 50 ? 3 : 5); }
__device__ __forceinline__ uint32_t mod_sum(uint2 v) { return pack_bf16(0.f, __uint_as_float(v.x) + __uint_as_float(v.y)); }

constexpr int NT = 3, LAG2 = 29, MG = 4;
__device__ __forceinline__ int w_block(int up, int m) { return m == 1 ? 2 + 3 * up : 3 * (m >> 1) + up; }
__host__ __device__ constexpr int w2_at(int v) { return 8192 * (v ? 0x0613030008ull >> v % 5 * 8 & 255 : 15); }
__host__ __device__ constexpr int w2_step(int v) { return 8192 * (v ? 0x32113 >> v % 5 * 4 & 15 : 1); }
__host__ __device__ constexpr int hid_at(int m, int g) { return 8192 * ((g ? 0x0D07110F1816ull : 0x0A19101A1412ull) >> m % 6 * 8 & 255); }
__host__ __device__ constexpr uint32_t w2_desc(int v) { return (DB + w2_at(v)) >> 4 | w2_step(v) << 12; }
__device__ __forceinline__ int next_slot(int s) { return s >= 4 * WSLOT ? 0 : s + WSLOT; }

template <int U> __device__ __forceinline__ void cstep(float* acc, const uint32_t* A, uint64_t db) {
  const uint32_t* a = A + 4 * U;
  const uint64_t d = db + 16 * U;
  if (U == 4) { wg_rs64_0(acc + 96, A, db + 192, 0); wg_rs48_0(acc + 96, A + 4, db + 208, 1); wg_rs32_0(acc + 96, A + 8, db + 224, 1); wg_rs16_0(acc + 96, A + 12, db + 240, 1); }
  if (U <= 4) wg_rs192_0(acc, a, d, U);
  if (U == 5) wg_rs176_0(acc, a, d, 1);
  if (U == 6) wg_rs160_0(acc, a, d, 1);
  if (U == 7) wg_rs144_0(acc, a, d, 1);
  if (U == 8) wg_rs128_0(acc, a, d, 1);
  if (U == 9) wg_rs112_0(acc, a, d, 1);
  if (U == 10) wg_rs96_0(acc, a, d, 1);
  if (U == 11) wg_rs80_0(acc, a, d, 1);
  if (U == 12) wg_rs64_0(acc, a, d, 1);
  if (U == 13) wg_rs48_0(acc, a, d, 1);
  if (U == 14) wg_rs32_0(acc, a, d, 1);
  if (U == 15) wg_rs16_0(acc, a, d, 1);
}
template <int U0, int U1> __device__ __forceinline__ void csteps(float* acc, const uint32_t* A, uint64_t db) {
  cstep<U0>(acc, A, db);
  if constexpr (U0 > U1) csteps<U0 - 1, U1>(acc, A, db);
}
template <int U0, int U1> __device__ __forceinline__ void cload(uint32_t* A, uint32_t fa) {
  asm volatile("{ld.shared.b32 %0, [%4+%5]; ld.shared.b32 %1, [%4+%5+128]; ld.shared.b32 %2, [%4+%5+16]; ld.shared.b32 %3, [%4+%5+144];}"
               : "=r"(A[4 * U0]), "=r"(A[4 * U0 + 1]), "=r"(A[4 * U0 + 2]), "=r"(A[4 * U0 + 3]) : "r"(fa), "n"(256 * U0) : "memory");
  if constexpr (U0 > U1) cload<U0 - 1, U1>(A, fa);
}

__device__ __forceinline__ void mod_gemv(Scratch* G, uint32_t wm, int unit, int w, int lane, uint32_t par) {
  float d[4] = {};
  fence_regs(d);
  wg_fence();
#pragma unroll 1
  for (int k = 0; k < 20; k += 2) {
    wg_ss8_10(d, mkdesc(DB + wm + 2048 * k, 16, 1024, 1), mkdesc(DB + OFF_CV + 32 * k, 16, 128, 0), 1);
    wg_ss8_10(d, mkdesc(DB + wm + 2048 * k + 2048, 16, 1024, 1), mkdesc(DB + OFF_CV + 32 * k + 32, 16, 128, 0), 1);
  }
  wg_commit();
  const int p = unit >> 1, ch = mod_ch(p) + 16 * w + (lane >> 2);
  uint32_t* dst = (uint32_t*)(p < 40 ? &G->modc[ch & 127][8 + (p >> 1)] : &G->modv[p >= 50][ch]) + (unit & 1);
  wg_wait<0>();
  fence_regs(d);
  if (!(lane & 3)) {
    publish(dst, (__float_as_uint(d[0]) & ~1u) | par);
    publish(dst + (p < 40 ? 512 : 16), (__float_as_uint(d[2]) & ~1u) | par);
    if (p < 40 && (p & 6) == 6) {
      dst = (uint32_t*)&G->modv[2][ch] + (unit & 1);
      publish(dst, (__float_as_uint(d[0]) & ~1u) | par);
      publish(dst + 16, (__float_as_uint(d[2]) & ~1u) | par);
    }
  }
}
__device__ __forceinline__ void silu_vector(const bf16* c, uint32_t base) {
  REGION_IDS;
  const uint32_t c0 = ldg32(c + 320 * (bid & 1) + 2 * i0), c1 = ldg32(c + 320 * (bid & 1) + 256 + 2 * lane);
  sts32(base + OFF_CV + 4 * i0, pack_bf16(silu_f(bf_lo(c0)), silu_f(bf_hi(c0))));
  sts32(base + OFF_CV + 512 + 4 * lane, pack_bf16(silu_f(bf_lo(c1)), silu_f(bf_hi(c1))));
  fence_async_smem();
}

__device__ __forceinline__ void mod_poll(Scratch* G, uint32_t base, int c, int n, uint32_t epoch) {
  REGION_IDS;
  const int e = 4 * c + (lane & (4 * n - 1));
  uint2 m;
  int it = 0;
#pragma unroll 1
  do m = ld_relaxed64(&G->modc[bid][8 + e]); while (__any_sync(~0u, ((m.x ^ epoch) | (m.y ^ epoch)) & 1) && ++it < SPIN_LIMIT);
  sts32(base + OFF_MODR + 4 * e, __byte_perm(badd2(mod_sum(m), (lane & 1) * 0x3F800000u), 0, 0x3232));
  __syncwarp();
  if (elect()) { mbar_arrive(BAR(B_MODR + c)); if (n > 1) mbar_arrive(BAR(B_MODR + c + 1)); }
}
__device__ __forceinline__ void row_stats(Scratch* G, uint32_t base, uint32_t epoch) {
  REGION_IDS;
  mbar_wait_cluster(BAR(B_ST1));
  if (lane < 8) red_hint(G->hint[5][lane]);
  const uint2 x = lds64(base + OFF_ST + 8 * (lane & 15)), y = lds64(base + OFF_ST + 128 + 8 * (lane & 15));
  float m, sd;
  ln_final(__uint_as_float(x.x) + __uint_as_float(y.x), __uint_as_float(x.y) + __uint_as_float(y.y), m, sd);
  sd = rbf(rcpf(sd));
  const uint32_t mr = pack_bf16(sd, -rbf(m) * sd), tg = lane & 7 ? 0 : lane & 8 ? 1 : 0x8000;
  const uint32_t o = __byte_perm(__shfl_sync(~0u, mr, 2 * lane & 14), __shfl_sync(~0u, mr, (2 * lane & 14) + 1), (lane & 8) ? 0x7632 : 0x5410);
  if (lane < 16) st_relaxed32(&G->st1[lane >> 3][8 * bid + (lane & 7)], (o & ~tg) | ((epoch & 1) * tg));
  if (elect()) mbar_arrive(BAR(B_FIN));
}
template <int B, int NEXT> __device__ __forceinline__ void strip(Scratch* G, const CUtensorMap* map, uint32_t base, int c, uint32_t epoch, uint32_t& ph, uint32_t& pre, float4& s) {
  REGION_IDS;
  int h, j, r, it = 0;
  ffn_role(h, j, r);
  const uint32_t buf = base + OFF_SX + 4096 * B, a = buf + 32 * lane;
#pragma unroll 1
  while (__any_sync(~0u, pre != 64 * epoch) && ++it < SPIN_LIMIT) pre = ld_relaxed32(G->xsh[c][(r & 6) + (j >> 1)]);
#pragma unroll 1
  for (it = 0; it < SPIN_LIMIT; it++) {
    if (elect()) { mbar_expect_tx(BAR(B_SX + B), 4096); tma2d(buf, map, 128 * r + 64 * h, D_ * (epoch & 1) + 128 * c + 32 * j, BAR(B_SX + B)); }
    mbar_wait(BAR(B_SX + B), ph);
    ph ^= 1;
    if (__all_sync(~0u, min(min(lds32(a), lds32(a + 1024)), min(lds32(a + 2048), lds32(a + 3072))))) break;
  }
  pre = 0;
  if (c == NEXT - 1 || c == NEXT - 2) pre = ld_relaxed32(G->xsh[c + 1][(r & 6) + (j >> 1)]);
#pragma unroll 1
  for (uint32_t o = buf + 4 * lane; o < buf + 4096; o += 1024) {
    uint32_t x[8];
#pragma unroll
    for (int i = 0; i < 8; i++) x[i] = lds32(o + 128 * i);
#pragma unroll
    for (int i = 0; i < 8; i++) { const float lo = bf_lo(x[i]), hi = bf_hi(x[i]); s.x += lo; s.y = fmaf(lo, lo, s.y); s.z += hi; s.w = fmaf(hi, hi, s.w); }
  }
}
__device__ __forceinline__ void mr_poll(Scratch* G, uint32_t base, uint32_t epoch) {
  int it = 0;
#pragma unroll 1
  while (__any_sync(~0u, ld_relaxed32(G->hint[5][4 * (blockIdx.x >> 6) + (blockIdx.x >> 3 & 3)]) != epoch << 7) && ++it < SPIN_LIMIT);
  if (elect()) { mbar_expect_tx(BAR(B_MR), 8192); bulk_load(base + OFF_MR, G->st1, 8192, BAR(B_MR)); mbar_arrive(BAR(B_QTOK)); }
}

__global__ void __cluster_dims__(2, 1, 1) __launch_bounds__(512, 1) k_fused(const __grid_constant__ Ptrs P, const __grid_constant__ Maps maps) {
  Scratch* const G = P.g;
  extern __shared__ __align__(1024) uint8_t smem_raw[];
  const uint32_t t_start = clock();
  const uint32_t base = __shfl_sync(~0u, smem_u32(smem_raw), 0);
  uint32_t t_iss = 0;
  if (threadIdx.x < 32 && blockIdx.x < 128) {
    mbar_init<1>(BAR(0), 1);
    if (elect()) {
      const int c0 = 64 * (blockIdx.x & 1), c1 = 2 * (blockIdx.x & 126);
      mbar_expect_tx(BAR(B_KV), 12288);
      tma3d(base + tab(T_KV, 0), &maps.km, c0, c1, 0, BAR(B_KV));
      tma3d(base + tab(T_KV, 0) + KV_V, &maps.v, c0, c1, 0, BAR(B_KV));
      tma3d(base + tab(T_KV, 0) + KV_H, &maps.kh, c0, c1 - 1, 5, BAR(B_KV));
      tma3d(base + OFF_TAP, &maps.tap, 0, blockIdx.x & 1, 0, BAR(B_KV));
    }
    if (P.boff) mbar_wait(BAR(0));
  }
  if ((base & 0xFFFFFFu) != DB) __trap();
  const int wid = __shfl_sync(~0u, threadIdx.x >> 5, 0), wg = wid >> 2, w = wid & 3;
  if (blockIdx.x + P.boff >= 128) {
    REGION_IDS;
    const int nu = 30 - (P.uhi - P.ulo) / 4;
    auto tile = [&](int n) { return 2 * (n < P.ulo / 4 ? n : n + 30 - nu) + (blockIdx.x >> 1 & 1); };
    auto fetch = [&](int n, int b) {
      if (elect()) {
        mbar_expect_tx(BAR(n), 40960);
#pragma unroll
        for (int k = 0; k < 5; k++) tma3d(base + 40960 * b + 8192 * k, &maps.wm, mod_col(tile(n)), 320 * (blockIdx.x & 1) + 64 * k, 0, BAR(n));
      }
    };
    if (P.boff) __syncthreads();
    if (wid == 12) {
      mbar_init<4>(BAR(0), 1);
#pragma unroll 1
      for (int n = 0; n < 4; n++) fetch(n, n);
      mbar_init<26>(BAR(4), 1);
      mbar_init<60>(BAR(32), 4);
    }
    const uint32_t par = ~ld_relaxed32(G->hint[7][0]) >> 7 & 1;
    silu_vector(P.c, base);
    __syncthreads();
    if (wid == 12) {
      wait_clock(t_start + P.th);
#pragma unroll 1
      for (int n = 4, b = 4; n < nu; n++) {
        if (n >= 5) mbar_wait(BAR(27 + n));
        fetch(n, b);
        b = b == 4 ? 0 : b + 1;
      }
    } else if (wg < 2) {
#pragma unroll 1
      for (int n = wg; n < nu; n += 2) {
        const uint32_t wm = 40960 * (n % 5);
        float d[20] = {};
        mbar_wait(BAR(n));
        fence_regs(d);
        wg_fence();
#pragma unroll 1
        for (int k = 0; k < 20; k += 5) {
#pragma unroll
          for (int e = 0; e < 5; e++) wg_ss8_10(d + 4 * e, mkdesc(DB + wm + 2048 * (k + e), 16, 1024, 1), mkdesc(DB + OFF_CV + 32 * (k + e), 16, 128, 0), 1);
        }
        wg_commit();
        wg_wait<0>();
        fence_regs(d);
        if (elect()) mbar_arrive(BAR(32 + n));
        if (!(lane & 3)) {
          sts32(base + 204800 + 256 * n + 64 * w + lane, __float_as_uint(d[0] + d[4] + d[8] + (d[12] + d[16])));
          sts32(base + 204800 + 256 * n + 64 * w + lane + 32, __float_as_uint(d[2] + d[6] + d[10] + (d[14] + d[18])));
        }
        arrive1(BAR(62 + n));
      }
    } else if (wg == 2) {
#pragma unroll 1
      for (int n = w; n < nu; n += 4) {
        const int t = tile(n), ch = mod_ch(t) + lane;
        uint32_t* q = (uint32_t*)(t < 40 ? &G->modc[ch & 127][8 + (t >> 1)] : &G->modv[t >= 50][ch]) + (bid & 1);
        mbar_wait(BAR(62 + n));
        const uint32_t x = (lds32(base + 204800 + 256 * n + 4 * lane) & ~1u) | par, y = (lds32(base + 204928 + 256 * n + 4 * lane) & ~1u) | par;
        publish(q, x);
        publish(q + (t < 40 ? 2048 : 64), y);
        if (t < 40 && (t & 6) == 6) {
          q = (uint32_t*)&G->modv[2][ch] + (bid & 1);
          publish(q, x);
          publish(q + 64, y);
        }
      }
    }
    return;
  }
  if (wid < 15) mbar_init<4>(BAR(4 * wid + (wid == 0)), wid < 8 ? 1 : 4);
  asm volatile("fence.mbarrier_init.release.cluster; bar.sync 0, 512;" ::: "memory");
  asm volatile("barrier.cluster.arrive.relaxed.aligned;" ::: "memory");
#define LAUNCHES const uint32_t launches = ld_relaxed32(G->hint[7][blockIdx.x >> 4])
#define EPOCH ((__shfl_sync(~0u, launches, 0) >> 7) + 1)
  if (wg == 3) {
    asm volatile("setmaxnreg.dec.sync.aligned.u32 24;");
    if (w == 1) {
      {
        REGION_IDS;
        const int c1 = 2 * (bid & 126), ws = bid >= P.ulo && bid < P.uhi ? P.wms : 99;
#pragma unroll 1
        for (int e = 0; e < NE; e++) {
          const uint2 x = P.sched[e];
          const uint32_t kind = x.x >> 16 & 15, ch = x.x >> 13 & 0x380, dst = base + (x.y & 0x3FFFF), b = BAR(x.y >> 18);
          wait_clock(t_start + (x.x & 0xFFFF));
          if (kind < 3 && elect()) tma3d(dst, &maps.km + kind, ch + 64 * (bid & 1), c1, 0, b);
          if (kind == 0 && elect()) tma3d(dst + KV_H, &maps.kh, ch + 64 * (bid & 1), c1 - 1, 5, b);
          if (kind == 3 && elect()) bulk_load(dst, P.ssmk + (ch + bid) * S_, 4096, b);
          if ((uint32_t)(e - ws) < 5 && elect()) tma3d(base + OFF_WM + 8192 * (e - ws), &maps.wm, mod_col(bid >> 1), 320 * (bid & 1) + 64 * (e - ws), 0, BAR(B_WM));
          if ((uint32_t)(e - 8) < 13 && elect()) prefetch_map(&maps.w1s + (e - 8));
        }
      }
      cluster_wait();
      int h, j, r;
      ffn_role(h, j, r);
      mbar_wait(BAR(B_QTD));
      mbar_wait(BAR(B_FL));
#pragma unroll 1
      for (int u = 0; u < 20; u++) {
        const uint32_t x = P.wdep[u], s = base + (x & ~8191u);
        if (u < 5) wait_clock(t_start + P.wt[u]);
        mbar_wait(BAR(opaque(x & 255)));
        if (elect()) {
          mbar_expect_tx(BAR(B_FULL + u), WSLOT + 4 * (x & 4096));
#pragma unroll
          for (int k = 0; k < 6; k++) tma3d(s + 4096 * w_block(k & 1, k >> 1), &maps.w1s + (k & 1), 0, 32 * u, 3 * (4 * h + j) + (k >> 1), BAR(B_FULL + u));
        }
      }
#pragma unroll 1
      for (int v = 0; v < 12; v++) {
        const int q = v * 11 >> 5, e = v - 3 * q, k32 = 24 * h + (q ? 6 * fslice(j, e) + 2 * q - 2 : 6 * j + 2 * e);
        const uint2 x = P.w2t[v];
        mbar_wait(BAR(x.y));
        if (elect()) {
          mbar_expect_tx(BAR(B_FULL + 20 + v), q ? WSLOT + 2 * ASLOT : WSLOT);
#pragma unroll
          for (int k = 0; k < 3; k++) tma5d(base - DB + 16 * ((x.x & 0xFFFF) + k * (x.x >> 16)), &maps.w2a + (q > 0), k < 2 ? 128 * j + 64 * k : 512 + 32 * (j & 2), k32, BAR(B_FULL + 20 + v));
        }
      }
    } else if (w == 0) {
      LAUNCHES;
      uint32_t epoch;
      {
        REGION_IDS;
        const unsigned* hp = G->hint[0][4 * (bid >> 6) + (bid >> 3 & 3)];
        uint32_t v = ld_relaxed32(hp + 256 * min(lane, 5));
        if (lane < 3) sts128(base + tab(T_X, lane) + 4096, 0, 0, 0, 0);
        if (lane && lane <= B_WM) mbar_expect_tx(BAR(lane), lane < B_FRAW ? 9728 : lane == B_WM ? 40960 : 4096);
        epoch = EPOCH;
        fence_async_smem();
        const uint32_t rdy = __ballot_sync(~0u, v == epoch << 6);
        uint32_t nx = 0, nm = 0;
#pragma unroll 1
        for (uint32_t seq = P.seq; seq; seq >>= 2) {
          int it = 0;
          if (seq & 1) {
            if (!(seq & 2)) mod_poll(G, base, nm, 1 + (seq == 13), epoch);
            nm++;
          } else if (seq & 2) {
            mr_poll(G, base, epoch);
          } else {
            if (!(rdy >> nx & 1)) {
#pragma unroll 1
              while (__any_sync(~0u, ld_relaxed32(hp + 256 * nx) != epoch << 6) && ++it < SPIN_LIMIT);
            }
            if (nx >= 3) mbar_wait(BAR(B_PFULL - 3 + nx));
            if (elect()) { mbar_expect_tx(BAR(B_XR + nx), 4096); bulk_load(base + tab(T_X, nx), G->xr + (128 * nx + bid) * 256, 4096, BAR(B_XR + nx)); }
            nx++;
          }
        }
      }
      REGION_IDS;
      int h, j, r;
      ffn_role(h, j, r);
      mbar_wait(BAR(B_G3));
      {
        const uint2* mp = &G->modv[lane & 4 ? 0 : 2][40 * (r & 14) + (lane & 24) + 2 * (lane & 3)];
        uint4 v[3];
        int it = 0;
#pragma unroll 1
        do {
          v[0] = ld_relaxed128(mp); v[1] = ld_relaxed128(mp + 32); v[2] = ld_relaxed128(mp + 64 - (lane & 16));
        } while (__any_sync(~0u, ((v[0].x ^ epoch) | (v[0].y ^ epoch) | (v[0].z ^ epoch) | (v[0].w ^ epoch) | (v[1].x ^ epoch) | (v[1].y ^ epoch) | (v[1].z ^ epoch) | (v[1].w ^ epoch) |
                                  (v[2].x ^ epoch) | (v[2].y ^ epoch) | (v[2].z ^ epoch) | (v[2].w ^ epoch)) & 1) && ++it < SPIN_LIMIT);
#pragma unroll
        for (int i = 0; i < 3; i++)
          sts32(base + OFF_CO + 128 * i + 4 * lane, badd2(pack_bf16(__uint_as_float(v[i].x) + __uint_as_float(v[i].y), __uint_as_float(v[i].z) + __uint_as_float(v[i].w)), lane & 4 ? 0 : 0x3F803F80u));
      }
      fence_async_smem();
      __syncwarp();
      ffn_role(h, j, r);
      mbar_wait(BAR(B_PEMPTY + 3));
      if (elect()) {
        mbar_expect_tx(BAR(B_UVB), WSLOT);
        tma3d(base + OFF_UV, &maps.w1 + (r & 1), 0, 40 * (r & 14), 3 * (4 * h + j), BAR(B_UVB));
        tma3d(base + OFF_UV + 12288, &maps.w1 + (r & 1), 0, 40 * (r & 14) + 32, 3 * (4 * h + j), BAR(B_UVB));
      }
      {
        float4 s = {};
        uint32_t ph = 0, pre = 0;
#pragma unroll 1
        for (int c = 2; c < 4; c++) strip<1, 3>(G, &maps.x1s, base, c, epoch, ph, pre, s);
        __syncwarp();
        sts128(base + OFF_SX + 4096 + 16 * lane, __float_as_uint(s.x), __float_as_uint(s.y), __float_as_uint(s.z), __float_as_uint(s.w));
        arrive1(BAR(B_S3));
      }
      ffn_role(h, j, r);
      cluster_wait();
      mbar_wait(BAR(B_UVD));
      asm volatile("fence.acq_rel.gpu;" ::: "memory");
      if (lane < 8) red_hint(G->hint[7][lane]);
      unsigned x;
      int it = 0;
#pragma unroll 1
      do { asm volatile("ld.acquire.gpu.global.u32 %0, [%1];" : "=r"(x) : "l"(G->hint[7][bid >> 4]) : "memory"); } while (__any_sync(~0u, x != 128 * epoch) && ++it < SPIN_LIMIT);
      fence_async_all();
      const int ch = D_ * (epoch & 1);
      mbar_wait(BAR(B_EXT));
      mbar_wait(BAR(B_EMPTY + 18));
      if (elect()) {
        mbar_expect_tx(BAR(B_FULL + 32), 20480);
#pragma unroll
        for (int k = 0; k < 4; k++) tma2d(base + (k < 3 ? OFF_X1 + k * WSLOT : OFF_SX), &maps.x1b, 128 * r + 64 * h, ch + 128 * j + 32 * (k ^ (j & 1)), BAR(B_FULL + 32));
        tma2d(base + OFF_SX + 4096, &maps.x1b, 128 * r + 64 * h, ch + 512 + 32 * j, BAR(B_FULL + 32));
        mbar_expect_tx(BAR(B_FULL), 8192); mbar_expect_tx(BAR(B_FULL + 1), 8192); mbar_expect_tx(BAR(B_FULL + 2), 4096);
      }
      mbar_wait(BAR(B_EMPTY + 27));
      if (elect()) mbar_arrive_remote(mapa(BAR(B_XFREE), h ^ 1));
    } else {
      LAUNCHES;
      uint32_t epoch;
      {
        REGION_IDS;
        uint32_t dv;
        asm volatile("ld.global.nc.u16 %0, [%1];" : "=r"(dv) : "l"(P.ssmd + 128 * (lane & 7) % D_ + bid));
        if (lane < 5) sts128(base + tab(T_F, lane) + (w & 1) * (F_O - 16), 0, 0, 0, 0);
        epoch = EPOCH;
        __syncwarp();
#pragma unroll 1
        for (int c = 0; c < 5; c++) {
          const float d = i0 == 64 ? bf_lo(dv) : 0.f;
          dv = __shfl_down_sync(~0u, dv, 1);
          const uint32_t a = base + tab(T_F, c) + 16 * (i0 - 64);
          mbar_wait(BAR(B_FRAW + c));
#pragma unroll
          for (int k = 0; k < 4; k++) {
            uint4 x = lds128(a + F_E + 1024 * k);
            const uint32_t pv = lds32(a + F_E - 4 + 1024 * k);
            if (k == 0) { x.x = pack_bf16(bf_lo(x.x) + d, bf_hi(x.x)); sts32(a + F_E, x.x); }
            sts128(a + F_O + 1024 * k, __byte_perm(pv, x.x, 0x5432), __byte_perm(x.x, x.y, 0x5432), __byte_perm(x.y, x.z, 0x5432), __byte_perm(x.z, x.w, 0x5432));
          }
          __syncwarp();
          if (elect()) mbar_arrive2(BAR(B_FRDY + c));
          if (c == 0 && w == P.fin) row_stats(G, base, epoch);
        }
      }
      REGION_IDS;
      int h, j, r;
      ffn_role(h, j, r);
      cluster_wait();
      if (w == 2) {
        const unsigned* fp = G->xsh[lane < 10 ? lane >> 1 : 0][(r & 6) + (lane & 1)];
        uint32_t rdy = 0, s = 0;
        mbar_wait(BAR(B_QTD));
        mbar_wait(BAR(B_FL + 2));
#pragma unroll 1
        for (int n = 0; n < 10; n++) {
          mbar_wait(BAR(n < 2 ? B_FL + 3 + n : n == 2 ? B_PFULL + 4 : B_EMPTY + 2 * n - 5));
#pragma unroll 1
          for (int it = 0; !(rdy >> n & 1) && it < SPIN_LIMIT; it++) rdy = __ballot_sync(~0u, ld_relaxed32(fp) == 64 * epoch);
          if (elect()) {
            tma2d(base + OFF_A + s, &maps.xs, 128 * r + 64 * h, 64 * n, BAR(B_FULL + 2 * n));
            tma2d(base + OFF_A + ARING + s, &maps.xs, 128 * r + 64 - 64 * h, 64 * n, BAR(B_FULL + 2 * n));
          }
          s = s == 2 * ASLOT ? 0 : s + ASLOT;
        }
      } else {
        if (P.m3 < 5) mod_poll(G, base, P.m3, 1, epoch);
        float4 s = {};
        uint32_t ph = 0, pre = 0;
        mbar_wait(BAR(B_FL + 2));
        mbar_wait(BAR(B_PFULL + 3));
#pragma unroll 1
        for (int c = 0; c < 5; c = c == 1 ? 4 : c + 1) {
          if (c == 4) {
            ffn_role(h, j, r);
            mbar_wait(BAR(B_PEMPTY + 4));
            if (elect()) {
              mbar_expect_tx(BAR(B_UVE), 6144);
              tma3d(base + OFF_UVE, &maps.w1e + (r & 1), 0, 40 * (r & 14) + 64, 3 * (4 * h + j), BAR(B_UVE));
            }
          }
          strip<0, 1>(G, &maps.x1s, base, c, epoch, ph, pre, s);
        }
        mbar_wait(BAR(B_S3));
        const uint4 y = lds128(base + OFF_SX + 4096 + 16 * lane);
        const float s0 = s.x + __uint_as_float(y.x), q0 = s.y + __uint_as_float(y.y), s1 = s.z + __uint_as_float(y.z), q1 = s.w + __uint_as_float(y.w);
        ffn_role(h, j, r);
        asm volatile("{.reg .b128 t, x; .reg .b64 a, b; mov.b64 a, {%1,%2}; mov.b64 b, {%3,%4}; mov.b128 x, {a,b}; atom.relaxed.gpu.global.exch.b128 t, [%0], x;}"
                     ::"l"(&G->st2[2 * r + h][j][4 * lane]), "r"((__float_as_uint(s0) & ~1u) | (epoch & 1)), "f"(q0), "r"((__float_as_uint(s1) & ~1u) | (epoch & 1)), "f"(q1) : "memory");
        uint4* z = G->x1[~epoch & 1] + 1280 * bid + lane;
#pragma unroll 1
        for (int k = 0; k < 40; k++) st_relaxed128(z + 32 * k, 0, 0, 0, 0);
      }
    }
  } else if (wg == 2) {
    asm volatile("setmaxnreg.dec.sync.aligned.u32 40;");
    mbar_init<12>(BAR(B_FULL + 12 * w), 1);
    mbar_init<9>(BAR(B_EMPTY - 1 + 9 * w), 8);
    asm volatile("fence.mbarrier_init.release.cluster;" ::: "memory");
    LAUNCHES;
    const uint32_t epoch = EPOCH;
    cluster_wait();
#pragma unroll 1
    for (uint64_t prog = P.prog; prog; prog >>= 4) {
      REGION_IDS;
      const int s = (prog & 7) - 1;
      if (!(prog & 8)) {
        const uint32_t a = base + tab(T_KV, s) + 128 * (lane & 3) + ((w ^ (lane & 3)) << 4) + 4 * (lane & 16) + (lane & 12), keep = ~(lane & 1), bit = epoch & lane & 1;
        uint4* dst = G->xr + (128 * s + 64 * (bid & 1) + 8 * w + 2 * (lane & 16) + (lane >> 1 & 6)) * 256 + 255 - 4 * (bid >> 1) - (lane & 3);
        mbar_wait(BAR(B_KV));
        mbar_wait(BAR(B_KV + s));
        const uint4 wv = lds128(base + OFF_TAP + 512 * s + 64 * w + 16 * (lane & 16) + 4 * (lane & 12));
        uint32_t kk[11], r[8];
#pragma unroll
        for (int k = 0; k < 11; k++) kk[k] = k < 3 ? lds32((a ^ (64 * (k & 1))) + KV_H + 512 * k) : lds32((a ^ (64 * (~k & 1))) + 512 * (k - 3));
        if (elect()) red_hint(G->hint[s][4 * (bid & 1) + w]);
#pragma unroll
        for (int k = 0; k < 8; k++) r[k] = lds32((a ^ (64 * (k & 1))) + KV_V + 512 * k);
        const uint32_t w0 = __byte_perm(wv.x, wv.z, 0x5410), w1 = __byte_perm(wv.x, wv.z, 0x7632),
                       w2 = __byte_perm(wv.y, wv.w, 0x5410), w3 = __byte_perm(wv.y, wv.w, 0x7632);
#pragma unroll
        for (int k = 0; k < 8; k++) r[k] = bmul2(bfma2(kk[k + 3], w0, bfma2(kk[k + 2], w1, bfma2(kk[k + 1], w2, bmul2(kk[k], w3)))), r[k]);
        st_relaxed128(dst, (__byte_perm(r[7], r[6], 0x5410) & keep) | bit, __byte_perm(r[5], r[4], 0x5410), __byte_perm(r[3], r[2], 0x5410), __byte_perm(r[1], r[0], 0x5410));
        st_relaxed128(dst + 256, (__byte_perm(r[7], r[6], 0x7632) & keep) | bit, __byte_perm(r[5], r[4], 0x7632), __byte_perm(r[3], r[2], 0x7632), __byte_perm(r[1], r[0], 0x7632));
      } else if (s >= 0) {
        const int tr = 4 * (lane & 1) + (lane >> 1 & 3);
        const uint32_t a = base + OFF_Q + 4096 * s + 128 * ((lane & 24) + tr) + ((w ^ tr) << 4);
        uint4* dst = G->qt + (128 * s + 64 * (bid & 1) + 8 * w + (lane >> 2)) * 256 + 4 * (bid >> 1) + (lane & 3);
        mbar_wait(BAR(B_Q + s));
#pragma unroll
        for (int k = 0; k < 2; k++) {
          uint32_t x[4];
          ldmatrix_x4_t(x, a ^ (64 * k));
          st_relaxed128(dst + 8192 * k, set_tag(x[0], ~lane & 1, epoch), x[1], x[2], x[3]);
        }
      } else if (w == 3) {
        row_stats(G, base, epoch);
      }
    }
    arrive1(BAR(B_QTD));
    {
      REGION_IDS;
      const uint32_t tag = opaque(~lane & 1);
      const uint32_t io = 16 * i0;
      uint4* gp = (uint4*)((char*)(G->xs + 256 * blockIdx.x) + io);
      constexpr int QO = -D_ * 256;
      const uint32_t sa = base + io;
      uint4 q[2];
      if (w == 0 && P.mr2) mr_poll(G, base, epoch);
      mbar_wait(BAR(B_QTOK));
      q[0] = ld_relaxed128(gp + QO);
      q[1] = ld_relaxed128(gp + QO + 128);
#pragma unroll 1
      for (int it = 0; it < SPIN_LIMIT; it++) {
        mbar_wait(BAR(B_MR), it & 1);
        const uint32_t x = lds32(sa + 16 * i0 + OFF_MR), y = lds32(sa + 16 * i0 + OFF_MR + 4096);
        sts32(sa + 16 * i0 + OFF_MR, x & 0xFFFF7FFFu);
        if (bar_all(3, !(((x >> 15 ^ epoch) | (y ^ epoch)) & 1))) break;
        if (w == 0 && elect()) { fence_async_smem(); mbar_expect_tx(BAR(B_MR), 8192); bulk_load(base + OFF_MR, G->st1, 8192, BAR(B_MR)); }
      }
#pragma unroll 1
      for (int c = 0; c < 5; c++) {
        mbar_wait(BAR(B_MODR + c));
        uint4 co = lds128(base + OFF_MODR + 16 * c);
        co.x = bmul2(co.x, co.z); co.y = bmul2(co.y, co.z);
        mbar_wait(BAR(B_PFULL + c));
        const uint32_t pb = io + (base + tab(T_P, c));
        gp = (uint4*)((char*)(G->xs + 256 * blockIdx.x + 32768 * c) + io);
#pragma unroll
        for (int hf = 0; hf < 2; hf++) {
#pragma unroll 1
          for (int it = 0; __any_sync(~0u, set_tag(q[hf].x, tag, epoch) != q[hf].x) && it < SPIN_LIMIT; it++) {
            q[hf] = ld_relaxed128(gp + QO + 128 * hf);
          }
          uint4 y = lds128(pb + 2048 * hf), z = lds128(pb + 2048 * hf + 4096);
          y.x = badd2(y.x, z.x); y.y = badd2(y.y, z.y); y.z = badd2(y.z, z.z); y.w = badd2(y.w, z.w);
          z = lds128(pb + 2048 * hf + 8192);
          uint4 m = lds128(pb + 2048 * hf + 12288);
          y.x = badd2(y.x, badd2(z.x, m.x)); y.y = badd2(y.y, badd2(z.y, m.y)); y.z = badd2(y.z, badd2(z.z, m.z)); y.w = badd2(y.w, badd2(z.w, m.w));
          z = lds128(sa + OFF_MR + 2048 * hf);
          m = lds128(sa + OFF_MR + 2048 * hf + 4096);
          y.x = bfma2(bfma2(bfma2(q[hf].x, z.x, m.x), co.y, co.x), y.x, q[hf].x);
          if (hf) {
            __syncwarp();
            asm volatile("{.reg .pred p; elect.sync _|p, 0xffffffff; @p red.relaxed.gpu.global.add.u32 [%0], 1; @p mbarrier.arrive.shared::cta.b64 _, [%1];}"
                         ::"l"(G->xsh[c][2 * w + (blockIdx.x >> 6)]), "r"(BAR(B_PEMPTY + c)), "r"(y.x) : "memory");
          }
          y.y = bfma2(bfma2(bfma2(q[hf].y, z.y, m.y), co.y, co.x), y.y, q[hf].y);
          y.z = bfma2(bfma2(bfma2(q[hf].z, z.z, m.z), co.y, co.x), y.z, q[hf].z);
          y.w = bfma2(bfma2(bfma2(q[hf].w, z.w, m.w), co.y, co.x), y.w, q[hf].w);
          st_relaxed128(gp + 128 * hf, set_tag(bmul2(y.x, co.w), tag, epoch), bmul2(y.y, co.w), bmul2(y.z, co.w), bmul2(y.w, co.w));
          asm volatile("{.reg .pred p; .reg .b32 t; setp.ne.u32 p, %5, 0; max.u32 t, %1, 1; @!p st.relaxed.gpu.global.v4.u32 [%0+%6], {t,%2,%3,%4}; @p st.relaxed.gpu.global.v4.u32 [%0+%7], {t,%2,%3,%4};}"
                       ::"l"(gp + 128 * hf), "r"(y.x), "r"(y.y), "r"(y.z), "r"(y.w), "r"(epoch & 1), "n"(D_ * 4096), "n"(D_ * 8192) : "memory");
          if (c < 4) q[hf] = ld_relaxed128(gp + QO + 32768 + 128 * hf);
        }
      }
    }
    int h, j, r;
    ffn_role(h, j, r);
    {
      REGION_IDS;
      mbar_wait(BAR(B_UVB));
      float d[12] = {};
      fence_regs(d);
      wg_fence();
#pragma unroll
      for (int k = 0; k < 15; k++) {
        if (k == 12) { wg_commit(); mbar_wait(BAR(B_UVE)); wg_fence(); }
        wg_ss8_10(d + 4 * (k % 3), mkdesc(DB + (k < 12 ? OFF_UV + 12288 * (k / 6) + 4096 * (k % 3) + 2048 * (k / 3 & 1) : OFF_UVE + 2048 * (k % 3)), 16, 1024, 1),
                  mkdesc(DB + OFF_CO + 64 * (k / 3), 32, 128, 0), 1);
      }
      wg_commit();
      const int row = (r & 14) + (lane >> 2 & 1);
      uint32_t* dst = &G->uv[4 * h + j][32 * row + 4 * ((2 * w ^ row) & 6) + (lane & 3)];
      const uint32_t tag = !(lane & 3);
      wg_wait<0>();
      fence_regs(d);
      if (elect()) { red_hint(G->hint[8][4 * h + j]); mbar_arrive(BAR(B_UVD)); }
      uint32_t x[6];
#pragma unroll
      for (int k = 0; k < 6; k++) asm volatile("movmatrix.sync.aligned.m8n8.trans.b16 %0, %1;" : "=r"(x[k]) : "r"(pack_bf16(d[2 * k], d[2 * k + 1])));
      if (lane < 8) {
#pragma unroll
        for (int k = 0; k < 6; k++) st_relaxed32(dst + 512 * w_block(r & 1, k >> 1) + ((4 * k ^ lane) & 4), set_tag(x[k], tag, epoch));
      }
    }
    {
      REGION_IDS;
      if (w == 0) {
        int it = 0;
#pragma unroll 1
        while (__any_sync(~0u, ld_relaxed32(G->hint[8][4 * h + j]) != 64 * epoch) && ++it < SPIN_LIMIT);
        if (elect()) { mbar_expect_tx(BAR(B_BX), 12288); bulk_load(base + OFF_BX, G->uv[4 * h + j], 12288, BAR(B_BX)); }
      }
      const uint32_t* sp = &G->st2[2 * r + (h ^ (w >> 1))][0][2 * (i0 & 63)];
      uint2 x[4];
      int it = 0;
#pragma unroll 1
      do {
#pragma unroll
        for (int k = 0; k < 4; k++) x[k] = ld_relaxed64(sp + 128 * k);
      } while (__any_sync(~0u, ((x[0].x ^ epoch) | (x[1].x ^ epoch) | (x[2].x ^ epoch) | (x[3].x ^ epoch)) & 1) && ++it < SPIN_LIMIT);
      float m, sd;
      ln_final((__uint_as_float(x[0].x) + __uint_as_float(x[1].x)) + (__uint_as_float(x[2].x) + __uint_as_float(x[3].x)),
               (__uint_as_float(x[0].y) + __uint_as_float(x[1].y)) + (__uint_as_float(x[2].y) + __uint_as_float(x[3].y)), m, sd);
      const uint32_t e = pack_bf16(-m, sd);
      sts128(base + OFF_AX + 16 * i0, e, e, e, e);
      sts32(base + OFF_RT + 4 * i0, __float_as_uint(rcpf(sd)));
      fence_async_smem();
#pragma unroll 1
      for (it = 0; it < SPIN_LIMIT; it++) {
        mbar_wait(BAR(B_BX), it & 1);
        uint32_t y = 0;
#pragma unroll
        for (int k = 0; k < 6; k++) y |= lds32(base + OFF_BX + 16 * i0 + 2048 * k) ^ epoch;
        if (bar_all(3, !(y & 1))) break;
        if (w == 0 && elect()) { mbar_expect_tx(BAR(B_BX), 12288); bulk_load(base + OFF_BX, G->uv[4 * h + j], 12288, BAR(B_BX)); }
      }
      arrive1(BAR(B_EXT));
      {
        uint2 g0, g1;
        int it = 0;
#pragma unroll 1
        do {
          g0 = ld_relaxed64(&G->modv[1][128 * j + i0]);
          g1 = ld_relaxed64(&G->modv[1][512 + 32 * j + lane]);
        } while (__any_sync(~0u, ((g0.x ^ epoch) | (g0.y ^ epoch) | (g1.x ^ epoch) | (g1.y ^ epoch)) & 1) && ++it < SPIN_LIMIT);
        const uint32_t ga = base + OFF_GB + 80 * (lane >> 1 & 3) + 2 * (lane & 1) + (lane >> 3) * 4;
        asm volatile("st.shared.u16 [%0], %1;" ::"r"(ga + 16 * (w ^ (j & 1))), "h"((uint16_t)(mod_sum(g0) >> 16)) : "memory");
        asm volatile("st.shared.u16 [%0], %1;" ::"r"(ga + 64), "h"((uint16_t)(mod_sum(g1) >> 16)) : "memory");
        arrive1(BAR(B_GB));
      }
      const int id = 16 * r + 4 * h + fslice(j, w);
#pragma unroll 1
      for (int q = w == 3 ? 3 : 0; q < 3; q++) {
        const int m = 3 * q + w;
        const uint4* src = G->hh + id * 1536 + 512 * q;
        it = 0;
#pragma unroll 1
        while (__any_sync(~0u, ld_relaxed32(&G->hhf[8 * id + 64 * (lane & 1) + q]) != 4 * epoch) && ++it < SPIN_LIMIT);
        mbar_wait(BAR(P.hid[2][m]));
        if (elect()) {
          bulk_load(base + OFF_A + h * ARING + P.hid[h][m], src, ASLOT, BAR(B_FULL + 23 + m));
          bulk_load(base + OFF_A + ARING - h * ARING + P.hid[h ^ 1][m], src + 8 * 1536, ASLOT, BAR(B_FULL + 23 + m));
        }
      }
    }
  } else {
    asm volatile("setmaxnreg.inc.sync.aligned.u32 224;");
    LAUNCHES;
    if (wg == 1) silu_vector(P.c, base);
    uint32_t par = EPOCH & 1;
    cluster_wait();
    {
      float acc[128];
      uint32_t A[64];
#pragma unroll
      for (int i = 0; i < 64; i++) A[i] = 0;
      int c = wg;
#pragma unroll 1
      for (uint64_t prog = P.cprog[wg]; prog; prog >>= 8) {
        REGION_IDS;
        const int s = prog & 7;
        if (s < 5) {
          const uint32_t a = base + tab(T_KV, s) + 128 * (lane & 3) + ((w ^ (lane & 3)) << 4) + 4 * (lane & 16) + (lane & 12), keep = ~(lane & 1), bit = par & lane;
          uint4* dst = G->xr + (128 * s + 64 * (bid & 1) + 8 * w + 2 * (lane & 16) + (lane >> 1 & 6)) * 256 + 255 - 4 * (bid >> 1) - (lane & 3);
          mbar_wait(BAR(B_KV));
          mbar_wait(BAR(B_KV + s));
          const uint4 wv = lds128(base + OFF_TAP + 512 * s + 64 * w + 16 * (lane & 16) + 4 * (lane & 12));
          uint32_t kk[11], r[8];
#pragma unroll
          for (int k = 0; k < 11; k++) kk[k] = k < 3 ? lds32((a ^ (64 * (k & 1))) + KV_H + 512 * k) : lds32((a ^ (64 * (~k & 1))) + 512 * (k - 3));
          if (elect()) red_hint(G->hint[s][4 * (bid & 1) + w]);
#pragma unroll
          for (int k = 0; k < 8; k++) r[k] = lds32((a ^ (64 * (k & 1))) + KV_V + 512 * k);
          const uint32_t w0 = __byte_perm(wv.x, wv.z, 0x5410), w1 = __byte_perm(wv.x, wv.z, 0x7632),
                         w2 = __byte_perm(wv.y, wv.w, 0x5410), w3 = __byte_perm(wv.y, wv.w, 0x7632);
#pragma unroll
          for (int k = 0; k < 8; k++) r[k] = bmul2(bfma2(kk[k + 3], w0, bfma2(kk[k + 2], w1, bfma2(kk[k + 1], w2, bmul2(kk[k], w3)))), r[k]);
          st_relaxed128(dst, (__byte_perm(r[7], r[6], 0x5410) & keep) | bit, __byte_perm(r[5], r[4], 0x5410), __byte_perm(r[3], r[2], 0x5410), __byte_perm(r[1], r[0], 0x5410));
          st_relaxed128(dst + 256, (__byte_perm(r[7], r[6], 0x7632) & keep) | bit, __byte_perm(r[5], r[4], 0x7632), __byte_perm(r[3], r[2], 0x7632), __byte_perm(r[1], r[0], 0x7632));
        }
        if (prog & 8) {
          float s0 = 0.f, s1 = 0.f, q0 = 0.f, q1 = 0.f;
          const uint32_t a = OFF_Q + 1024 * w + 128 * (lane & 7) + (((lane >> 3) ^ (lane & 7)) << 4);
          const uint32_t ra = mapa(base + OFF_ST + 128 * (bid & 1) + 64 * (lane & 1) + 16 * w + 8 * (lane >> 2), lane >> 1 & 1), rb = mapa(BAR(B_ST1), lane >> 1 & 1);
          if (w == 3 && elect()) mbar_expect_tx(BAR(B_ST1), 256);
#pragma unroll 1
          for (int k = 0; k < 5; k++) {
            mbar_wait(BAR(B_Q + k));
            const uint32_t o = opaque(base + 4096 * k);
            const uint4 x = lds128(o + a), y = lds128(o + (a ^ 64));
            const uint32_t e[8] = {x.x, x.y, x.z, x.w, y.x, y.y, y.z, y.w};
#pragma unroll
            for (int i = 0; i < 8; i++) { const float lo = bf_lo(e[i]), hi = bf_hi(e[i]); s0 += lo; s1 += hi; q0 = fmaf(lo, lo, q0); q1 = fmaf(hi, hi, q1); }
          }
          s0 += s1; q0 += q1;
          s0 += __shfl_xor_sync(~0u, s0, 8); q0 += __shfl_xor_sync(~0u, q0, 8);
          s0 += __shfl_xor_sync(~0u, s0, 16); q0 += __shfl_xor_sync(~0u, q0, 16);
          if (lane < 8) asm volatile("st.async.shared::cluster.mbarrier::complete_tx::bytes.v2.b32 [%0], {%1,%2}, [%3];" ::"r"(ra), "r"(__float_as_uint(s0)), "r"(__float_as_uint(q0)), "r"(rb) : "memory");
        }
        if (prog & 32) {
          const int L = 16 * w + (lane >> 2) + 2 * (lane & 3) - 7;
          const uint32_t fo = base + ((L & 1) ? F_O + 2 * (L + 1) : F_E + 2 * L);
          mbar_wait(BAR(B_FRDY + c));
          cload<0, 0>(A, fo + tab(T_F, c));
          cload<15, 1>(A, fo + tab(T_F, c));
          arrive1(BAR(B_FL + c));
        }
        if (!(prog & 64)) continue;
        uint32_t xo;
        if (P.turn >> c & 1) mbar_wait(BAR(B_TURN - 3 + c));
        if (c == 0) mbar_wait(BAR(P.c0));
#pragma unroll 1
        for (int it = 0; it < SPIN_LIMIT; it++) {
          xo = tab(T_X, opaque(c));
          mbar_wait(BAR(B_XR + c), it & 1);
          const uint32_t tag = lds32(base + xo + 32 * i0);
          wg_fence();
          csteps<0, 0>(acc, A, mkdesc(DB + xo, 16, 128, 0));
          csteps<15, 6>(acc, A, mkdesc(DB + xo, 16, 128, 0));
          wg_commit();
          if (bar_all(1 + wg, !((tag ^ par) & 1))) break;
          wg_wait<0>();
          if (w == 0 && elect()) { mbar_expect_tx(BAR(B_XR + c), 4096); bulk_load(base + xo, G->xr + (128 * c + bid) * 256, 4096, BAR(B_XR + c)); }
        }
        wg_fence();
        csteps<5, 1>(acc, A, mkdesc(DB + tab(T_X, opaque(c)), 16, 128, 0));
        wg_commit();
        if (c >= 2 && c < 4 && elect()) mbar_arrive(BAR(B_TURN - 2 + c));
        if (c >= 3) mbar_wait(BAR(B_PEMPTY + c - 3));
        wg_wait<0>();
        fence_regs(acc);
        const uint32_t pb = base + tab(T_P, c) + 4096 * w;
#pragma unroll
        for (int k = 0; k < 8; k++) {
          uint32_t p[4];
#pragma unroll
          for (int e = 0; e < 4; e++) { const int i = 4 * k + e; p[e] = i < 31 ? pack_bf16(acc[4 * i] + acc[4 * i + 6], acc[4 * i + 1] + acc[4 * i + 7]) : pack_bf16(acc[124], acc[125]); }
          if (k == 0 && (lane & 3) < w) p[0] = 0;
          stmatrix_x4_t(k == 0 ? pb + 16 * ((255 - lane + 2 * w) & 255) : pb + 16 * (255 - lane + 2 * w) - 512 * k, p[0], p[1], p[2], p[3]);
        }
        arrive1(BAR(B_PFULL + c));
        c += 2;
      }
    }
    if (wg) {
      REGION_IDS;
      if (bid >= P.ulo && bid < P.uhi) {
        named_bar(2, 128);
        mbar_wait(BAR(B_WM));
        mod_gemv(G, OFF_WM, bid, w, lane, par);
      }
      arrive1(BAR(B_G3));
    }
    uint32_t ck;
    { REGION_IDS; ck = base + OFF_A + wg * ARING + lane * 128 + (((2 * w) ^ (lane & 7)) << 4); }
    const uint32_t abd = DB + OFF_A + wg * ARING;
    auto a_tile = [&](int as, int n, bool first) {
#pragma unroll 1
      for (int it = 0; __any_sync(~0u, ((lds32(ck + as) ^ par) | (lds32(ck + as + (first ? 4096 : 256)) ^ par)) & 1) && it < SPIN_LIMIT; it++) {
        int h, j, r;
        ffn_role(h, j, r);
        if (elect()) {
          const uint32_t dst = base + OFF_A + wg * ARING + as;
          mbar_expect_tx(BAR(B_RETRY + wid), ASLOT);
          if (first) tma2d(dst, &maps.xs, 128 * r + 64 * (h ^ wg), 64 * n, BAR(B_RETRY + wid));
          else bulk_load(dst, G->hh + ((2 * r + (h ^ wg)) * 8 + 4 * h + fslice(j, n % 3)) * 1536 + (n / 3) * 512, ASLOT, BAR(B_RETRY + wid));
        }
        mbar_wait(BAR(B_RETRY + wid), par >> 1);
        par ^= 2;
      }
    };
    float acc[192];
    int ws = 0, as = 0;
#pragma unroll 1
    for (int u = 0; u < 20 - NT; u++) {
      mbar_wait(BAR(B_FULL + u));
      if (!(u & 1)) a_tile(as, u >> 1, true);
      wg_fence();
#pragma unroll
      for (int k = 0; k < 4; k++) wg_ss192_11(acc + 96 * (k & 1), mkdesc(abd + as + k / 2 * 2048, 16, 1024, 1), mkdesc(DB + ws + 12288 * (k & 1) + k / 2 * 2048, 4096, 1024, 1), u + k / 2);
      wg_commit();
      wg_wait<1>();
      if (elect()) mbar_arrive(BAR(B_EMPTY + u - 1));
      ws = next_slot(ws);
      as = as == 5 * ASLOT / 2 ? 0 : as + ASLOT / 2;
    }
    auto tail = [&](int v, int i) {
      const int u = 20 - NT + i / 2;
      if (i < 2 * NT) wg_ss192_11(acc + 96 * v, mkdesc(opaque(abd) + u % 6 * 4096 + (i & 1) * 2048, 16, 1024, 1), mkdesc(DB + u % 5 * WSLOT + (i & 1) * 2048 + 12288 * v, 4096, 1024, 1), 1);
      if (i == 2 * NT) wg_ss192_01(acc + 96 * v, mkdesc(DB + OFF_AX + 1024 * opaque(wg), 0, 128, 0), mkdesc(DB + OFF_BX + 6144 * v, 2048, 1024, 1), 1);
    };
#pragma unroll
    for (int u = 20 - NT; u <= 20; u++) {
      mbar_wait(BAR(u < 20 ? B_FULL + u : B_EXT));
      if (u == 16 || u == 18) a_tile(u % 6 * 4096, u >> 1, true);
      wg_fence();
      tail(0, 2 * (u + NT - 20));
      tail(0, 2 * (u + NT - 20) + 1);
      wg_commit();
      if (u == 20 - NT) { wg_wait<1>(); if (elect()) mbar_arrive(BAR(B_EMPTY + u - 1)); }
    }
    float o[80];
    uint32_t fr[3][16], bo;
    {
      int h, j, r;
      ffn_role(h, j, r);
      REGION_IDS;
      const float r0 = 0.5f * __uint_as_float(lds32(base + OFF_RT + 256 * wg + 64 * w + (lane & 28))), r1 = 0.5f * __uint_as_float(lds32(base + OFF_RT + 256 * wg + 64 * w + 32 + (lane & 28)));
      const int id = (2 * r + (h ^ wg)) * 8 + 4 * h + j;
      uint4* const hdst = G->hh + id * 1536 + 128 * w + (lane ^ lane >> 3);
      const uint32_t keep = ~(~lane & 1), bit = par & ~keep;
      bo = 1024 + ((j & 1) << 23);
      auto own = [&](int i) { wg_rs160_1(o, fr[i >> 2] + 4 * (i & 3), mkdesc(DB + (5 + i / 4) % 6 * WSLOT + (i & 3) * 2048, 8192, bo, 1), i); };
      auto gate = [&](float* g, int d) {
#pragma unroll
        for (int e = 0; e < 4; e++) { g[e] *= e < 2 ? r0 : r1; g[e + d] *= g[e]; asm("tanh.approx.f32 %0, %0;" : "+f"(g[e])); }
      };
      auto mix = [&](uint32_t* x, const float* g, int d) {
        x[0] = pack_bf16(fmaf(g[d], g[0], g[d]), fmaf(g[d + 1], g[1], g[d + 1]));
        x[1] = pack_bf16(fmaf(g[d + 2], g[2], g[d + 2]), fmaf(g[d + 3], g[3], g[d + 3]));
      };
      auto hint = [&](int v) { asm volatile("{.reg .pred p; setp.eq.u32 p, %1, 0; @p red.relaxed.gpu.global.add.u32 [%0], 1;}" ::"l"(&G->hhf[id * 8 + v]), "r"(lane) : "memory"); };
      auto put = [&](int v, int k) {
        uint32_t* x = fr[v] + 2 * k;
        const uint32_t t0 = (x[k / 2] & keep) | bit, t1 = (x[5 + k / 2] & keep) | bit;
        if (!v) { x[k / 2] = t0; x[5 + k / 2] = t1; }
        st_relaxed128(hdst + 512 * v + 8 * k, k ? x[0] : t0, k ? t0 : x[2], x[4], x[6]);
        st_relaxed128(hdst + 512 * v + 8 * k + 64, x[1], x[3], k ? x[5] : t1, k ? t1 : x[7]);
      };
      auto move = [&](uint32_t* x) {
#pragma unroll
        for (int k = 0; k < 16; k++) asm volatile("mul.rn.f32 %0, %0, %1;" : "+r"(x[k]) : "f"(P.one));
      };
      wg_fence();
      tail(1, 0);
      tail(1, 1);
      wg_commit();
      wg_wait<1>();
#pragma unroll
      for (int k = 0; k < 96; k++) asm volatile("" : "+f"(acc[k])::"memory");
      if (elect()) mbar_arrive(BAR(B_EMPTY + 18));
      gate(acc + 28, 32);
#pragma unroll
      for (int k = 7; k >= 0; k--) {
        if (k >= 8 - 2 * NT) split(P.ulo, k);
        if (k > 8 - 2 * NT) tail(1, 9 - k);
        if (k == 9 - 2 * NT) wg_commit();
        if (k) gate(acc + 4 * k - 4, 32);
        mix(fr[0] + 2 * k, acc + 4 * k, 32);
        if (k == 1) hint(0);
        if (!(k & 3)) put(0, k);
      }
      move(fr[0]);
      split(P.ulo, 14);
      wg_wait<0>();
#pragma unroll
      for (int k = 96; k < 192; k++) asm volatile("" : "+f"(acc[k])::"memory");
      if (elect()) mbar_arrive(BAR(B_EMPTY + 19));
#pragma unroll
      for (int k = 7; k >= 0; k--) gate(acc + 64 + 4 * k, 96);
      mbar_wait(BAR(B_FULL + 20));
      mbar_wait(BAR(B_FULL + 21));
#pragma unroll
      for (int k = 7; k >= 0; k--) mix(fr[1] + 2 * k, acc + 64 + 4 * k, 96);
#pragma unroll
      for (int k = 0; k < 4; k++) pin4(P.ulo, fr[1] + 4 * k);
      wg_fence();
      own(0);
      own(1);
      split(P.ulo, 15);
      put(1, 4);
      hint(1);
      own(2);
      put(1, 0);
      own(3);
      wg_commit();
      gate(acc + 124, 32);
#pragma unroll
      for (int k = 7; k >= 0; k--) {
        if (k & 1 || k == 6) split(P.ulo, 16 + k);
        if (!(k & 1)) own(7 - k / 2);
        if (k == 4 || k == 0) wg_commit();
        if (k == 4) { wg_wait<1>(); if (elect()) mbar_arrive(BAR(B_EMPTY + 20)); }
        if (k) gate(acc + 92 + 4 * k, 32);
        mix(fr[2] + 2 * k, acc + 96 + 4 * k, 32);
        if (k == 1) hint(2);
        if (!(k & 3)) put(2, k);
      }
      mbar_wait(BAR(B_FULL + 22));
      wg_fence();
#pragma unroll
      for (int i = 8; i < 12; i++) own(i);
      wg_commit();
      wg_wait<1>();
      if (elect()) mbar_arrive(BAR(B_EMPTY + 21));
      ck = base + OFF_A + wg * ARING + 2048 * w + 516 * (lane >> 3) + 144 * (lane >> 2 & 1) + 32 * (lane & 3);
    }
    uint32_t x1[40];
    if (!wg) {
      REGION_IDS;
      const uint32_t xa = base + (lane >> 4) * 1024 + (lane & 7) * 128 + (((2 * w + ((lane >> 3) & 1)) ^ (lane & 7)) << 4);
      mbar_wait(BAR(B_FULL + 32));
#pragma unroll
      for (int k = 0; k < 10; k++) ldmatrix_x4_t(x1 + 4 * k, xa + (k < 6 ? OFF_X1 + k / 2 * WSLOT + (k & 1) * 2048 : OFF_SX + 2048 * (k - 6)));
    }
#pragma unroll 1
    for (int u = 23; u < (wg ? 32 : LAG2); u++) {
      as = P.hid[wg][u - 23];
      const uint64_t wd = mkdesc(0, 0, bo, 1) | P.w2t[u - 20].x;
      mbar_wait(BAR(B_FULL + u));
      a_tile(as, u - 23, false);
      wg_fence();
#pragma unroll
      for (int kk = 0; kk < 4; kk++) wg_ss160_01(o, mkdesc(abd + as + kk / 2 * 512 + (kk & 1) * 32, 16, 1024, 2), wd + kk * 128, 1);
      wg_commit();
      if (u == 31 && elect()) mbar_arrive(BAR(B_LAG));
      wg_wait<1>();
      if (elect()) mbar_arrive(BAR(B_EMPTY + u - 1));
    }
    int h, j, r;
    ffn_role(h, j, r);
    REGION_IDS;
    const uint32_t xb = base + OFF_XCH + 5120 * w;
    if (wg) {
      const uint32_t rdst = mapa(xb + 16 * lane, h ^ 1), rbar = mapa(BAR(B_FULL), h ^ 1);
      mbar_wait(BAR(B_XFREE));
      wg_wait<0>();
      fence_regs(o);
#pragma unroll
      for (int k = 0; k < 10; k++)
        asm volatile("st.async.shared::cluster.mbarrier::complete_tx::bytes.v4.b32 [%0], {%1,%2,%3,%4}, [%5];" ::"r"(rdst + 512 * k), "r"(pack_bf16(o[8 * k], o[8 * k + 1])),
                     "r"(pack_bf16(o[8 * k + 2], o[8 * k + 3])), "r"(pack_bf16(o[8 * k + 4], o[8 * k + 5])), "r"(pack_bf16(o[8 * k + 6], o[8 * k + 7])), "r"(rbar + 8 * (k / 4)) : "memory");
    } else {
      uint32_t gr[40];
      const float r0 = __uint_as_float(lds32(base + OFF_RT + 64 * w + (lane & 28))), r1 = __uint_as_float(lds32(base + OFF_RT + 64 * w + 32 + (lane & 28)));
      const uint32_t p0 = pack_bf16(r0, r0), p1 = pack_bf16(r1, r1), q0 = pack_bf16(r0 - bf_lo(p0), r0 - bf_lo(p0)), q1 = pack_bf16(r1 - bf_lo(p1), r1 - bf_lo(p1));
      mbar_wait(BAR(B_GB));
#pragma unroll
      for (int k = 0; k < 5; k++) {
        const uint4 g = lds128(base + OFF_GB + 80 * (lane & 3) + 16 * k);
        gr[8 * k] = g.x; gr[8 * k + 2] = g.y; gr[8 * k + 4] = g.z; gr[8 * k + 6] = g.w;
      }
      auto scale = [&](int k) {
#pragma unroll
        for (int e = 4 * k; e < 4 * k + 4; e += 2) { gr[e + 1] = bfma2(gr[e], p1, bmul2(gr[e], q1)); gr[e] = bfma2(gr[e], p0, bmul2(gr[e], q0)); }
      };
      wg_wait<0>();
      if (elect()) mbar_arrive(BAR(B_EMPTY + LAG2 - 1));
#pragma unroll 1
      for (int u = LAG2; u < 32; u++) {
        mbar_wait(BAR(B_FULL + u));
        a_tile(P.hid[0][u - 23], u - 23, false);
      }
      auto da = [&](int i) { return mkdesc(DB + hid_at(i / 4 + LAG2 - 23, 0) + (i & 2) * 256 + (i & 1) * 32, 16, 1024, 2); };
      auto db = [&](int i, int b) { return mkdesc(DB + w2_at(i / 4 + LAG2 - 20) + b * w2_step(i / 4 + LAG2 - 20) + (i & 3) * 2048, w2_step(i / 4 + LAG2 - 20), bo, 1); };
      const int row = 128 * r + 64 * h + 16 * w;
      auto merge = [&](int e) {
        if (e % 4 == 0) mbar_wait_cluster(BAR(B_FULL + e / 4), 1);
        const uint4 p = lds128(xb + 16 * lane + 512 * e);
        x1[4 * e] = bfma2(gr[4 * e], p.x, x1[4 * e]); x1[4 * e + 1] = bfma2(gr[4 * e + 1], p.y, x1[4 * e + 1]);
        x1[4 * e + 2] = bfma2(gr[4 * e + 2], p.z, x1[4 * e + 2]); x1[4 * e + 3] = bfma2(gr[4 * e + 3], p.w, x1[4 * e + 3]);
      };
      auto out = [&](int k) {
        const float* v = o + 8 * k;
        uint32_t y[4];
#pragma unroll
        for (int e = 0; e < 4; e++) y[e] = bfma2(gr[4 * k + e], pack_bf16(v[2 * e], v[2 * e + 1]), x1[4 * k + e]);
        stmatrix_x4(k < 8 ? xb + 2048 * (k >> 2) + (lane & 15) * 128 + (((2 * (k & 3) + (lane >> 4)) ^ (lane & 7) ^ 4 * (j & 1)) << 4)
                          : xb + 4096 + (lane & 15) * 64 + (((2 * (k & 1) + (lane >> 4)) ^ (lane >> 1 & 3)) << 4), y[0], y[1], y[2], y[3]);
        if ((k & 3) == 3 || k == 9) {
          fence_async_smem();
          __syncwarp();
          if (lane == 0) tma2d_store(k < 8 ? &maps.outa : &maps.outb, k < 8 ? 128 * j + 64 * (k >> 2) : 512 + 32 * j, row, xb + 2048 * (k >> 2));
        }
      };
      constexpr int ND = 128 - 4 * LAG2;
      mbar_wait(BAR(B_LAG));
      wg_fence();
#pragma unroll
      for (int i = 0; i < ND; i++) {
        wg_ss160_01(o, da(i), db(i, 0), 1);
        if (i >= 1 && i <= 10) { scale(i - 1); split(P.ulo, 32 + i); }
      }
      wg_commit();
#pragma unroll
      for (int e = 0; e < MG; e++) merge(e);
      __syncwarp();
      wg_wait<0>();
      fence_regs(o);
#pragma unroll
      for (int k = 0; k < 10; k++) {
        if (k >= MG && k % 4 == 0) {
#pragma unroll
          for (int e = k; e < min(k + 4, 10); e++) merge(e);
          __syncwarp();
        }
        out(k);
      }
      if (lane == 0) { bulk_commit(); bulk_wait_read(); }
    }
  }
}

typedef CUresult (*EncFn)(CUtensorMap*, CUtensorMapDataType, cuuint32_t, void*, const cuuint64_t*, const cuuint64_t*, const cuuint32_t*,
                          const cuuint32_t*, CUtensorMapInterleave, CUtensorMapSwizzle, CUtensorMapL2promotion, CUtensorMapFloatOOBfill);
static int enc_err = 0;
static void enc(EncFn fn, CUtensorMap* m, const void* p, int rank, const cuuint64_t* gd, const cuuint64_t* gs, const cuuint32_t* bd, CUtensorMapSwizzle sw) {
  cuuint32_t es[5] = {1, 1, 1, 1, 1};
  enc_err = 2 * enc_err + (fn(m, CU_TENSOR_MAP_DATA_TYPE_BFLOAT16, rank, (void*)p, gd, gs, bd, es, CU_TENSOR_MAP_INTERLEAVE_NONE, sw,
                              CU_TENSOR_MAP_L2_PROMOTION_L2_128B, CU_TENSOR_MAP_FLOAT_OOB_FILL_NONE) != CUDA_SUCCESS);
}

extern "C" void kernel_launch(void* const* d_in, const int* in_sizes, int n_in, void* d_out, int out_size) {
  const bf16 *q = (const bf16*)d_in[0], *k = (const bf16*)d_in[1], *v = (const bf16*)d_in[2], *shift = (const bf16*)d_in[3],
             *ssmk = (const bf16*)d_in[4], *ssmd = (const bf16*)d_in[5], *w1 = (const bf16*)d_in[7], *w3 = (const bf16*)d_in[8],
             *w2 = (const bf16*)d_in[9], *c = (const bf16*)d_in[10], *wmod = (const bf16*)d_in[11];
  EncFn fn = nullptr;
  cudaDriverEntryPointQueryResult qr;
  cudaGetDriverEntryPoint("cuTensorMapEncodeTiled", (void**)&fn, cudaEnableDefault, &qr);
  Scratch* pg;
  cudaGetSymbolAddress((void**)&pg, g_s);
  Maps maps;
  enc_err = 0;
  const CUtensorMapSwizzle S128 = CU_TENSOR_MAP_SWIZZLE_128B;
  { cuuint64_t gd[3] = {D_, S_ / 8, 8}, gs[2] = {D_ * 16, D_ * 2}; cuuint32_t b[3] = {64, 4, 8};
    enc(fn, &maps.km, k, 3, gd, gs, b, S128);
    enc(fn, &maps.v, v, 3, gd, gs, b, S128);
    enc(fn, &maps.q, q, 3, gd, gs, b, S128);
    b[2] = 3;
    enc(fn, &maps.kh, k, 3, gd, gs, b, S128); }
  { cuuint64_t gd[3] = {256, 2, 5}, gs[2] = {512, 1024}; cuuint32_t b[3] = {256, 1, 5};
    enc(fn, &maps.tap, shift, 3, gd, gs, b, CU_TENSOR_MAP_SWIZZLE_NONE); }
  { cuuint64_t gd[3] = {6 * D_, D_, 1}, gs[2] = {6 * D_ * 2, 6 * D_ * 2 * D_}; cuuint32_t b[3] = {64, 64, 1};
    enc(fn, &maps.wm, wmod, 3, gd, gs, b, S128); }
  { cuuint64_t gd[3] = {64, D_, F_ / 64}, gs[2] = {F_ * 2, 128}; cuuint32_t b[3] = {64, 32, 3};
    enc(fn, &maps.w1, w1, 3, gd, gs, b, S128);
    enc(fn, &maps.w3, w3, 3, gd, gs, b, S128);
    b[1] = 16;
    enc(fn, &maps.w1e, w1, 3, gd, gs, b, S128);
    enc(fn, &maps.w3e, w3, 3, gd, gs, b, S128);
    b[1] = 32; b[2] = 1;
    enc(fn, &maps.w1s, w1, 3, gd, gs, b, S128);
    enc(fn, &maps.w3s, w3, 3, gd, gs, b, S128); }
  { cuuint64_t gd[2] = {S_, D_}, gs[1] = {S_ * 2}; cuuint32_t b1[2] = {64, 64}, b2[2] = {64, 32};
    enc(fn, &maps.xs, pg->xs, 2, gd, gs, b1, S128);
    gd[1] = 2 * D_;
    enc(fn, &maps.x1b, pg->x1, 2, gd, gs, b2, S128);
    enc(fn, &maps.x1s, pg->x1, 2, gd, gs, b2, CU_TENSOR_MAP_SWIZZLE_NONE); }
  { cuuint64_t gd[5] = {D_, 2, 4, 4, 48}, gs[4] = {D_ * 2, D_ * 4, D_ * 16, D_ * 64}; cuuint32_t b[5] = {64, 2, 4, 4, 2};
    enc(fn, &maps.w2a, w2, 5, gd, gs, b, S128);
    gs[1] = D_ * 16; gs[2] = D_ * 4;
    enc(fn, &maps.w2b, w2, 5, gd, gs, b, S128); }
  { cuuint64_t gd[2] = {D_, S_}, gs[1] = {D_ * 2}; cuuint32_t b1[2] = {64, 16}, b2[2] = {32, 16};
    enc(fn, &maps.outa, d_out, 2, gd, gs, b1, S128);
    enc(fn, &maps.outb, d_out, 2, gd, gs, b2, CU_TENSOR_MAP_SWIZZLE_64B); }
  if (enc_err) return;
  cudaFuncSetAttribute(k_fused, cudaFuncAttributeMaxDynamicSharedMemorySize, SMEM_BYTES);
  cudaLaunchConfig_t cfg = {132, 512, SMEM_BYTES};
  cudaLaunchAttribute at = {cudaLaunchAttributeClusterDimension};
  at.val.clusterDim.x = 2; at.val.clusterDim.y = at.val.clusterDim.z = 1;
  cfg.attrs = &at; cfg.numAttrs = 1;
  int nc = 0;
  cudaOccupancyMaxActiveClusters(&nc, k_fused, &cfg);
  Ptrs P = {ssmk, c, ssmd, pg, 0x48DCBA9ull, {0x676760, 0x64620F01}, 0, 5000, 19, 48, 100, B_KV, 0, 8, 1, 1, 0xD7010, 1.f};
  const char* sched = "k10v14f04q04q14q24q34q44k24v24f14k34v34f24k44v44f34f44n04n02n04n06n06n06";
  int t = 1000, pace = 420;
  for (int e = 0; e < NE; e++) {
    const char x = sched[3 * e];
    const int r = sched[3 * e + 1] - '0', kind = x == 'k' ? 0 : x == 'v' ? 1 : x == 'q' ? 2 : x == 'f' ? 3 : 4;
    t += (sched[3 * e + 2] - '0') * pace / 4;
    P.sched[e] = make_uint2(t | kind << 16 | r << 20, (kind < 2 ? tab(T_KV, r) + kind * KV_V : kind == 2 ? OFF_Q + 4096 * r : tab(T_F, r) + F_E) | (r + (kind < 2 ? B_KV : kind == 2 ? B_Q : B_FRAW)) << 18);
  }
  for (int u = 0; u < 5; u++) P.wt[u] = 9000 + 700 * u;
  const int dep[5] = {B_FL + 1, B_FL + 2, B_PFULL + 2, B_G3, B_PEMPTY + 2};
  for (int u = 0; u < 20; u++) P.wdep[u] = u % 5 * WSLOT | (~u & 1) << 12 | (u < 5 ? dep[u] : B_EMPTY + u - 5);
  for (int v = 0; v < 12; v++) P.w2t[v] = make_uint2(w2_desc(v), v ? B_EMPTY + (v > 5 ? 15 + v : v > 3 ? 14 + v : v > 1 ? 16 : 15) : B_UVD);
  for (int m = 0; m < 9; m++) { P.hid[0][m] = hid_at(m, 0) - OFF_A; P.hid[1][m] = hid_at(m, 1) - OFF_A - ARING; P.hid[2][m] = B_EMPTY + 19 + (m > 2 ? m : m / 2); }
  if (nc < 66) { P.boff = 128; k_fused<<<4, 512, SMEM_BYTES, cudaStreamPerThread>>>(P, maps); P.boff = 0; }
  k_fused<<<nc < 66 ? 128 : 132, 512, SMEM_BYTES, cudaStreamPerThread>>>(P, maps);
}
```

```cpp
#include <cuda_runtime.h>
#include <cuda.h>
#include <cuda_bf16.h>
#include <stdint.h>
#include <stdlib.h>

typedef __nv_bfloat16 bf16;
constexpr int S_ = 2048, D_ = 640, F_ = 1536;

struct Scratch {
  uint32_t st1[2][1024];
  uint32_t st2[32][4][128];
  uint2 modc[128][32];
  uint2 modv[3][D_];
  uint32_t uv[8][3072];
  unsigned hint[9][8][32];
  unsigned xsh[5][8][32], hhf[256 * 8];
  uint4 xr[D_ * 256];
  uint4 qt[D_ * 256];
  uint4 xs[D_ * 256];
  uint4 x1[2][D_ * 256];
  uint4 hh[32 * 8 * 1536];
};
__device__ __align__(1024) Scratch g_s;

__device__ __forceinline__ uint32_t smem_u32(const void* p) { return (uint32_t)__cvta_generic_to_shared(p); }
__device__ __forceinline__ void mbar_expect_tx(uint32_t b, uint32_t n) { asm volatile("mbarrier.arrive.expect_tx.shared::cta.b64 _, [%0], %1;" ::"r"(b), "r"(n) : "memory"); }
__device__ __forceinline__ void mbar_arrive(uint32_t b) { asm volatile("mbarrier.arrive.shared::cta.b64 _, [%0];" ::"r"(b) : "memory"); }
__device__ __forceinline__ void mbar_arrive2(uint32_t b) { asm volatile("mbarrier.arrive.shared::cta.b64 _, [%0], 2;" ::"r"(b) : "memory"); }
__device__ __forceinline__ uint32_t mapa(uint32_t a, uint32_t cta) { uint32_t r; asm volatile("mapa.shared::cluster.u32 %0, %1, %2;" : "=r"(r) : "r"(a), "r"(cta)); return r; }
__device__ __forceinline__ void mbar_arrive_remote(uint32_t rb) { asm volatile("mbarrier.arrive.shared::cluster.b64 _, [%0];" ::"r"(rb) : "memory"); }
constexpr int SPIN_LIMIT = 1 << 16;
template <int N> __device__ __forceinline__ void mbar_init(uint32_t b, uint32_t count) {
#pragma unroll
  for (int i = 0; i < N; i++) asm volatile("mbarrier.init.shared::cta.b64 [%0], %1;" ::"r"(b + 8 * i), "r"(count) : "memory");
}
__device__ __forceinline__ bool elect() { uint32_t p; asm volatile("{.reg .pred q; elect.sync _|q, 0xffffffff; selp.u32 %0, 1, 0, q;}" : "=r"(p)); return p; }
__device__ __forceinline__ void arrive1(uint32_t b) { __syncwarp(); if (elect()) mbar_arrive(b); }
__device__ __forceinline__ bool mbar_test(uint32_t b) {
  uint32_t ok;
  asm volatile("{.reg .pred p; mbarrier.test_wait.parity.shared::cta.b64 p, [%1], 0; selp.u32 %0,1,0,p;}" : "=r"(ok) : "r"(b) : "memory");
  return ok;
}
#define WAIT_LOOP(sem) "{.reg .pred p; mov.u32 %0, 0; W: mbarrier.try_wait.parity" sem ".shared::cta.b64 p, [%1], %2; @p bra.uni D; add.u32 %0, %0, 1; setp.lt.u32 p, %0, %3; @p bra.uni W; D:}"
__device__ __forceinline__ void mbar_wait(uint32_t b, uint32_t ph = 0) {
  int it;
  asm volatile(WAIT_LOOP("") : "=&r"(it) : "r"(b), "r"(ph), "n"(SPIN_LIMIT) : "memory");
}
__device__ __forceinline__ void mbar_wait_cluster(uint32_t b, uint32_t ph = 0) {
  int it;
  asm volatile(WAIT_LOOP(".acquire.cluster") : "=&r"(it) : "r"(b), "r"(ph), "n"(SPIN_LIMIT) : "memory");
}
__device__ __forceinline__ void wait_clock(uint32_t t) {
  asm volatile("{.reg .pred p; .reg .s32 d; W: mov.u32 d, %%clock; sub.s32 d, d, %0; setp.lt.s32 p, d, 0; @p bra.uni W;}" ::"r"(t) : "memory");
}
__device__ __forceinline__ void tma2d(uint32_t dst, const CUtensorMap* m, int c0, int c1, uint32_t bar) {
  asm volatile("cp.async.bulk.tensor.2d.shared::cluster.global.mbarrier::complete_tx::bytes [%0], [%1, {%3,%4}], [%2];" ::"r"(dst), "l"(m), "r"(bar), "r"(c0), "r"(c1) : "memory");
}
__device__ __forceinline__ void tma3d(uint32_t dst, const CUtensorMap* m, int c0, int c1, int c2, uint32_t bar) {
  asm volatile("cp.async.bulk.tensor.3d.shared::cluster.global.mbarrier::complete_tx::bytes [%0], [%1, {%3,%4,%5}], [%2];" ::"r"(dst), "l"(m), "r"(bar), "r"(c0), "r"(c1), "r"(c2) : "memory");
}
__device__ __forceinline__ void tma5d(uint32_t dst, const CUtensorMap* m, int c0, int c4, uint32_t bar) {
  asm volatile("cp.async.bulk.tensor.5d.shared::cluster.global.mbarrier::complete_tx::bytes [%0], [%1, {%4,%3,%3,%3,%5}], [%2];" ::"r"(dst), "l"(m), "r"(bar), "r"(0), "r"(c0), "r"(c4) : "memory");
}
__device__ __forceinline__ void tma2d_store(const CUtensorMap* m, int c0, int c1, uint32_t src) {
  asm volatile("cp.async.bulk.tensor.2d.global.shared::cta.bulk_group [%0, {%2,%3}], [%1];" ::"l"(m), "r"(src), "r"(c0), "r"(c1) : "memory");
}
__device__ __forceinline__ void bulk_load(uint32_t dst, const void* src, uint32_t bytes, uint32_t bar) {
  asm volatile("cp.async.bulk.shared::cluster.global.mbarrier::complete_tx::bytes [%0], [%1], %2, [%3];" ::"r"(dst), "l"(src), "r"(bytes), "r"(bar) : "memory");
}
__device__ __forceinline__ void prefetch_map(const CUtensorMap* m) { asm volatile("prefetch.tensormap [%0];" ::"l"(m) : "memory"); }
__device__ __forceinline__ void bulk_commit() { asm volatile("cp.async.bulk.commit_group;" ::: "memory"); }
__device__ __forceinline__ void bulk_wait_read() { asm volatile("cp.async.bulk.wait_group.read 0;" ::: "memory"); }
__device__ __forceinline__ void fence_async_smem() { asm volatile("fence.proxy.async.shared::cta;" ::: "memory"); }
__device__ __forceinline__ void fence_async_all() { asm volatile("fence.proxy.async.global;" ::: "memory"); }
__device__ __forceinline__ void named_bar(int id, int n) { asm volatile("bar.sync %0, %1;" ::"r"(id), "r"(n) : "memory"); }
__device__ __forceinline__ bool bar_all(int id, bool v) {
  uint32_t r;
  asm volatile("{.reg .pred p, q; setp.ne.u32 p, %2, 0; bar.red.and.pred q, %1, 128, p; selp.u32 %0, 1, 0, q;}" : "=r"(r) : "r"(id), "r"((uint32_t)v) : "memory");
  return __all_sync(~0u, r);
}
__device__ __forceinline__ void cluster_wait() { asm volatile("barrier.cluster.wait.aligned;" ::: "memory"); }
__device__ __forceinline__ void wg_fence() { asm volatile("wgmma.fence.sync.aligned;" ::: "memory"); }
__device__ __forceinline__ void wg_commit() { asm volatile("wgmma.commit_group.sync.aligned;" ::: "memory"); }
template <int N> __device__ __forceinline__ void wg_wait() { asm volatile("wgmma.wait_group.sync.aligned %0;" ::"n"(N) : "memory"); }
template <int N> __device__ __forceinline__ void fence_regs(float (&a)[N]) {
#pragma unroll
  for (int i = 0; i < N; i++) asm volatile("" : "+f"(a[i])::"memory");
}
template <int N> __device__ __forceinline__ void fence_n(float* a) {
#pragma unroll
  for (int i = 0; i < N; i++) asm volatile("" : "+f"(a[i])::"memory");
}
__device__ __forceinline__ uint64_t mkdesc(uint32_t addr, uint32_t lbo, uint32_t sbo, uint32_t swz) {
  uint32_t lo = (addr >> 4) | ((lbo >> 4) << 16), hi = (sbo >> 4) | (swz << 30);
  return ((uint64_t)hi << 32) | lo;
}
__device__ __forceinline__ void stmatrix_x4(uint32_t a, uint32_t r0, uint32_t r1, uint32_t r2, uint32_t r3) {
  asm volatile("stmatrix.sync.aligned.m8n8.x4.shared.b16 [%0], {%1,%2,%3,%4};" ::"r"(a), "r"(r0), "r"(r1), "r"(r2), "r"(r3) : "memory");
}
__device__ __forceinline__ void stmatrix_x4_t(uint32_t a, uint32_t r0, uint32_t r1, uint32_t r2, uint32_t r3) {
  asm volatile("stmatrix.sync.aligned.m8n8.x4.trans.shared.b16 [%0], {%1,%2,%3,%4};" ::"r"(a), "r"(r0), "r"(r1), "r"(r2), "r"(r3) : "memory");
}
__device__ __forceinline__ void ldmatrix_x4_t(uint32_t* r, uint32_t a) {
  asm volatile("ldmatrix.sync.aligned.m8n8.x4.trans.shared.b16 {%0,%1,%2,%3}, [%4];" : "=r"(r[0]), "=r"(r[1]), "=r"(r[2]), "=r"(r[3]) : "r"(a) : "memory");
}
__device__ __forceinline__ uint32_t lds32(uint32_t a) { uint32_t v; asm volatile("ld.shared.b32 %0, [%1];" : "=r"(v) : "r"(a) : "memory"); return v; }
__device__ __forceinline__ uint2 lds64(uint32_t a) { uint2 v; asm volatile("ld.shared.v2.b32 {%0,%1}, [%2];" : "=r"(v.x), "=r"(v.y) : "r"(a) : "memory"); return v; }
__device__ __forceinline__ uint4 lds128(uint32_t a) { uint4 v; asm volatile("ld.shared.v4.b32 {%0,%1,%2,%3}, [%4];" : "=r"(v.x), "=r"(v.y), "=r"(v.z), "=r"(v.w) : "r"(a) : "memory"); return v; }
__device__ __forceinline__ void sts32(uint32_t a, uint32_t v) { asm volatile("st.shared.b32 [%0], %1;" ::"r"(a), "r"(v) : "memory"); }
__device__ __forceinline__ void sts64(uint32_t a, uint32_t x, uint32_t y) { asm volatile("st.shared.v2.b32 [%0], {%1,%2};" ::"r"(a), "r"(x), "r"(y) : "memory"); }
__device__ __forceinline__ void sts128(uint32_t a, uint32_t x, uint32_t y, uint32_t z, uint32_t w) { asm volatile("st.shared.v4.b32 [%0], {%1,%2,%3,%4};" ::"r"(a), "r"(x), "r"(y), "r"(z), "r"(w) : "memory"); }
__device__ __forceinline__ uint4 ld_relaxed128(const void* p) { uint4 v; asm volatile("ld.relaxed.gpu.global.v4.u32 {%0,%1,%2,%3}, [%4];" : "=r"(v.x), "=r"(v.y), "=r"(v.z), "=r"(v.w) : "l"(p) : "memory"); return v; }
__device__ __forceinline__ uint2 ld_relaxed64(const void* p) { uint2 v; asm volatile("ld.relaxed.gpu.global.v2.u32 {%0,%1}, [%2];" : "=r"(v.x), "=r"(v.y) : "l"(p) : "memory"); return v; }
__device__ __forceinline__ uint32_t ld_relaxed32(const void* p) { uint32_t v; asm volatile("ld.relaxed.gpu.global.u32 %0, [%1];" : "=r"(v) : "l"(p) : "memory"); return v; }
__device__ __forceinline__ void st_relaxed128(void* p, uint32_t x, uint32_t y, uint32_t z, uint32_t w) { asm volatile("st.relaxed.gpu.global.v4.u32 [%0], {%1,%2,%3,%4};" ::"l"(p), "r"(x), "r"(y), "r"(z), "r"(w) : "memory"); }
__device__ __forceinline__ void st_relaxed32(void* p, uint32_t x) { asm volatile("st.relaxed.gpu.global.u32 [%0], %1;" ::"l"(p), "r"(x) : "memory"); }
__device__ __forceinline__ void red_hint(unsigned* p) { asm volatile("red.relaxed.gpu.global.add.u32 [%0], 1;" ::"l"(p) : "memory"); }
__device__ __forceinline__ void publish(uint32_t* p, uint32_t x) { asm volatile("{.reg .b32 t; atom.relaxed.gpu.global.exch.b32 t, [%0], %1;}" ::"l"(p), "r"(x) : "memory"); }
__device__ __forceinline__ uint32_t ldg32(const void* p) { uint32_t v; asm volatile("ld.global.nc.L1::no_allocate.b32 %0, [%1];" : "=r"(v) : "l"(p)); return v; }
__device__ __forceinline__ uint32_t pack_bf16(float lo, float hi) { uint32_t r; asm("cvt.rn.bf16x2.f32 %0, %1, %2;" : "=r"(r) : "f"(hi), "f"(lo)); return r; }
__device__ __forceinline__ float bf_lo(uint32_t v) { return __uint_as_float(v << 16); }
__device__ __forceinline__ float bf_hi(uint32_t v) { return __uint_as_float(v & 0xFFFF0000u); }
__device__ __forceinline__ uint32_t bmul2(uint32_t a, uint32_t b) { uint32_t r; asm("mul.rn.bf16x2 %0, %1, %2;" : "=r"(r) : "r"(a), "r"(b)); return r; }
__device__ __forceinline__ uint32_t badd2(uint32_t a, uint32_t b) { uint32_t r; asm("add.rn.bf16x2 %0, %1, %2;" : "=r"(r) : "r"(a), "r"(b)); return r; }
__device__ __forceinline__ uint32_t bfma2(uint32_t a, uint32_t b, uint32_t c) { uint32_t r; asm("fma.rn.bf16x2 %0, %1, %2, %3;" : "=r"(r) : "r"(a), "r"(b), "r"(c)); return r; }
__device__ __forceinline__ uint32_t set_tag(uint32_t x, uint32_t mask, uint32_t e) { uint32_t r; asm("lop3.b32 %0, %1, %2, %3, 0xB8;" : "=r"(r) : "r"(x), "r"(mask), "r"(e)); return r; }
__device__ __forceinline__ uint32_t opaque(uint32_t x) { asm volatile("" : "+r"(x)); return x; }
__device__ __forceinline__ float rbf(float x) { return __bfloat162float(__float2bfloat16(x)); }
__device__ __forceinline__ float silu_f(float x) {
  float e, r;
  asm("ex2.approx.ftz.f32 %0, %1;" : "=f"(e) : "f"(x * -1.4426950408889634f));
  asm("rcp.approx.ftz.f32 %0, %1;" : "=f"(r) : "f"(1.f + e));
  return x * r;
}
__device__ __forceinline__ float silu2(float x) {
  float t;
  asm("tanh.approx.f32 %0, %1;" : "=f"(t) : "f"(x));
  return fmaf(x, t, x);
}
__device__ __forceinline__ void pin(int off, uint32_t x) { asm volatile("{.reg .pred p; setp.lt.s32 p, %0, 0; @p st.shared.b32 [%0], %1;}" ::"r"(off), "r"(x) : "memory"); }
__device__ __forceinline__ void pin4(int off, const uint32_t* x) { asm volatile("{.reg .pred p; setp.lt.s32 p, %0, 0; @p st.shared.v4.b32 [%0], {%1,%2,%3,%4};}" ::"r"(off), "r"(x[0]), "r"(x[1]), "r"(x[2]), "r"(x[3]) : "memory"); }
__device__ __forceinline__ void split(int x, int n) { asm volatile("{.reg .pred p; setp.eq.s32 p, %0, %1; @p trap;}" ::"r"(x), "r"(~n) : "memory"); }
__device__ __forceinline__ void ln_final(float s, float q, float& m, float& sd) {
  m = s * (1.f / D_);
  asm("sqrt.approx.f32 %0, %1;" : "=f"(sd) : "f"(rbf(rbf(fmaxf(fmaf(-m, m, q * (1.f / D_)), 0.f)) + 1e-5f)));
  sd = rbf(sd);
}
__device__ __forceinline__ float rcpf(float x) { float r; asm("rcp.approx.f32 %0, %1;" : "=f"(r) : "f"(x)); return r; }

__device__ __forceinline__ void wg_rs16_0(float* d, const uint32_t* a, uint64_t db, int sc) {
  asm volatile("{.reg .pred p; setp.ne.b32 p, %13, 0; wgmma.mma_async.sync.aligned.m64n16k16.f32.bf16.bf16 {%0,%1,%2,%3,%4,%5,%6,%7}, {%8,%9,%10,%11}, %12, p, 1, 1, 0;}"
    : "+f"(d[0]),"+f"(d[1]),"+f"(d[2]),"+f"(d[3]),"+f"(d[4]),"+f"(d[5]),"+f"(d[6]),"+f"(d[7]) : "r"(a[0]),"r"(a[1]),"r"(a[2]),"r"(a[3]),"l"(db),"r"(sc));
}
__device__ __forceinline__ void wg_rs32_0(float* d, const uint32_t* a, uint64_t db, int sc) {
  asm volatile("{.reg .pred p; setp.ne.b32 p, %21, 0; wgmma.mma_async.sync.aligned.m64n32k16.f32.bf16.bf16 {%0,%1,%2,%3,%4,%5,%6,%7,%8,%9,%10,%11,%12,%13,%14,%15}, {%16,%17,%18,%19}, %20, p, 1, 1, 0;}"
    : "+f"(d[0]),"+f"(d[1]),"+f"(d[2]),"+f"(d[3]),"+f"(d[4]),"+f"(d[5]),"+f"(d[6]),"+f"(d[7]),"+f"(d[8]),"+f"(d[9]),"+f"(d[10]),"+f"(d[11]),"+f"(d[12]),"+f"(d[13]),"+f"(d[14]),"+f"(d[15]) : "r"(a[0]),"r"(a[1]),"r"(a[2]),"r"(a[3]),"l"(db),"r"(sc));
}
__device__ __forceinline__ void wg_rs48_0(float* d, const uint32_t* a, uint64_t db, int sc) {
  asm volatile("{.reg .pred p; setp.ne.b32 p, %29, 0; wgmma.mma_async.sync.aligned.m64n48k16.f32.bf16.bf16 {%0,%1,%2,%3,%4,%5,%6,%7,%8,%9,%10,%11,%12,%13,%14,%15,%16,%17,%18,%19,%20,%21,%22,%23}, {%24,%25,%26,%27}, %28, p, 1, 1, 0;}"
    : "+f"(d[0]),"+f"(d[1]),"+f"(d[2]),"+f"(d[3]),"+f"(d[4]),"+f"(d[5]),"+f"(d[6]),"+f"(d[7]),"+f"(d[8]),"+f"(d[9]),"+f"(d[10]),"+f"(d[11]),"+f"(d[12]),"+f"(d[13]),"+f"(d[14]),"+f"(d[15]),"+f"(d[16]),"+f"(d[17]),"+f"(d[18]),"+f"(d[19]),"+f"(d[20]),"+f"(d[21]),"+f"(d[22]),"+f"(d[23]) : "r"(a[0]),"r"(a[1]),"r"(a[2]),"r"(a[3]),"l"(db),"r"(sc));
}
__device__ __forceinline__ void wg_rs64_0(float* d, const uint32_t* a, uint64_t db, int sc) {
  asm volatile("{.reg .pred p; setp.ne.b32 p, %37, 0; wgmma.mma_async.sync.aligned.m64n64k16.f32.bf16.bf16 {%0,%1,%2,%3,%4,%5,%6,%7,%8,%9,%10,%11,%12,%13,%14,%15,%16,%17,%18,%19,%20,%21,%22,%23,%24,%25,%26,%27,%28,%29,%30,%31}, {%32,%33,%34,%35}, %36, p, 1, 1, 0;}"
    : "+f"(d[0]),"+f"(d[1]),"+f"(d[2]),"+f"(d[3]),"+f"(d[4]),"+f"(d[5]),"+f"(d[6]),"+f"(d[7]),"+f"(d[8]),"+f"(d[9]),"+f"(d[10]),"+f"(d[11]),"+f"(d[12]),"+f"(d[13]),"+f"(d[14]),"+f"(d[15]),"+f"(d[16]),"+f"(d[17]),"+f"(d[18]),"+f"(d[19]),"+f"(d[20]),"+f"(d[21]),"+f"(d[22]),"+f"(d[23]),"+f"(d[24]),"+f"(d[25]),"+f"(d[26]),"+f"(d[27]),"+f"(d[28]),"+f"(d[29]),"+f"(d[30]),"+f"(d[31]) : "r"(a[0]),"r"(a[1]),"r"(a[2]),"r"(a[3]),"l"(db),"r"(sc));
}
__device__ __forceinline__ void wg_rs80_0(float* d, const uint32_t* a, uint64_t db, int sc) {
  asm volatile("{.reg .pred p; setp.ne.b32 p, %45, 0; wgmma.mma_async.sync.aligned.m64n80k16.f32.bf16.bf16 {%0,%1,%2,%3,%4,%5,%6,%7,%8,%9,%10,%11,%12,%13,%14,%15,%16,%17,%18,%19,%20,%21,%22,%23,%24,%25,%26,%27,%28,%29,%30,%31,%32,%33,%34,%35,%36,%37,%38,%39}, {%40,%41,%42,%43}, %44, p, 1, 1, 0;}"
    : "+f"(d[0]),"+f"(d[1]),"+f"(d[2]),"+f"(d[3]),"+f"(d[4]),"+f"(d[5]),"+f"(d[6]),"+f"(d[7]),"+f"(d[8]),"+f"(d[9]),"+f"(d[10]),"+f"(d[11]),"+f"(d[12]),"+f"(d[13]),"+f"(d[14]),"+f"(d[15]),"+f"(d[16]),"+f"(d[17]),"+f"(d[18]),"+f"(d[19]),"+f"(d[20]),"+f"(d[21]),"+f"(d[22]),"+f"(d[23]),"+f"(d[24]),"+f"(d[25]),"+f"(d[26]),"+f"(d[27]),"+f"(d[28]),"+f"(d[29]),"+f"(d[30]),"+f"(d[31]),"+f"(d[32]),"+f"(d[33]),"+f"(d[34]),"+f"(d[35]),"+f"(d[36]),"+f"(d[37]),"+f"(d[38]),"+f"(d[39]) : "r"(a[0]),"r"(a[1]),"r"(a[2]),"r"(a[3]),"l"(db),"r"(sc));
}
__device__ __forceinline__ void wg_rs96_0(float* d, const uint32_t* a, uint64_t db, int sc) {
  asm volatile("{.reg .pred p; setp.ne.b32 p, %53, 0; wgmma.mma_async.sync.aligned.m64n96k16.f32.bf16.bf16 {%0,%1,%2,%3,%4,%5,%6,%7,%8,%9,%10,%11,%12,%13,%14,%15,%16,%17,%18,%19,%20,%21,%22,%23,%24,%25,%26,%27,%28,%29,%30,%31,%32,%33,%34,%35,%36,%37,%38,%39,%40,%41,%42,%43,%44,%45,%46,%47}, {%48,%49,%50,%51}, %52, p, 1, 1, 0;}"
    : "+f"(d[0]),"+f"(d[1]),"+f"(d[2]),"+f"(d[3]),"+f"(d[4]),"+f"(d[5]),"+f"(d[6]),"+f"(d[7]),"+f"(d[8]),"+f"(d[9]),"+f"(d[10]),"+f"(d[11]),"+f"(d[12]),"+f"(d[13]),"+f"(d[14]),"+f"(d[15]),"+f"(d[16]),"+f"(d[17]),"+f"(d[18]),"+f"(d[19]),"+f"(d[20]),"+f"(d[21]),"+f"(d[22]),"+f"(d[23]),"+f"(d[24]),"+f"(d[25]),"+f"(d[26]),"+f"(d[27]),"+f"(d[28]),"+f"(d[29]),"+f"(d[30]),"+f"(d[31]),"+f"(d[32]),"+f"(d[33]),"+f"(d[34]),"+f"(d[35]),"+f"(d[36]),"+f"(d[37]),"+f"(d[38]),"+f"(d[39]),"+f"(d[40]),"+f"(d[41]),"+f"(d[42]),"+f"(d[43]),"+f"(d[44]),"+f"(d[45]),"+f"(d[46]),"+f"(d[47]) : "r"(a[0]),"r"(a[1]),"r"(a[2]),"r"(a[3]),"l"(db),"r"(sc));
}
__device__ __forceinline__ void wg_rs112_0(float* d, const uint32_t* a, uint64_t db, int sc) {
  asm volatile("{.reg .pred p; setp.ne.b32 p, %61, 0; wgmma.mma_async.sync.aligned.m64n112k16.f32.bf16.bf16 {%0,%1,%2,%3,%4,%5,%6,%7,%8,%9,%10,%11,%12,%13,%14,%15,%16,%17,%18,%19,%20,%21,%22,%23,%24,%25,%26,%27,%28,%29,%30,%31,%32,%33,%34,%35,%36,%37,%38,%39,%40,%41,%42,%43,%44,%45,%46,%47,%48,%49,%50,%51,%52,%53,%54,%55}, {%56,%57,%58,%59}, %60, p, 1, 1, 0;}"
    : "+f"(d[0]),"+f"(d[1]),"+f"(d[2]),"+f"(d[3]),"+f"(d[4]),"+f"(d[5]),"+f"(d[6]),"+f"(d[7]),"+f"(d[8]),"+f"(d[9]),"+f"(d[10]),"+f"(d[11]),"+f"(d[12]),"+f"(d[13]),"+f"(d[14]),"+f"(d[15]),"+f"(d[16]),"+f"(d[17]),"+f"(d[18]),"+f"(d[19]),"+f"(d[20]),"+f"(d[21]),"+f"(d[22]),"+f"(d[23]),"+f"(d[24]),"+f"(d[25]),"+f"(d[26]),"+f"(d[27]),"+f"(d[28]),"+f"(d[29]),"+f"(d[30]),"+f"(d[31]),"+f"(d[32]),"+f"(d[33]),"+f"(d[34]),"+f"(d[35]),"+f"(d[36]),"+f"(d[37]),"+f"(d[38]),"+f"(d[39]),"+f"(d[40]),"+f"(d[41]),"+f"(d[42]),"+f"(d[43]),"+f"(d[44]),"+f"(d[45]),"+f"(d[46]),"+f"(d[47]),"+f"(d[48]),"+f"(d[49]),"+f"(d[50]),"+f"(d[51]),"+f"(d[52]),"+f"(d[53]),"+f"(d[54]),"+f"(d[55]) : "r"(a[0]),"r"(a[1]),"r"(a[2]),"r"(a[3]),"l"(db),"r"(sc));
}
__device__ __forceinline__ void wg_rs128_0(float* d, const uint32_t* a, uint64_t db, int sc) {
  asm volatile("{.reg .pred p; setp.ne.b32 p, %69, 0; wgmma.mma_async.sync.aligned.m64n128k16.f32.bf16.bf16 {%0,%1,%2,%3,%4,%5,%6,%7,%8,%9,%10,%11,%12,%13,%14,%15,%16,%17,%18,%19,%20,%21,%22,%23,%24,%25,%26,%27,%28,%29,%30,%31,%32,%33,%34,%35,%36,%37,%38,%39,%40,%41,%42,%43,%44,%45,%46,%47,%48,%49,%50,%51,%52,%53,%54,%55,%56,%57,%58,%59,%60,%61,%62,%63}, {%64,%65,%66,%67}, %68, p, 1, 1, 0;}"
    : "+f"(d[0]),"+f"(d[1]),"+f"(d[2]),"+f"(d[3]),"+f"(d[4]),"+f"(d[5]),"+f"(d[6]),"+f"(d[7]),"+f"(d[8]),"+f"(d[9]),"+f"(d[10]),"+f"(d[11]),"+f"(d[12]),"+f"(d[13]),"+f"(d[14]),"+f"(d[15]),"+f"(d[16]),"+f"(d[17]),"+f"(d[18]),"+f"(d[19]),"+f"(d[20]),"+f"(d[21]),"+f"(d[22]),"+f"(d[23]),"+f"(d[24]),"+f"(d[25]),"+f"(d[26]),"+f"(d[27]),"+f"(d[28]),"+f"(d[29]),"+f"(d[30]),"+f"(d[31]),"+f"(d[32]),"+f"(d[33]),"+f"(d[34]),"+f"(d[35]),"+f"(d[36]),"+f"(d[37]),"+f"(d[38]),"+f"(d[39]),"+f"(d[40]),"+f"(d[41]),"+f"(d[42]),"+f"(d[43]),"+f"(d[44]),"+f"(d[45]),"+f"(d[46]),"+f"(d[47]),"+f"(d[48]),"+f"(d[49]),"+f"(d[50]),"+f"(d[51]),"+f"(d[52]),"+f"(d[53]),"+f"(d[54]),"+f"(d[55]),"+f"(d[56]),"+f"(d[57]),"+f"(d[58]),"+f"(d[59]),"+f"(d[60]),"+f"(d[61]),"+f"(d[62]),"+f"(d[63]) : "r"(a[0]),"r"(a[1]),"r"(a[2]),"r"(a[3]),"l"(db),"r"(sc));
}
__device__ __forceinline__ void wg_rs144_0(float* d, const uint32_t* a, uint64_t db, int sc) {
  asm volatile("{.reg .pred p; setp.ne.b32 p, %77, 0; wgmma.mma_async.sync.aligned.m64n144k16.f32.bf16.bf16 {%0,%1,%2,%3,%4,%5,%6,%7,%8,%9,%10,%11,%12,%13,%14,%15,%16,%17,%18,%19,%20,%21,%22,%23,%24,%25,%26,%27,%28,%29,%30,%31,%32,%33,%34,%35,%36,%37,%38,%39,%40,%41,%42,%43,%44,%45,%46,%47,%48,%49,%50,%51,%52,%53,%54,%55,%56,%57,%58,%59,%60,%61,%62,%63,%64,%65,%66,%67,%68,%69,%70,%71}, {%72,%73,%74,%75}, %76, p, 1, 1, 0;}"
    : "+f"(d[0]),"+f"(d[1]),"+f"(d[2]),"+f"(d[3]),"+f"(d[4]),"+f"(d[5]),"+f"(d[6]),"+f"(d[7]),"+f"(d[8]),"+f"(d[9]),"+f"(d[10]),"+f"(d[11]),"+f"(d[12]),"+f"(d[13]),"+f"(d[14]),"+f"(d[15]),"+f"(d[16]),"+f"(d[17]),"+f"(d[18]),"+f"(d[19]),"+f"(d[20]),"+f"(d[21]),"+f"(d[22]),"+f"(d[23]),"+f"(d[24]),"+f"(d[25]),"+f"(d[26]),"+f"(d[27]),"+f"(d[28]),"+f"(d[29]),"+f"(d[30]),"+f"(d[31]),"+f"(d[32]),"+f"(d[33]),"+f"(d[34]),"+f"(d[35]),"+f"(d[36]),"+f"(d[37]),"+f"(d[38]),"+f"(d[39]),"+f"(d[40]),"+f"(d[41]),"+f"(d[42]),"+f"(d[43]),"+f"(d[44]),"+f"(d[45]),"+f"(d[46]),"+f"(d[47]),"+f"(d[48]),"+f"(d[49]),"+f"(d[50]),"+f"(d[51]),"+f"(d[52]),"+f"(d[53]),"+f"(d[54]),"+f"(d[55]),"+f"(d[56]),"+f"(d[57]),"+f"(d[58]),"+f"(d[59]),"+f"(d[60]),"+f"(d[61]),"+f"(d[62]),"+f"(d[63]),"+f"(d[64]),"+f"(d[65]),"+f"(d[66]),"+f"(d[67]),"+f"(d[68]),"+f"(d[69]),"+f"(d[70]),"+f"(d[71]) : "r"(a[0]),"r"(a[1]),"r"(a[2]),"r"(a[3]),"l"(db),"r"(sc));
}
__device__ __forceinline__ void wg_rs160_0(float* d, const uint32_t* a, uint64_t db, int sc) {
  asm volatile("{.reg .pred p; setp.ne.b32 p, %85, 0; wgmma.mma_async.sync.aligned.m64n160k16.f32.bf16.bf16 {%0,%1,%2,%3,%4,%5,%6,%7,%8,%9,%10,%11,%12,%13,%14,%15,%16,%17,%18,%19,%20,%21,%22,%23,%24,%25,%26,%27,%28,%29,%30,%31,%32,%33,%34,%35,%36,%37,%38,%39,%40,%41,%42,%43,%44,%45,%46,%47,%48,%49,%50,%51,%52,%53,%54,%55,%56,%57,%58,%59,%60,%61,%62,%63,%64,%65,%66,%67,%68,%69,%70,%71,%72,%73,%74,%75,%76,%77,%78,%79}, {%80,%81,%82,%83}, %84, p, 1, 1, 0;}"
    : "+f"(d[0]),"+f"(d[1]),"+f"(d[2]),"+f"(d[3]),"+f"(d[4]),"+f"(d[5]),"+f"(d[6]),"+f"(d[7]),"+f"(d[8]),"+f"(d[9]),"+f"(d[10]),"+f"(d[11]),"+f"(d[12]),"+f"(d[13]),"+f"(d[14]),"+f"(d[15]),"+f"(d[16]),"+f"(d[17]),"+f"(d[18]),"+f"(d[19]),"+f"(d[20]),"+f"(d[21]),"+f"(d[22]),"+f"(d[23]),"+f"(d[24]),"+f"(d[25]),"+f"(d[26]),"+f"(d[27]),"+f"(d[28]),"+f"(d[29]),"+f"(d[30]),"+f"(d[31]),"+f"(d[32]),"+f"(d[33]),"+f"(d[34]),"+f"(d[35]),"+f"(d[36]),"+f"(d[37]),"+f"(d[38]),"+f"(d[39]),"+f"(d[40]),"+f"(d[41]),"+f"(d[42]),"+f"(d[43]),"+f"(d[44]),"+f"(d[45]),"+f"(d[46]),"+f"(d[47]),"+f"(d[48]),"+f"(d[49]),"+f"(d[50]),"+f"(d[51]),"+f"(d[52]),"+f"(d[53]),"+f"(d[54]),"+f"(d[55]),"+f"(d[56]),"+f"(d[57]),"+f"(d[58]),"+f"(d[59]),"+f"(d[60]),"+f"(d[61]),"+f"(d[62]),"+f"(d[63]),"+f"(d[64]),"+f"(d[65]),"+f"(d[66]),"+f"(d[67]),"+f"(d[68]),"+f"(d[69]),"+f"(d[70]),"+f"(d[71]),"+f"(d[72]),"+f"(d[73]),"+f"(d[74]),"+f"(d[75]),"+f"(d[76]),"+f"(d[77]),"+f"(d[78]),"+f"(d[79]) : "r"(a[0]),"r"(a[1]),"r"(a[2]),"r"(a[3]),"l"(db),"r"(sc));
}
__device__ __forceinline__ void wg_rs176_0(float* d, const uint32_t* a, uint64_t db, int sc) {
  asm volatile("{.reg .pred p; setp.ne.b32 p, %93, 0; wgmma.mma_async.sync.aligned.m64n176k16.f32.bf16.bf16 {%0,%1,%2,%3,%4,%5,%6,%7,%8,%9,%10,%11,%12,%13,%14,%15,%16,%17,%18,%19,%20,%21,%22,%23,%24,%25,%26,%27,%28,%29,%30,%31,%32,%33,%34,%35,%36,%37,%38,%39,%40,%41,%42,%43,%44,%45,%46,%47,%48,%49,%50,%51,%52,%53,%54,%55,%56,%57,%58,%59,%60,%61,%62,%63,%64,%65,%66,%67,%68,%69,%70,%71,%72,%73,%74,%75,%76,%77,%78,%79,%80,%81,%82,%83,%84,%85,%86,%87}, {%88,%89,%90,%91}, %92, p, 1, 1, 0;}"
    : "+f"(d[0]),"+f"(d[1]),"+f"(d[2]),"+f"(d[3]),"+f"(d[4]),"+f"(d[5]),"+f"(d[6]),"+f"(d[7]),"+f"(d[8]),"+f"(d[9]),"+f"(d[10]),"+f"(d[11]),"+f"(d[12]),"+f"(d[13]),"+f"(d[14]),"+f"(d[15]),"+f"(d[16]),"+f"(d[17]),"+f"(d[18]),"+f"(d[19]),"+f"(d[20]),"+f"(d[21]),"+f"(d[22]),"+f"(d[23]),"+f"(d[24]),"+f"(d[25]),"+f"(d[26]),"+f"(d[27]),"+f"(d[28]),"+f"(d[29]),"+f"(d[30]),"+f"(d[31]),"+f"(d[32]),"+f"(d[33]),"+f"(d[34]),"+f"(d[35]),"+f"(d[36]),"+f"(d[37]),"+f"(d[38]),"+f"(d[39]),"+f"(d[40]),"+f"(d[41]),"+f"(d[42]),"+f"(d[43]),"+f"(d[44]),"+f"(d[45]),"+f"(d[46]),"+f"(d[47]),"+f"(d[48]),"+f"(d[49]),"+f"(d[50]),"+f"(d[51]),"+f"(d[52]),"+f"(d[53]),"+f"(d[54]),"+f"(d[55]),"+f"(d[56]),"+f"(d[57]),"+f"(d[58]),"+f"(d[59]),"+f"(d[60]),"+f"(d[61]),"+f"(d[62]),"+f"(d[63]),"+f"(d[64]),"+f"(d[65]),"+f"(d[66]),"+f"(d[67]),"+f"(d[68]),"+f"(d[69]),"+f"(d[70]),"+f"(d[71]),"+f"(d[72]),"+f"(d[73]),"+f"(d[74]),"+f"(d[75]),"+f"(d[76]),"+f"(d[77]),"+f"(d[78]),"+f"(d[79]),"+f"(d[80]),"+f"(d[81]),"+f"(d[82]),"+f"(d[83]),"+f"(d[84]),"+f"(d[85]),"+f"(d[86]),"+f"(d[87]) : "r"(a[0]),"r"(a[1]),"r"(a[2]),"r"(a[3]),"l"(db),"r"(sc));
}
__device__ __forceinline__ void wg_rs192_0(float* d, const uint32_t* a, uint64_t db, int sc) {
  asm volatile("{.reg .pred p; setp.ne.b32 p, %101, 0; wgmma.mma_async.sync.aligned.m64n192k16.f32.bf16.bf16 {%0,%1,%2,%3,%4,%5,%6,%7,%8,%9,%10,%11,%12,%13,%14,%15,%16,%17,%18,%19,%20,%21,%22,%23,%24,%25,%26,%27,%28,%29,%30,%31,%32,%33,%34,%35,%36,%37,%38,%39,%40,%41,%42,%43,%44,%45,%46,%47,%48,%49,%50,%51,%52,%53,%54,%55,%56,%57,%58,%59,%60,%61,%62,%63,%64,%65,%66,%67,%68,%69,%70,%71,%72,%73,%74,%75,%76,%77,%78,%79,%80,%81,%82,%83,%84,%85,%86,%87,%88,%89,%90,%91,%92,%93,%94,%95}, {%96,%97,%98,%99}, %100, p, 1, 1, 0;}"
    : "+f"(d[0]),"+f"(d[1]),"+f"(d[2]),"+f"(d[3]),"+f"(d[4]),"+f"(d[5]),"+f"(d[6]),"+f"(d[7]),"+f"(d[8]),"+f"(d[9]),"+f"(d[10]),"+f"(d[11]),"+f"(d[12]),"+f"(d[13]),"+f"(d[14]),"+f"(d[15]),"+f"(d[16]),"+f"(d[17]),"+f"(d[18]),"+f"(d[19]),"+f"(d[20]),"+f"(d[21]),"+f"(d[22]),"+f"(d[23]),"+f"(d[24]),"+f"(d[25]),"+f"(d[26]),"+f"(d[27]),"+f"(d[28]),"+f"(d[29]),"+f"(d[30]),"+f"(d[31]),"+f"(d[32]),"+f"(d[33]),"+f"(d[34]),"+f"(d[35]),"+f"(d[36]),"+f"(d[37]),"+f"(d[38]),"+f"(d[39]),"+f"(d[40]),"+f"(d[41]),"+f"(d[42]),"+f"(d[43]),"+f"(d[44]),"+f"(d[45]),"+f"(d[46]),"+f"(d[47]),"+f"(d[48]),"+f"(d[49]),"+f"(d[50]),"+f"(d[51]),"+f"(d[52]),"+f"(d[53]),"+f"(d[54]),"+f"(d[55]),"+f"(d[56]),"+f"(d[57]),"+f"(d[58]),"+f"(d[59]),"+f"(d[60]),"+f"(d[61]),"+f"(d[62]),"+f"(d[63]),"+f"(d[64]),"+f"(d[65]),"+f"(d[66]),"+f"(d[67]),"+f"(d[68]),"+f"(d[69]),"+f"(d[70]),"+f"(d[71]),"+f"(d[72]),"+f"(d[73]),"+f"(d[74]),"+f"(d[75]),"+f"(d[76]),"+f"(d[77]),"+f"(d[78]),"+f"(d[79]),"+f"(d[80]),"+f"(d[81]),"+f"(d[82]),"+f"(d[83]),"+f"(d[84]),"+f"(d[85]),"+f"(d[86]),"+f"(d[87]),"+f"(d[88]),"+f"(d[89]),"+f"(d[90]),"+f"(d[91]),"+f"(d[92]),"+f"(d[93]),"+f"(d[94]),"+f"(d[95]) : "r"(a[0]),"r"(a[1]),"r"(a[2]),"r"(a[3]),"l"(db),"r"(sc));
}
__device__ __forceinline__ void wg_ss192_11(float* d, uint64_t da, uint64_t db, int sc) {
  asm volatile("{.reg .pred p; setp.ne.b32 p, %98, 0; wgmma.mma_async.sync.aligned.m64n192k16.f32.bf16.bf16 {%0,%1,%2,%3,%4,%5,%6,%7,%8,%9,%10,%11,%12,%13,%14,%15,%16,%17,%18,%19,%20,%21,%22,%23,%24,%25,%26,%27,%28,%29,%30,%31,%32,%33,%34,%35,%36,%37,%38,%39,%40,%41,%42,%43,%44,%45,%46,%47,%48,%49,%50,%51,%52,%53,%54,%55,%56,%57,%58,%59,%60,%61,%62,%63,%64,%65,%66,%67,%68,%69,%70,%71,%72,%73,%74,%75,%76,%77,%78,%79,%80,%81,%82,%83,%84,%85,%86,%87,%88,%89,%90,%91,%92,%93,%94,%95}, %96, %97, p, 1, 1, 1, 1;}"
    : "+f"(d[0]),"+f"(d[1]),"+f"(d[2]),"+f"(d[3]),"+f"(d[4]),"+f"(d[5]),"+f"(d[6]),"+f"(d[7]),"+f"(d[8]),"+f"(d[9]),"+f"(d[10]),"+f"(d[11]),"+f"(d[12]),"+f"(d[13]),"+f"(d[14]),"+f"(d[15]),"+f"(d[16]),"+f"(d[17]),"+f"(d[18]),"+f"(d[19]),"+f"(d[20]),"+f"(d[21]),"+f"(d[22]),"+f"(d[23]),"+f"(d[24]),"+f"(d[25]),"+f"(d[26]),"+f"(d[27]),"+f"(d[28]),"+f"(d[29]),"+f"(d[30]),"+f"(d[31]),"+f"(d[32]),"+f"(d[33]),"+f"(d[34]),"+f"(d[35]),"+f"(d[36]),"+f"(d[37]),"+f"(d[38]),"+f"(d[39]),"+f"(d[40]),"+f"(d[41]),"+f"(d[42]),"+f"(d[43]),"+f"(d[44]),"+f"(d[45]),"+f"(d[46]),"+f"(d[47]),"+f"(d[48]),"+f"(d[49]),"+f"(d[50]),"+f"(d[51]),"+f"(d[52]),"+f"(d[53]),"+f"(d[54]),"+f"(d[55]),"+f"(d[56]),"+f"(d[57]),"+f"(d[58]),"+f"(d[59]),"+f"(d[60]),"+f"(d[61]),"+f"(d[62]),"+f"(d[63]),"+f"(d[64]),"+f"(d[65]),"+f"(d[66]),"+f"(d[67]),"+f"(d[68]),"+f"(d[69]),"+f"(d[70]),"+f"(d[71]),"+f"(d[72]),"+f"(d[73]),"+f"(d[74]),"+f"(d[75]),"+f"(d[76]),"+f"(d[77]),"+f"(d[78]),"+f"(d[79]),"+f"(d[80]),"+f"(d[81]),"+f"(d[82]),"+f"(d[83]),"+f"(d[84]),"+f"(d[85]),"+f"(d[86]),"+f"(d[87]),"+f"(d[88]),"+f"(d[89]),"+f"(d[90]),"+f"(d[91]),"+f"(d[92]),"+f"(d[93]),"+f"(d[94]),"+f"(d[95]) : "l"(da),"l"(db),"r"(sc));
}
__device__ __forceinline__ void wg_ss192_01(float* d, uint64_t da, uint64_t db, int sc) {
  asm volatile("{.reg .pred p; setp.ne.b32 p, %98, 0; wgmma.mma_async.sync.aligned.m64n192k16.f32.bf16.bf16 {%0,%1,%2,%3,%4,%5,%6,%7,%8,%9,%10,%11,%12,%13,%14,%15,%16,%17,%18,%19,%20,%21,%22,%23,%24,%25,%26,%27,%28,%29,%30,%31,%32,%33,%34,%35,%36,%37,%38,%39,%40,%41,%42,%43,%44,%45,%46,%47,%48,%49,%50,%51,%52,%53,%54,%55,%56,%57,%58,%59,%60,%61,%62,%63,%64,%65,%66,%67,%68,%69,%70,%71,%72,%73,%74,%75,%76,%77,%78,%79,%80,%81,%82,%83,%84,%85,%86,%87,%88,%89,%90,%91,%92,%93,%94,%95}, %96, %97, p, 1, 1, 0, 1;}"
    : "+f"(d[0]),"+f"(d[1]),"+f"(d[2]),"+f"(d[3]),"+f"(d[4]),"+f"(d[5]),"+f"(d[6]),"+f"(d[7]),"+f"(d[8]),"+f"(d[9]),"+f"(d[10]),"+f"(d[11]),"+f"(d[12]),"+f"(d[13]),"+f"(d[14]),"+f"(d[15]),"+f"(d[16]),"+f"(d[17]),"+f"(d[18]),"+f"(d[19]),"+f"(d[20]),"+f"(d[21]),"+f"(d[22]),"+f"(d[23]),"+f"(d[24]),"+f"(d[25]),"+f"(d[26]),"+f"(d[27]),"+f"(d[28]),"+f"(d[29]),"+f"(d[30]),"+f"(d[31]),"+f"(d[32]),"+f"(d[33]),"+f"(d[34]),"+f"(d[35]),"+f"(d[36]),"+f"(d[37]),"+f"(d[38]),"+f"(d[39]),"+f"(d[40]),"+f"(d[41]),"+f"(d[42]),"+f"(d[43]),"+f"(d[44]),"+f"(d[45]),"+f"(d[46]),"+f"(d[47]),"+f"(d[48]),"+f"(d[49]),"+f"(d[50]),"+f"(d[51]),"+f"(d[52]),"+f"(d[53]),"+f"(d[54]),"+f"(d[55]),"+f"(d[56]),"+f"(d[57]),"+f"(d[58]),"+f"(d[59]),"+f"(d[60]),"+f"(d[61]),"+f"(d[62]),"+f"(d[63]),"+f"(d[64]),"+f"(d[65]),"+f"(d[66]),"+f"(d[67]),"+f"(d[68]),"+f"(d[69]),"+f"(d[70]),"+f"(d[71]),"+f"(d[72]),"+f"(d[73]),"+f"(d[74]),"+f"(d[75]),"+f"(d[76]),"+f"(d[77]),"+f"(d[78]),"+f"(d[79]),"+f"(d[80]),"+f"(d[81]),"+f"(d[82]),"+f"(d[83]),"+f"(d[84]),"+f"(d[85]),"+f"(d[86]),"+f"(d[87]),"+f"(d[88]),"+f"(d[89]),"+f"(d[90]),"+f"(d[91]),"+f"(d[92]),"+f"(d[93]),"+f"(d[94]),"+f"(d[95]) : "l"(da),"l"(db),"r"(sc));
}
__device__ __forceinline__ void wg_ss160_01(float* d, uint64_t da, uint64_t db, int sc) {
  asm volatile("{.reg .pred p; setp.ne.b32 p, %82, 0; wgmma.mma_async.sync.aligned.m64n160k16.f32.bf16.bf16 {%0,%1,%2,%3,%4,%5,%6,%7,%8,%9,%10,%11,%12,%13,%14,%15,%16,%17,%18,%19,%20,%21,%22,%23,%24,%25,%26,%27,%28,%29,%30,%31,%32,%33,%34,%35,%36,%37,%38,%39,%40,%41,%42,%43,%44,%45,%46,%47,%48,%49,%50,%51,%52,%53,%54,%55,%56,%57,%58,%59,%60,%61,%62,%63,%64,%65,%66,%67,%68,%69,%70,%71,%72,%73,%74,%75,%76,%77,%78,%79}, %80, %81, p, 1, 1, 0, 1;}"
    : "+f"(d[0]),"+f"(d[1]),"+f"(d[2]),"+f"(d[3]),"+f"(d[4]),"+f"(d[5]),"+f"(d[6]),"+f"(d[7]),"+f"(d[8]),"+f"(d[9]),"+f"(d[10]),"+f"(d[11]),"+f"(d[12]),"+f"(d[13]),"+f"(d[14]),"+f"(d[15]),"+f"(d[16]),"+f"(d[17]),"+f"(d[18]),"+f"(d[19]),"+f"(d[20]),"+f"(d[21]),"+f"(d[22]),"+f"(d[23]),"+f"(d[24]),"+f"(d[25]),"+f"(d[26]),"+f"(d[27]),"+f"(d[28]),"+f"(d[29]),"+f"(d[30]),"+f"(d[31]),"+f"(d[32]),"+f"(d[33]),"+f"(d[34]),"+f"(d[35]),"+f"(d[36]),"+f"(d[37]),"+f"(d[38]),"+f"(d[39]),"+f"(d[40]),"+f"(d[41]),"+f"(d[42]),"+f"(d[43]),"+f"(d[44]),"+f"(d[45]),"+f"(d[46]),"+f"(d[47]),"+f"(d[48]),"+f"(d[49]),"+f"(d[50]),"+f"(d[51]),"+f"(d[52]),"+f"(d[53]),"+f"(d[54]),"+f"(d[55]),"+f"(d[56]),"+f"(d[57]),"+f"(d[58]),"+f"(d[59]),"+f"(d[60]),"+f"(d[61]),"+f"(d[62]),"+f"(d[63]),"+f"(d[64]),"+f"(d[65]),"+f"(d[66]),"+f"(d[67]),"+f"(d[68]),"+f"(d[69]),"+f"(d[70]),"+f"(d[71]),"+f"(d[72]),"+f"(d[73]),"+f"(d[74]),"+f"(d[75]),"+f"(d[76]),"+f"(d[77]),"+f"(d[78]),"+f"(d[79]) : "l"(da),"l"(db),"r"(sc));
}
__device__ __forceinline__ void wg_ss96_01(float* d, uint64_t da, uint64_t db, int sc) {
  asm volatile("{.reg .pred p; setp.ne.b32 p, %50, 0; wgmma.mma_async.sync.aligned.m64n96k16.f32.bf16.bf16 {%0,%1,%2,%3,%4,%5,%6,%7,%8,%9,%10,%11,%12,%13,%14,%15,%16,%17,%18,%19,%20,%21,%22,%23,%24,%25,%26,%27,%28,%29,%30,%31,%32,%33,%34,%35,%36,%37,%38,%39,%40,%41,%42,%43,%44,%45,%46,%47}, %48, %49, p, 1, 1, 0, 1;}"
    : "+f"(d[0]),"+f"(d[1]),"+f"(d[2]),"+f"(d[3]),"+f"(d[4]),"+f"(d[5]),"+f"(d[6]),"+f"(d[7]),"+f"(d[8]),"+f"(d[9]),"+f"(d[10]),"+f"(d[11]),"+f"(d[12]),"+f"(d[13]),"+f"(d[14]),"+f"(d[15]),"+f"(d[16]),"+f"(d[17]),"+f"(d[18]),"+f"(d[19]),"+f"(d[20]),"+f"(d[21]),"+f"(d[22]),"+f"(d[23]),"+f"(d[24]),"+f"(d[25]),"+f"(d[26]),"+f"(d[27]),"+f"(d[28]),"+f"(d[29]),"+f"(d[30]),"+f"(d[31]),"+f"(d[32]),"+f"(d[33]),"+f"(d[34]),"+f"(d[35]),"+f"(d[36]),"+f"(d[37]),"+f"(d[38]),"+f"(d[39]),"+f"(d[40]),"+f"(d[41]),"+f"(d[42]),"+f"(d[43]),"+f"(d[44]),"+f"(d[45]),"+f"(d[46]),"+f"(d[47]) : "l"(da),"l"(db),"r"(sc));
}
__device__ __forceinline__ void wg_ss64_01(float* d, uint64_t da, uint64_t db, int sc) {
  asm volatile("{.reg .pred p; setp.ne.b32 p, %34, 0; wgmma.mma_async.sync.aligned.m64n64k16.f32.bf16.bf16 {%0,%1,%2,%3,%4,%5,%6,%7,%8,%9,%10,%11,%12,%13,%14,%15,%16,%17,%18,%19,%20,%21,%22,%23,%24,%25,%26,%27,%28,%29,%30,%31}, %32, %33, p, 1, 1, 0, 1;}"
    : "+f"(d[0]),"+f"(d[1]),"+f"(d[2]),"+f"(d[3]),"+f"(d[4]),"+f"(d[5]),"+f"(d[6]),"+f"(d[7]),"+f"(d[8]),"+f"(d[9]),"+f"(d[10]),"+f"(d[11]),"+f"(d[12]),"+f"(d[13]),"+f"(d[14]),"+f"(d[15]),"+f"(d[16]),"+f"(d[17]),"+f"(d[18]),"+f"(d[19]),"+f"(d[20]),"+f"(d[21]),"+f"(d[22]),"+f"(d[23]),"+f"(d[24]),"+f"(d[25]),"+f"(d[26]),"+f"(d[27]),"+f"(d[28]),"+f"(d[29]),"+f"(d[30]),"+f"(d[31]) : "l"(da),"l"(db),"r"(sc));
}
__device__ __forceinline__ void wg_rs160_1(float* d, const uint32_t* a, uint64_t db, int sc) {
  asm volatile("{.reg .pred p; setp.ne.b32 p, %85, 0; wgmma.mma_async.sync.aligned.m64n160k16.f32.bf16.bf16 {%0,%1,%2,%3,%4,%5,%6,%7,%8,%9,%10,%11,%12,%13,%14,%15,%16,%17,%18,%19,%20,%21,%22,%23,%24,%25,%26,%27,%28,%29,%30,%31,%32,%33,%34,%35,%36,%37,%38,%39,%40,%41,%42,%43,%44,%45,%46,%47,%48,%49,%50,%51,%52,%53,%54,%55,%56,%57,%58,%59,%60,%61,%62,%63,%64,%65,%66,%67,%68,%69,%70,%71,%72,%73,%74,%75,%76,%77,%78,%79}, {%80,%81,%82,%83}, %84, p, 1, 1, 1;}"
    : "+f"(d[0]),"+f"(d[1]),"+f"(d[2]),"+f"(d[3]),"+f"(d[4]),"+f"(d[5]),"+f"(d[6]),"+f"(d[7]),"+f"(d[8]),"+f"(d[9]),"+f"(d[10]),"+f"(d[11]),"+f"(d[12]),"+f"(d[13]),"+f"(d[14]),"+f"(d[15]),"+f"(d[16]),"+f"(d[17]),"+f"(d[18]),"+f"(d[19]),"+f"(d[20]),"+f"(d[21]),"+f"(d[22]),"+f"(d[23]),"+f"(d[24]),"+f"(d[25]),"+f"(d[26]),"+f"(d[27]),"+f"(d[28]),"+f"(d[29]),"+f"(d[30]),"+f"(d[31]),"+f"(d[32]),"+f"(d[33]),"+f"(d[34]),"+f"(d[35]),"+f"(d[36]),"+f"(d[37]),"+f"(d[38]),"+f"(d[39]),"+f"(d[40]),"+f"(d[41]),"+f"(d[42]),"+f"(d[43]),"+f"(d[44]),"+f"(d[45]),"+f"(d[46]),"+f"(d[47]),"+f"(d[48]),"+f"(d[49]),"+f"(d[50]),"+f"(d[51]),"+f"(d[52]),"+f"(d[53]),"+f"(d[54]),"+f"(d[55]),"+f"(d[56]),"+f"(d[57]),"+f"(d[58]),"+f"(d[59]),"+f"(d[60]),"+f"(d[61]),"+f"(d[62]),"+f"(d[63]),"+f"(d[64]),"+f"(d[65]),"+f"(d[66]),"+f"(d[67]),"+f"(d[68]),"+f"(d[69]),"+f"(d[70]),"+f"(d[71]),"+f"(d[72]),"+f"(d[73]),"+f"(d[74]),"+f"(d[75]),"+f"(d[76]),"+f"(d[77]),"+f"(d[78]),"+f"(d[79]) : "r"(a[0]),"r"(a[1]),"r"(a[2]),"r"(a[3]),"l"(db),"r"(sc));
}
__device__ __forceinline__ void wg_ss8_10(float* d, uint64_t da, uint64_t db, int sc) {
  asm volatile("{.reg .pred p; setp.ne.b32 p, %6, 0; wgmma.mma_async.sync.aligned.m64n8k16.f32.bf16.bf16 {%0,%1,%2,%3}, %4, %5, p, 1, 1, 1, 0;}"
    : "+f"(d[0]),"+f"(d[1]),"+f"(d[2]),"+f"(d[3]) : "l"(da),"l"(db),"r"(sc));
}

constexpr uint32_t DB = 1024;
constexpr int WSLOT = 24576, NW = 6, ASLOT = 8192, ARING = 4 * ASLOT;
constexpr int OFF_A = NW * WSLOT;
constexpr int OFF_PB = OFF_A + 2 * ARING;
constexpr int OFF_CV = OFF_PB + 16384, OFF_ST = OFF_CV + 768, OFF_TS = OFF_ST + 256, OFF_MODR = OFF_TS + 512, OFF_BAR = OFF_MODR + 80, SMEM_BYTES = OFF_BAR + 1168;
constexpr int OFF_BX = OFF_PB, OFF_AX = OFF_BX + 12288, OFF_RT = OFF_AX + 2048, OFF_GB = OFF_RT + 512, OFF_CO = OFF_CV;
constexpr int OFF_UV = 5 * WSLOT, OFF_UVE = OFF_PB, OFF_SX = OFF_A + ARING + 3 * ASLOT, OFF_X1 = 2 * WSLOT + ASLOT, OFF_XCH = WSLOT;
constexpr int OFF_Q = 0, KV_V = 4096, KV_H = 8192, F_E = 16, F_O = 4176, OFF_WM = 3 * WSLOT, OFF_TAP = 168576, OFF_MR = OFF_A + 3 * ASLOT;
constexpr uint64_t pk5(int a, int b, int c, int d, int e) { return (uint64_t)(a / 128) | (uint64_t)(b / 128) << 12 | (uint64_t)(c / 128) << 24 | (uint64_t)(d / 128) << 36 | (uint64_t)(e / 128) << 48; }
constexpr uint64_t T_KV = pk5(20480, 30720, 40960, 180224, 190464), T_F = pk5(51200, 59648, 200192, 147456, 155904), T_X = pk5(208512, 164352, 68096, 208512, 164352),
                   T_P = pk5(131072, OFF_PB, 114688, 131072, OFF_PB);
__host__ __device__ __forceinline__ uint32_t tab(uint64_t t, int c) { return ((uint32_t)(t >> (12 * c)) & 0xFFF) << 7; }
enum { B_KV = 0, B_FRAW = 5, B_Q = 10, B_WM = 15, B_XR, B_MR = B_XR + 5, B_QTOK, B_ST1, B_MODR, B_S3 = B_MODR + 5, B_FIN, B_FL = 32, B_PFULL = B_FL + 5, B_PEMPTY = B_PFULL + 5, B_FRDY = B_PEMPTY + 5,
       B_G3 = B_FRDY + 5, B_EXT, B_QTD, B_LAG, B_GB, B_UVD, B_TURN, B_FULL = 60, B_RETRY = B_FULL + 33, B_XFREE = B_RETRY + 9, B_BX, B_UVB, B_UVE, B_SX, B_EMPTY = 109 };
static_assert(B_MODR + 5 <= B_FL && B_UVD < B_FULL && B_SX + 2 == B_EMPTY - 1, "barrier groups");
#define BAR(i) (base + OFF_BAR + 8 * (i))

constexpr int NE = 24;
struct Maps { CUtensorMap km, v, q, kh, tap, wm, w1s, w3s, xs, w1, w3, w1e, w3e, x1s, x1b, w2a, w2b, outa, outb; };
struct Ptrs { const bf16 *ssmk, *c, *ssmd; Scratch* g; uint64_t prog, cprog[2]; int boff, th, wms, ulo, uhi; uint32_t c0, fin, turn, mr2, m3, seq; float one; uint2 sched[NE]; uint32_t wdep[20], wt[5]; uint2 w2t[12]; int hid[3][9]; };

#define REGION_IDS int tid, lane, bid; \
  asm volatile("mov.u32 %0, %%tid.x;" : "=r"(tid)); asm volatile("mov.u32 %0, %%laneid;" : "=r"(lane)); asm volatile("mov.u32 %0, %%ctaid.x;" : "=r"(bid)); \
  const int i0 = tid & 127; (void)i0; (void)lane; (void)bid

__device__ __forceinline__ void ffn_role(int& h, int& j, int& r) {
  uint32_t b;
  asm volatile("mov.u32 %0, %%ctaid.x;" : "=r"(b));
  const uint32_t c = b >> 1, q = (c - 36) * 37 >> 8, e = c - 36 - 7 * q;
  h = b & 1;
  const uint32_t k = c < 4 ? 0 : c < 36 ? (c - 4) & 7 : e + 1, p = c < 4 ? c : c < 36 ? (c - 4) >> 3 : q, up = c - 4 >= 32;
  j = 2 * (k & 1) + up;
  r = 2 * (k & 6) + p;
}
__device__ __forceinline__ int fslice(int j, int e) { return e == 2 ? j ^ 1 : (~j & 2) + e; }
__device__ __forceinline__ int mod_ch(int p) { return p < 40 ? (p >> 3) * 128 + (p & 1) * 64 : 64 * (p < 50 ? p - 40 : p - 50); }
__device__ __forceinline__ int mod_col(int p) { return mod_ch(p) + 640 * (p < 40 ? 0x4210 >> (2 * (p & 6)) & 7 : p < 50 ? 3 : 5); }
__device__ __forceinline__ uint32_t mod_sum(uint2 v) { return pack_bf16(0.f, __uint_as_float(v.x) + __uint_as_float(v.y)); }

constexpr int NT = 3, LAG2 = 29, MG = 4;
__device__ __forceinline__ int w_block(int up, int m) { return m == 1 ? 2 + 3 * up : 3 * (m >> 1) + up; }
__host__ __device__ constexpr int w2_at(int v) { return 8192 * (v ? 0x0613030008ull >> v % 5 * 8 & 255 : 15); }
__host__ __device__ constexpr int w2_step(int v) { return 8192 * (v ? 0x32113 >> v % 5 * 4 & 15 : 1); }
__host__ __device__ constexpr int hid_at(int m, int g) { return 8192 * ((g ? 0x0D07110F1816ull : 0x0A19101A1412ull) >> m % 6 * 8 & 255); }
__host__ __device__ constexpr uint32_t w2_desc(int v) { return (DB + w2_at(v)) >> 4 | w2_step(v) << 12; }
__device__ __forceinline__ int next_slot(int s) { return s >= 4 * WSLOT ? 0 : s + WSLOT; }

template <int U> __device__ __forceinline__ void cstep(float* acc, const uint32_t* A, uint64_t db) {
  const uint32_t* a = A + 4 * U;
  const uint64_t d = db + 16 * U;
  if (U == 4) { wg_rs64_0(acc + 96, A, db + 192, 0); wg_rs48_0(acc + 96, A + 4, db + 208, 1); wg_rs32_0(acc + 96, A + 8, db + 224, 1); wg_rs16_0(acc + 96, A + 12, db + 240, 1); }
  if (U <= 4) wg_rs192_0(acc, a, d, U);
  if (U == 5) wg_rs176_0(acc, a, d, 1);
  if (U == 6) wg_rs160_0(acc, a, d, 1);
  if (U == 7) wg_rs144_0(acc, a, d, 1);
  if (U == 8) wg_rs128_0(acc, a, d, 1);
  if (U == 9) wg_rs112_0(acc, a, d, 1);
  if (U == 10) wg_rs96_0(acc, a, d, 1);
  if (U == 11) wg_rs80_0(acc, a, d, 1);
  if (U == 12) wg_rs64_0(acc, a, d, 1);
  if (U == 13) wg_rs48_0(acc, a, d, 1);
  if (U == 14) wg_rs32_0(acc, a, d, 1);
  if (U == 15) wg_rs16_0(acc, a, d, 1);
}
template <int U0, int U1> __device__ __forceinline__ void csteps(float* acc, const uint32_t* A, uint64_t db) {
  cstep<U0>(acc, A, db);
  if constexpr (U0 > U1) csteps<U0 - 1, U1>(acc, A, db);
}
template <int U0, int U1> __device__ __forceinline__ void cload(uint32_t* A, uint32_t fa) {
  asm volatile("{ld.shared.b32 %0, [%4+%5]; ld.shared.b32 %1, [%4+%5+128]; ld.shared.b32 %2, [%4+%5+16]; ld.shared.b32 %3, [%4+%5+144];}"
               : "=r"(A[4 * U0]), "=r"(A[4 * U0 + 1]), "=r"(A[4 * U0 + 2]), "=r"(A[4 * U0 + 3]) : "r"(fa), "n"(256 * U0) : "memory");
  if constexpr (U0 > U1) cload<U0 - 1, U1>(A, fa);
}

__device__ __forceinline__ void mod_gemv(Scratch* G, uint32_t wm, int unit, int w, int lane, uint32_t par) {
  float d[4] = {};
  fence_regs(d);
  wg_fence();
#pragma unroll 1
  for (int k = 0; k < 20; k += 2) {
    wg_ss8_10(d, mkdesc(DB + wm + 2048 * k, 16, 1024, 1), mkdesc(DB + OFF_CV + 32 * k, 16, 128, 0), 1);
    wg_ss8_10(d, mkdesc(DB + wm + 2048 * k + 2048, 16, 1024, 1), mkdesc(DB + OFF_CV + 32 * k + 32, 16, 128, 0), 1);
  }
  wg_commit();
  const int p = unit >> 1, ch = mod_ch(p) + 16 * w + (lane >> 2);
  uint32_t* dst = (uint32_t*)(p < 40 ? &G->modc[ch & 127][8 + (p >> 1)] : &G->modv[p >= 50][ch]) + (unit & 1);
  wg_wait<0>();
  fence_regs(d);
  if (!(lane & 3)) {
    publish(dst, (__float_as_uint(d[0]) & ~1u) | par);
    publish(dst + (p < 40 ? 512 : 16), (__float_as_uint(d[2]) & ~1u) | par);
    if (p < 40 && (p & 6) == 6) {
      dst = (uint32_t*)&G->modv[2][ch] + (unit & 1);
      publish(dst, (__float_as_uint(d[0]) & ~1u) | par);
      publish(dst + 16, (__float_as_uint(d[2]) & ~1u) | par);
    }
  }
}
__device__ __forceinline__ void silu_vector(const bf16* c, uint32_t base) {
  REGION_IDS;
  const uint32_t c0 = ldg32(c + 320 * (bid & 1) + 2 * i0), c1 = ldg32(c + 320 * (bid & 1) + 256 + 2 * lane);
  sts32(base + OFF_CV + 4 * i0, pack_bf16(silu_f(bf_lo(c0)), silu_f(bf_hi(c0))));
  sts32(base + OFF_CV + 512 + 4 * lane, pack_bf16(silu_f(bf_lo(c1)), silu_f(bf_hi(c1))));
  fence_async_smem();
}

__device__ __forceinline__ void mod_poll(Scratch* G, uint32_t base, int c, int n, uint32_t epoch) {
  REGION_IDS;
  const int e = 4 * c + (lane & (4 * n - 1));
  uint2 m;
  int it = 0;
#pragma unroll 1
  do m = ld_relaxed64(&G->modc[bid][8 + e]); while (__any_sync(~0u, ((m.x ^ epoch) | (m.y ^ epoch)) & 1) && ++it < SPIN_LIMIT);
  sts32(base + OFF_MODR + 4 * e, __byte_perm(badd2(mod_sum(m), (lane & 1) * 0x3F800000u), 0, 0x3232));
  __syncwarp();
  if (elect()) { mbar_arrive(BAR(B_MODR + c)); if (n > 1) mbar_arrive(BAR(B_MODR + c + 1)); }
}
__device__ __forceinline__ void row_stats(Scratch* G, uint32_t base, uint32_t epoch) {
  REGION_IDS;
  mbar_wait_cluster(BAR(B_ST1));
  if (lane < 8) red_hint(G->hint[5][lane]);
  const uint2 x = lds64(base + OFF_ST + 8 * (lane & 15)), y = lds64(base + OFF_ST + 128 + 8 * (lane & 15));
  float m, sd;
  ln_final(__uint_as_float(x.x) + __uint_as_float(y.x), __uint_as_float(x.y) + __uint_as_float(y.y), m, sd);
  sd = rbf(rcpf(sd));
  const uint32_t mr = pack_bf16(sd, -rbf(m) * sd), tg = lane & 7 ? 0 : lane & 8 ? 1 : 0x8000;
  const uint32_t o = __byte_perm(__shfl_sync(~0u, mr, 2 * lane & 14), __shfl_sync(~0u, mr, (2 * lane & 14) + 1), (lane & 8) ? 0x7632 : 0x5410);
  if (lane < 16) st_relaxed32(&G->st1[lane >> 3][8 * bid + (lane & 7)], (o & ~tg) | ((epoch & 1) * tg));
  if (elect()) mbar_arrive(BAR(B_FIN));
}
template <int B, int NEXT> __device__ __forceinline__ void strip(Scratch* G, const CUtensorMap* map, uint32_t base, int c, uint32_t epoch, uint32_t& ph, uint32_t& pre, float4& s) {
  REGION_IDS;
  int h, j, r, it = 0;
  ffn_role(h, j, r);
  const uint32_t buf = base + OFF_SX + 4096 * B, a = buf + 32 * lane;
#pragma unroll 1
  while (__any_sync(~0u, pre != 64 * epoch) && ++it < SPIN_LIMIT) pre = ld_relaxed32(G->xsh[c][(r & 6) + (j >> 1)]);
#pragma unroll 1
  for (it = 0; it < SPIN_LIMIT; it++) {
    if (elect()) { mbar_expect_tx(BAR(B_SX + B), 4096); tma2d(buf, map, 128 * r + 64 * h, D_ * (epoch & 1) + 128 * c + 32 * j, BAR(B_SX + B)); }
    mbar_wait(BAR(B_SX + B), ph);
    ph ^= 1;
    if (__all_sync(~0u, min(min(lds32(a), lds32(a + 1024)), min(lds32(a + 2048), lds32(a + 3072))))) break;
  }
  pre = 0;
  if (c == NEXT - 1 || c == NEXT - 2) pre = ld_relaxed32(G->xsh[c + 1][(r & 6) + (j >> 1)]);
#pragma unroll 1
  for (uint32_t o = buf + 4 * lane; o < buf + 4096; o += 1024) {
    uint32_t x[8];
#pragma unroll
    for (int i = 0; i < 8; i++) x[i] = lds32(o + 128 * i);
#pragma unroll
    for (int i = 0; i < 8; i++) { const float lo = bf_lo(x[i]), hi = bf_hi(x[i]); s.x += lo; s.y = fmaf(lo, lo, s.y); s.z += hi; s.w = fmaf(hi, hi, s.w); }
  }
}
__device__ __forceinline__ void planes(uint32_t a, uint4& y) {
  uint4 z = lds128(a + 4096);
  y.x = badd2(y.x, z.x); y.y = badd2(y.y, z.y); y.z = badd2(y.z, z.z); y.w = badd2(y.w, z.w);
  z = lds128(a + 8192);
  const uint4 m = lds128(a + 12288);
  y.x = badd2(y.x, badd2(z.x, m.x)); y.y = badd2(y.y, badd2(z.y, m.y)); y.z = badd2(y.z, badd2(z.z, m.z)); y.w = badd2(y.w, badd2(z.w, m.w));
}
__device__ __forceinline__ void mr_poll(Scratch* G, uint32_t base, uint32_t epoch) {
  int it = 0;
#pragma unroll 1
  while (__any_sync(~0u, ld_relaxed32(G->hint[5][4 * (blockIdx.x >> 6) + (blockIdx.x >> 3 & 3)]) != epoch << 7) && ++it < SPIN_LIMIT);
  if (elect()) { mbar_expect_tx(BAR(B_MR), 8192); bulk_load(base + OFF_MR, G->st1, 8192, BAR(B_MR)); mbar_arrive(BAR(B_QTOK)); }
}

__global__ void __cluster_dims__(2, 1, 1) __launch_bounds__(512, 1) k_fused(const __grid_constant__ Ptrs P, const __grid_constant__ Maps maps) {
  Scratch* const G = P.g;
  extern __shared__ __align__(1024) uint8_t smem_raw[];
  const uint32_t t_start = clock();
  const uint32_t base = __shfl_sync(~0u, smem_u32(smem_raw), 0);
  uint32_t t_iss = 0;
  if (threadIdx.x < 32 && blockIdx.x < 128) {
    mbar_init<1>(BAR(0), 1);
    if (elect()) {
      const int c0 = 64 * (blockIdx.x & 1), c1 = 2 * (blockIdx.x & 126);
      mbar_expect_tx(BAR(B_KV), 12288);
      tma3d(base + tab(T_KV, 0), &maps.km, c0, c1, 0, BAR(B_KV));
      tma3d(base + tab(T_KV, 0) + KV_V, &maps.v, c0, c1, 0, BAR(B_KV));
      tma3d(base + tab(T_KV, 0) + KV_H, &maps.kh, c0, c1 - 1, 5, BAR(B_KV));
      tma3d(base + OFF_TAP, &maps.tap, 0, blockIdx.x & 1, 0, BAR(B_KV));
    }
    if (P.boff) mbar_wait(BAR(0));
  }
  if ((base & 0xFFFFFFu) != DB) __trap();
  const int wid = __shfl_sync(~0u, threadIdx.x >> 5, 0), wg = wid >> 2, w = wid & 3;
  if (blockIdx.x + P.boff >= 128) {
    REGION_IDS;
    const int nu = 30 - (P.uhi - P.ulo) / 4;
    auto tile = [&](int n) { return 2 * (n < P.ulo / 4 ? n : n + 30 - nu) + (blockIdx.x >> 1 & 1); };
    auto fetch = [&](int n, int b) {
      if (elect()) {
        mbar_expect_tx(BAR(n), 40960);
#pragma unroll
        for (int k = 0; k < 5; k++) tma3d(base + 40960 * b + 8192 * k, &maps.wm, mod_col(tile(n)), 320 * (blockIdx.x & 1) + 64 * k, 0, BAR(n));
      }
    };
    if (P.boff) __syncthreads();
    if (wid == 12) {
      mbar_init<4>(BAR(0), 1);
#pragma unroll 1
      for (int n = 0; n < 4; n++) fetch(n, n);
      mbar_init<26>(BAR(4), 1);
      mbar_init<60>(BAR(32), 4);
    }
    const uint32_t par = ~ld_relaxed32(G->hint[7][0]) >> 7 & 1;
    silu_vector(P.c, base);
    __syncthreads();
    if (wid == 12) {
      wait_clock(t_start + P.th);
#pragma unroll 1
      for (int n = 4, b = 4; n < nu; n++) {
        if (n >= 5) mbar_wait(BAR(27 + n));
        fetch(n, b);
        b = b == 4 ? 0 : b + 1;
      }
    } else if (wg < 2) {
      uint32_t cv[40];
#pragma unroll
      for (int k = 0; k < 40; k++) cv[k] = lds32(base + OFF_CV + 16 * k + 4 * (lane & 3));
      const uint32_t a0 = base + 128 * ((lane & 7) + (lane >> 4) * 8) + (((2 * w + (lane >> 3 & 1)) ^ (lane & 7)) << 4);
#pragma unroll 1
      for (int n = wg; n < nu; n += 2) {
        float d[16] = {};
        mbar_wait(BAR(n));
#pragma unroll
        for (int k0 = 0; k0 < 20; k0 += 10) {
          uint32_t a[40];
#pragma unroll
          for (int k = 0; k < 10; k++) ldmatrix_x4_t(a + 4 * k, a0 + 40960 * (n % 5) + 2048 * (k0 + k));
#pragma unroll
          for (int k = 0; k < 10; k++)
            asm("mma.sync.aligned.m16n8k16.row.col.f32.bf16.bf16.f32 {%0,%1,%2,%3}, {%4,%5,%6,%7}, {%8,%9}, {%0,%1,%2,%3};"
                : "+f"(d[4 * (k & 3)]), "+f"(d[4 * (k & 3) + 1]), "+f"(d[4 * (k & 3) + 2]), "+f"(d[4 * (k & 3) + 3])
                : "r"(a[4 * k]), "r"(a[4 * k + 1]), "r"(a[4 * k + 2]), "r"(a[4 * k + 3]), "r"(cv[2 * (k0 + k)]), "r"(cv[2 * (k0 + k) + 1]));
        }
        arrive1(BAR(32 + n));
        if (!(lane & 3)) {
          sts32(base + 204800 + 256 * n + 64 * w + lane, __float_as_uint(d[0] + d[4] + (d[8] + d[12])));
          sts32(base + 204800 + 256 * n + 64 * w + lane + 32, __float_as_uint(d[2] + d[6] + (d[10] + d[14])));
        }
        arrive1(BAR(62 + n));
      }
    } else if (wg == 2) {
#pragma unroll 1
      for (int n = w; n < nu; n += 4) {
        const int t = tile(n), ch = mod_ch(t) + lane;
        uint32_t* q = (uint32_t*)(t < 40 ? &G->modc[ch & 127][8 + (t >> 1)] : &G->modv[t >= 50][ch]) + (bid & 1);
        mbar_wait(BAR(62 + n));
        const uint32_t x = (lds32(base + 204800 + 256 * n + 4 * lane) & ~1u) | par, y = (lds32(base + 204928 + 256 * n + 4 * lane) & ~1u) | par;
        publish(q, x);
        publish(q + (t < 40 ? 2048 : 64), y);
        if (t < 40 && (t & 6) == 6) {
          q = (uint32_t*)&G->modv[2][ch] + (bid & 1);
          publish(q, x);
          publish(q + 64, y);
        }
      }
    }
    return;
  }
  if (wid < 15) mbar_init<4>(BAR(4 * wid + (wid == 0)), wid < 8 ? 1 : 4);
  asm volatile("fence.mbarrier_init.release.cluster; bar.sync 0, 512;" ::: "memory");
  asm volatile("barrier.cluster.arrive.relaxed.aligned;" ::: "memory");
#define LAUNCHES const uint32_t launches = ld_relaxed32(G->hint[7][blockIdx.x >> 4])
#define EPOCH ((__shfl_sync(~0u, launches, 0) >> 7) + 1)
  if (wg == 3) {
    asm volatile("setmaxnreg.dec.sync.aligned.u32 24;");
    if (w == 1) {
      {
        REGION_IDS;
        const int c1 = 2 * (bid & 126), ws = bid >= P.ulo && bid < P.uhi ? P.wms : 99;
#pragma unroll 1
        for (int e = 0; e < NE; e++) {
          const uint2 x = P.sched[e];
          const uint32_t kind = x.x >> 16 & 15, ch = x.x >> 13 & 0x380, dst = base + (x.y & 0x3FFFF), b = BAR(x.y >> 18);
          wait_clock(t_start + (x.x & 0xFFFF));
          if (kind < 3 && elect()) tma3d(dst, &maps.km + kind, ch + 64 * (bid & 1), c1, 0, b);
          if (kind == 0 && elect()) tma3d(dst + KV_H, &maps.kh, ch + 64 * (bid & 1), c1 - 1, 5, b);
          if (kind == 3 && elect()) bulk_load(dst, P.ssmk + (ch + bid) * S_, 4096, b);
          if ((uint32_t)(e - ws) < 5 && elect()) tma3d(base + OFF_WM + 8192 * (e - ws), &maps.wm, mod_col(bid >> 1), 320 * (bid & 1) + 64 * (e - ws), 0, BAR(B_WM));
          if ((uint32_t)(e - 8) < 13 && elect()) prefetch_map(&maps.w1s + (e - 8));
        }
      }
      cluster_wait();
      int h, j, r;
      ffn_role(h, j, r);
      mbar_wait(BAR(B_QTD));
      mbar_wait(BAR(B_FL));
#pragma unroll 1
      for (int u = 0; u < 20; u++) {
        const uint32_t x = P.wdep[u], s = base + (x & ~8191u);
        if (u < 5) wait_clock(t_start + P.wt[u]);
        mbar_wait(BAR(opaque(x & 255)));
        if (elect()) {
          mbar_expect_tx(BAR(B_FULL + u), WSLOT + 4 * (x & 4096));
#pragma unroll
          for (int k = 0; k < 6; k++) tma3d(s + 4096 * w_block(k & 1, k >> 1), &maps.w1s + (k & 1), 0, 32 * u, 3 * (4 * h + j) + (k >> 1), BAR(B_FULL + u));
        }
      }
#pragma unroll 1
      for (int v = 0; v < 12; v++) {
        const int q = v * 11 >> 5, e = v - 3 * q, k32 = 24 * h + (q ? 6 * fslice(j, e) + 2 * q - 2 : 6 * j + 2 * e);
        const uint2 x = P.w2t[v];
        mbar_wait(BAR(x.y));
        if (elect()) {
          mbar_expect_tx(BAR(B_FULL + 20 + v), q ? WSLOT + 2 * ASLOT : WSLOT);
#pragma unroll
          for (int k = 0; k < 3; k++) tma5d(base - DB + 16 * ((x.x & 0xFFFF) + k * (x.x >> 16)), &maps.w2a + (q > 0), k < 2 ? 128 * j + 64 * k : 512 + 32 * (j & 2), k32, BAR(B_FULL + 20 + v));
        }
      }
    } else if (w == 0) {
      LAUNCHES;
      uint32_t epoch;
      {
        REGION_IDS;
        const unsigned* hp = G->hint[0][4 * (bid >> 6) + (bid >> 3 & 3)];
        uint32_t v = ld_relaxed32(hp + 256 * min(lane, 5));
        if (lane < 3) sts128(base + tab(T_X, lane) + 4096, 0, 0, 0, 0);
        if (lane && lane <= B_WM) mbar_expect_tx(BAR(lane), lane < B_FRAW ? 9728 : lane == B_WM ? 40960 : 4096);
        epoch = EPOCH;
        fence_async_smem();
        const uint32_t rdy = __ballot_sync(~0u, v == epoch << 6);
        uint32_t nx = 0, nm = 0;
#pragma unroll 1
        for (uint32_t seq = P.seq; seq; seq >>= 2) {
          int it = 0;
          if (seq & 1) {
            if (!(seq & 2)) mod_poll(G, base, nm, 1 + (seq == 13), epoch);
            nm++;
          } else if (seq & 2) {
            mr_poll(G, base, epoch);
          } else {
            if (!(rdy >> nx & 1)) {
#pragma unroll 1
              while (__any_sync(~0u, ld_relaxed32(hp + 256 * nx) != epoch << 6) && ++it < SPIN_LIMIT);
            }
            if (nx >= 3) mbar_wait(BAR(B_PFULL - 3 + nx));
            if (elect()) { mbar_expect_tx(BAR(B_XR + nx), 4096); bulk_load(base + tab(T_X, nx), G->xr + (128 * nx + bid) * 256, 4096, BAR(B_XR + nx)); }
            nx++;
          }
        }
      }
      REGION_IDS;
      int h, j, r;
      ffn_role(h, j, r);
      mbar_wait(BAR(B_G3));
      {
        const uint2* mp = &G->modv[lane & 4 ? 0 : 2][40 * (r & 14) + (lane & 24) + 2 * (lane & 3)];
        uint4 v[3];
        int it = 0;
#pragma unroll 1
        do {
          v[0] = ld_relaxed128(mp); v[1] = ld_relaxed128(mp + 32); v[2] = ld_relaxed128(mp + 64 - (lane & 16));
        } while (__any_sync(~0u, ((v[0].x ^ epoch) | (v[0].y ^ epoch) | (v[0].z ^ epoch) | (v[0].w ^ epoch) | (v[1].x ^ epoch) | (v[1].y ^ epoch) | (v[1].z ^ epoch) | (v[1].w ^ epoch) |
                                  (v[2].x ^ epoch) | (v[2].y ^ epoch) | (v[2].z ^ epoch) | (v[2].w ^ epoch)) & 1) && ++it < SPIN_LIMIT);
#pragma unroll
        for (int i = 0; i < 3; i++)
          sts32(base + OFF_CO + 128 * i + 4 * lane, badd2(pack_bf16(__uint_as_float(v[i].x) + __uint_as_float(v[i].y), __uint_as_float(v[i].z) + __uint_as_float(v[i].w)), lane & 4 ? 0 : 0x3F803F80u));
      }
      fence_async_smem();
      __syncwarp();
      ffn_role(h, j, r);
      mbar_wait(BAR(B_PEMPTY + 3));
      if (elect()) {
        mbar_expect_tx(BAR(B_UVB), WSLOT);
        tma3d(base + OFF_UV, &maps.w1 + (r & 1), 0, 40 * (r & 14), 3 * (4 * h + j), BAR(B_UVB));
        tma3d(base + OFF_UV + 12288, &maps.w1 + (r & 1), 0, 40 * (r & 14) + 32, 3 * (4 * h + j), BAR(B_UVB));
      }
      {
        float4 s = {};
        uint32_t ph = 0, pre = 0;
#pragma unroll 1
        for (int c = 2; c < 4; c++) strip<1, 3>(G, &maps.x1s, base, c, epoch, ph, pre, s);
        __syncwarp();
        sts128(base + OFF_SX + 4096 + 16 * lane, __float_as_uint(s.x), __float_as_uint(s.y), __float_as_uint(s.z), __float_as_uint(s.w));
        arrive1(BAR(B_S3));
      }
      ffn_role(h, j, r);
      cluster_wait();
      mbar_wait(BAR(B_UVD));
      asm volatile("fence.acq_rel.gpu;" ::: "memory");
      if (lane < 8) red_hint(G->hint[7][lane]);
      unsigned x;
      int it = 0;
#pragma unroll 1
      do { asm volatile("ld.acquire.gpu.global.u32 %0, [%1];" : "=r"(x) : "l"(G->hint[7][bid >> 4]) : "memory"); } while (__any_sync(~0u, x != 128 * epoch) && ++it < SPIN_LIMIT);
      fence_async_all();
      const int ch = D_ * (epoch & 1);
      mbar_wait(BAR(B_EXT));
      mbar_wait(BAR(B_EMPTY + 18));
      if (elect()) {
        mbar_expect_tx(BAR(B_FULL + 32), 20480);
#pragma unroll
        for (int k = 0; k < 4; k++) tma2d(base + (k < 3 ? OFF_X1 + k * WSLOT : OFF_SX), &maps.x1b, 128 * r + 64 * h, ch + 128 * j + 32 * (k ^ (j & 1)), BAR(B_FULL + 32));
        tma2d(base + OFF_SX + 4096, &maps.x1b, 128 * r + 64 * h, ch + 512 + 32 * j, BAR(B_FULL + 32));
        mbar_expect_tx(BAR(B_FULL), 8192); mbar_expect_tx(BAR(B_FULL + 1), 8192); mbar_expect_tx(BAR(B_FULL + 2), 4096);
      }
      mbar_wait(BAR(B_EMPTY + 27));
      if (elect()) mbar_arrive_remote(mapa(BAR(B_XFREE), h ^ 1));
    } else {
      LAUNCHES;
      uint32_t epoch;
      {
        REGION_IDS;
        uint32_t dv;
        asm volatile("ld.global.nc.u16 %0, [%1];" : "=r"(dv) : "l"(P.ssmd + 128 * (lane & 7) % D_ + bid));
        if (lane < 5) sts128(base + tab(T_F, lane) + (w & 1) * (F_O - 16), 0, 0, 0, 0);
        epoch = EPOCH;
        __syncwarp();
#pragma unroll 1
        for (int c = 0; c < 5; c++) {
          const float d = i0 == 64 ? bf_lo(dv) : 0.f;
          dv = __shfl_down_sync(~0u, dv, 1);
          const uint32_t a = base + tab(T_F, c) + 16 * (i0 - 64);
          mbar_wait(BAR(B_FRAW + c));
#pragma unroll
          for (int k = 0; k < 4; k++) {
            uint4 x = lds128(a + F_E + 1024 * k);
            const uint32_t pv = lds32(a + F_E - 4 + 1024 * k);
            if (k == 0) { x.x = pack_bf16(bf_lo(x.x) + d, bf_hi(x.x)); sts32(a + F_E, x.x); }
            sts128(a + F_O + 1024 * k, __byte_perm(pv, x.x, 0x5432), __byte_perm(x.x, x.y, 0x5432), __byte_perm(x.y, x.z, 0x5432), __byte_perm(x.z, x.w, 0x5432));
          }
          __syncwarp();
          if (elect()) mbar_arrive2(BAR(B_FRDY + c));
          if (c == 0 && w == P.fin) row_stats(G, base, epoch);
        }
      }
      REGION_IDS;
      int h, j, r;
      ffn_role(h, j, r);
      cluster_wait();
      if (w == 2) {
        const unsigned* fp = G->xsh[lane < 10 ? lane >> 1 : 0][(r & 6) + (lane & 1)];
        uint32_t rdy = 0, s = 0;
        mbar_wait(BAR(B_QTD));
        mbar_wait(BAR(B_FL + 2));
#pragma unroll 1
        for (int n = 0; n < 10; n++) {
          mbar_wait(BAR(n < 2 ? B_FL + 3 + n : n == 2 ? B_PFULL + 4 : B_EMPTY + 2 * n - 5));
#pragma unroll 1
          for (int it = 0; !(rdy >> n & 1) && it < SPIN_LIMIT; it++) rdy = __ballot_sync(~0u, ld_relaxed32(fp) == 64 * epoch);
          if (elect()) {
            tma2d(base + OFF_A + s, &maps.xs, 128 * r + 64 * h, 64 * n, BAR(B_FULL + 2 * n));
            tma2d(base + OFF_A + ARING + s, &maps.xs, 128 * r + 64 - 64 * h, 64 * n, BAR(B_FULL + 2 * n));
          }
          s = s == 2 * ASLOT ? 0 : s + ASLOT;
        }
      } else {
        if (P.m3 < 5) mod_poll(G, base, P.m3, 1, epoch);
        float4 s = {};
        uint32_t ph = 0, pre = 0;
        mbar_wait(BAR(B_FL + 2));
        mbar_wait(BAR(B_PFULL + 3));
#pragma unroll 1
        for (int c = 0; c < 5; c = c == 1 ? 4 : c + 1) {
          if (c == 4) {
            ffn_role(h, j, r);
            mbar_wait(BAR(B_PEMPTY + 4));
            if (elect()) {
              mbar_expect_tx(BAR(B_UVE), 6144);
              tma3d(base + OFF_UVE, &maps.w1e + (r & 1), 0, 40 * (r & 14) + 64, 3 * (4 * h + j), BAR(B_UVE));
            }
          }
          strip<0, 1>(G, &maps.x1s, base, c, epoch, ph, pre, s);
        }
        mbar_wait(BAR(B_S3));
        const uint4 y = lds128(base + OFF_SX + 4096 + 16 * lane);
        const float s0 = s.x + __uint_as_float(y.x), q0 = s.y + __uint_as_float(y.y), s1 = s.z + __uint_as_float(y.z), q1 = s.w + __uint_as_float(y.w);
        ffn_role(h, j, r);
        asm volatile("{.reg .b128 t, x; .reg .b64 a, b; mov.b64 a, {%1,%2}; mov.b64 b, {%3,%4}; mov.b128 x, {a,b}; atom.relaxed.gpu.global.exch.b128 t, [%0], x;}"
                     ::"l"(&G->st2[2 * r + h][j][4 * lane]), "r"((__float_as_uint(s0) & ~1u) | (epoch & 1)), "f"(q0), "r"((__float_as_uint(s1) & ~1u) | (epoch & 1)), "f"(q1) : "memory");
        uint4* z = G->x1[~epoch & 1] + 1280 * bid + lane;
#pragma unroll 1
        for (int k = 0; k < 40; k++) st_relaxed128(z + 32 * k, 0, 0, 0, 0);
      }
    }
  } else if (wg == 2) {
    asm volatile("setmaxnreg.dec.sync.aligned.u32 40;");
    mbar_init<12>(BAR(B_FULL + 12 * w), 1);
    mbar_init<9>(BAR(B_EMPTY - 1 + 9 * w), 8);
    asm volatile("fence.mbarrier_init.release.cluster;" ::: "memory");
    LAUNCHES;
    const uint32_t epoch = EPOCH;
    cluster_wait();
#pragma unroll 1
    for (uint64_t prog = P.prog; prog; prog >>= 4) {
      REGION_IDS;
      const int s = (prog & 7) - 1;
      if (!(prog & 8)) {
        const uint32_t a = base + tab(T_KV, s) + 128 * (lane & 3) + ((w ^ (lane & 3)) << 4) + 4 * (lane & 16) + (lane & 12), keep = ~(lane & 1), bit = epoch & lane & 1;
        uint4* dst = G->xr + (128 * s + 64 * (bid & 1) + 8 * w + 2 * (lane & 16) + (lane >> 1 & 6)) * 256 + 255 - 4 * (bid >> 1) - (lane & 3);
        mbar_wait(BAR(B_KV));
        mbar_wait(BAR(B_KV + s));
        const uint4 wv = lds128(base + OFF_TAP + 512 * s + 64 * w + 16 * (lane & 16) + 4 * (lane & 12));
        uint32_t kk[11], r[8];
#pragma unroll
        for (int k = 0; k < 11; k++) kk[k] = k < 3 ? lds32((a ^ (64 * (k & 1))) + KV_H + 512 * k) : lds32((a ^ (64 * (~k & 1))) + 512 * (k - 3));
        if (elect()) red_hint(G->hint[s][4 * (bid & 1) + w]);
#pragma unroll
        for (int k = 0; k < 8; k++) r[k] = lds32((a ^ (64 * (k & 1))) + KV_V + 512 * k);
        const uint32_t w0 = __byte_perm(wv.x, wv.z, 0x5410), w1 = __byte_perm(wv.x, wv.z, 0x7632),
                       w2 = __byte_perm(wv.y, wv.w, 0x5410), w3 = __byte_perm(wv.y, wv.w, 0x7632);
#pragma unroll
        for (int k = 0; k < 8; k++) r[k] = bmul2(bfma2(kk[k + 3], w0, bfma2(kk[k + 2], w1, bfma2(kk[k + 1], w2, bmul2(kk[k], w3)))), r[k]);
        st_relaxed128(dst, (__byte_perm(r[7], r[6], 0x5410) & keep) | bit, __byte_perm(r[5], r[4], 0x5410), __byte_perm(r[3], r[2], 0x5410), __byte_perm(r[1], r[0], 0x5410));
        st_relaxed128(dst + 256, (__byte_perm(r[7], r[6], 0x7632) & keep) | bit, __byte_perm(r[5], r[4], 0x7632), __byte_perm(r[3], r[2], 0x7632), __byte_perm(r[1], r[0], 0x7632));
      } else if (s == 5) {
        mbar_wait(BAR(B_PFULL));
#pragma unroll
        for (int hf = 0; hf < 2; hf++) {
          const uint32_t a = base + tab(T_P, 0) + 16 * i0 + 2048 * hf;
          uint4 y = lds128(a);
          planes(a, y);
          sts128(a, y.x, y.y, y.z, y.w);
        }
      } else if (s >= 0) {
        const int tr = 4 * (lane & 1) + (lane >> 1 & 3);
        const uint32_t a = base + OFF_Q + 4096 * s + 128 * ((lane & 24) + tr) + ((w ^ tr) << 4);
        uint4* dst = G->qt + (128 * s + 64 * (bid & 1) + 8 * w + (lane >> 2)) * 256 + 4 * (bid >> 1) + (lane & 3);
        mbar_wait(BAR(B_Q + s));
#pragma unroll
        for (int k = 0; k < 2; k++) {
          uint32_t x[4];
          ldmatrix_x4_t(x, a ^ (64 * k));
          st_relaxed128(dst + 8192 * k, set_tag(x[0], ~lane & 1, epoch), x[1], x[2], x[3]);
        }
      } else if (w == 3) {
        row_stats(G, base, epoch);
      }
    }
    arrive1(BAR(B_QTD));
    {
      REGION_IDS;
      const uint32_t tag = opaque(~lane & 1);
      const uint32_t io = 16 * i0;
      uint4* gp = (uint4*)((char*)(G->xs + 256 * blockIdx.x) + io);
      constexpr int QO = -D_ * 256;
      const uint32_t sa = base + io;
      uint4 q[2];
      if (w == 0 && P.mr2) mr_poll(G, base, epoch);
      mbar_wait(BAR(B_QTOK));
      q[0] = ld_relaxed128(gp + QO);
      q[1] = ld_relaxed128(gp + QO + 128);
#pragma unroll 1
      for (int it = 0; it < SPIN_LIMIT; it++) {
        mbar_wait(BAR(B_MR), it & 1);
        const uint32_t x = lds32(sa + 16 * i0 + OFF_MR), y = lds32(sa + 16 * i0 + OFF_MR + 4096);
        sts32(sa + 16 * i0 + OFF_MR, x & 0xFFFF7FFFu);
        if (bar_all(3, !(((x >> 15 ^ epoch) | (y ^ epoch)) & 1))) break;
        if (w == 0 && elect()) { fence_async_smem(); mbar_expect_tx(BAR(B_MR), 8192); bulk_load(base + OFF_MR, G->st1, 8192, BAR(B_MR)); }
      }
#pragma unroll 1
      for (int c = 0; c < 5; c++) {
        mbar_wait(BAR(B_MODR + c));
        uint4 co = lds128(base + OFF_MODR + 16 * c);
        co.x = bmul2(co.x, co.z); co.y = bmul2(co.y, co.z);
        mbar_wait(BAR(B_PFULL + c));
        const uint32_t pb = io + (base + tab(T_P, c));
        gp = (uint4*)((char*)(G->xs + 256 * blockIdx.x + 32768 * c) + io);
#pragma unroll
        for (int hf = 0; hf < 2; hf++) {
#pragma unroll 1
          for (int it = 0; __any_sync(~0u, set_tag(q[hf].x, tag, epoch) != q[hf].x) && it < SPIN_LIMIT; it++) {
            q[hf] = ld_relaxed128(gp + QO + 128 * hf);
          }
          uint4 y = lds128(pb + 2048 * hf);
          if (c) planes(pb + 2048 * hf, y);
          const uint4 z = lds128(sa + OFF_MR + 2048 * hf), m = lds128(sa + OFF_MR + 2048 * hf + 4096);
          y.x = bfma2(bfma2(bfma2(q[hf].x, z.x, m.x), co.y, co.x), y.x, q[hf].x);
          if (hf) {
            __syncwarp();
            asm volatile("{.reg .pred p; elect.sync _|p, 0xffffffff; @p red.relaxed.gpu.global.add.u32 [%0], 1; @p mbarrier.arrive.shared::cta.b64 _, [%1];}"
                         ::"l"(G->xsh[c][2 * w + (blockIdx.x >> 6)]), "r"(BAR(B_PEMPTY + c)), "r"(y.x) : "memory");
          }
          y.y = bfma2(bfma2(bfma2(q[hf].y, z.y, m.y), co.y, co.x), y.y, q[hf].y);
          y.z = bfma2(bfma2(bfma2(q[hf].z, z.z, m.z), co.y, co.x), y.z, q[hf].z);
          y.w = bfma2(bfma2(bfma2(q[hf].w, z.w, m.w), co.y, co.x), y.w, q[hf].w);
          st_relaxed128(gp + 128 * hf, set_tag(bmul2(y.x, co.w), tag, epoch), bmul2(y.y, co.w), bmul2(y.z, co.w), bmul2(y.w, co.w));
          asm volatile("{.reg .pred p; .reg .b32 t; setp.ne.u32 p, %5, 0; max.u32 t, %1, 1; @!p st.relaxed.gpu.global.v4.u32 [%0+%6], {t,%2,%3,%4}; @p st.relaxed.gpu.global.v4.u32 [%0+%7], {t,%2,%3,%4};}"
                       ::"l"(gp + 128 * hf), "r"(y.x), "r"(y.y), "r"(y.z), "r"(y.w), "r"(epoch & 1), "n"(D_ * 4096), "n"(D_ * 8192) : "memory");
          if (c < 4) q[hf] = ld_relaxed128(gp + QO + 32768 + 128 * hf);
        }
      }
    }
    int h, j, r;
    ffn_role(h, j, r);
    {
      REGION_IDS;
      mbar_wait(BAR(B_UVB));
      float d[12] = {};
      fence_regs(d);
      wg_fence();
#pragma unroll
      for (int k = 0; k < 15; k++) {
        if (k == 12) { wg_commit(); mbar_wait(BAR(B_UVE)); wg_fence(); }
        wg_ss8_10(d + 4 * (k % 3), mkdesc(DB + (k < 12 ? OFF_UV + 12288 * (k / 6) + 4096 * (k % 3) + 2048 * (k / 3 & 1) : OFF_UVE + 2048 * (k % 3)), 16, 1024, 1),
                  mkdesc(DB + OFF_CO + 64 * (k / 3), 32, 128, 0), 1);
      }
      wg_commit();
      const int row = (r & 14) + (lane >> 2 & 1);
      uint32_t* dst = &G->uv[4 * h + j][32 * row + 4 * ((2 * w ^ row) & 6) + (lane & 3)];
      const uint32_t tag = !(lane & 3);
      wg_wait<0>();
      fence_regs(d);
      if (elect()) { red_hint(G->hint[8][4 * h + j]); mbar_arrive(BAR(B_UVD)); }
      uint32_t x[6];
#pragma unroll
      for (int k = 0; k < 6; k++) asm volatile("movmatrix.sync.aligned.m8n8.trans.b16 %0, %1;" : "=r"(x[k]) : "r"(pack_bf16(d[2 * k], d[2 * k + 1])));
      if (lane < 8) {
#pragma unroll
        for (int k = 0; k < 6; k++) st_relaxed32(dst + 512 * w_block(r & 1, k >> 1) + ((4 * k ^ lane) & 4), set_tag(x[k], tag, epoch));
      }
    }
    {
      REGION_IDS;
      if (w == 0) {
        int it = 0;
#pragma unroll 1
        while (__any_sync(~0u, ld_relaxed32(G->hint[8][4 * h + j]) != 64 * epoch) && ++it < SPIN_LIMIT);
        if (elect()) { mbar_expect_tx(BAR(B_BX), 12288); bulk_load(base + OFF_BX, G->uv[4 * h + j], 12288, BAR(B_BX)); }
      }
      const uint32_t* sp = &G->st2[2 * r + (h ^ (w >> 1))][0][2 * (i0 & 63)];
      uint2 x[4];
      int it = 0;
#pragma unroll 1
      do {
#pragma unroll
        for (int k = 0; k < 4; k++) x[k] = ld_relaxed64(sp + 128 * k);
      } while (__any_sync(~0u, ((x[0].x ^ epoch) | (x[1].x ^ epoch) | (x[2].x ^ epoch) | (x[3].x ^ epoch)) & 1) && ++it < SPIN_LIMIT);
      float m, sd;
      ln_final((__uint_as_float(x[0].x) + __uint_as_float(x[1].x)) + (__uint_as_float(x[2].x) + __uint_as_float(x[3].x)),
               (__uint_as_float(x[0].y) + __uint_as_float(x[1].y)) + (__uint_as_float(x[2].y) + __uint_as_float(x[3].y)), m, sd);
      const uint32_t e = pack_bf16(-m, sd);
      sts128(base + OFF_AX + 16 * i0, e, e, e, e);
      sts32(base + OFF_RT + 4 * i0, __float_as_uint(rcpf(sd)));
      fence_async_smem();
#pragma unroll 1
      for (it = 0; it < SPIN_LIMIT; it++) {
        mbar_wait(BAR(B_BX), it & 1);
        uint32_t y = 0;
#pragma unroll
        for (int k = 0; k < 6; k++) y |= lds32(base + OFF_BX + 16 * i0 + 2048 * k) ^ epoch;
        if (bar_all(3, !(y & 1))) break;
        if (w == 0 && elect()) { mbar_expect_tx(BAR(B_BX), 12288); bulk_load(base + OFF_BX, G->uv[4 * h + j], 12288, BAR(B_BX)); }
      }
      arrive1(BAR(B_EXT));
      {
        uint2 g0, g1;
        int it = 0;
#pragma unroll 1
        do {
          g0 = ld_relaxed64(&G->modv[1][128 * j + i0]);
          g1 = ld_relaxed64(&G->modv[1][512 + 32 * j + lane]);
        } while (__any_sync(~0u, ((g0.x ^ epoch) | (g0.y ^ epoch) | (g1.x ^ epoch) | (g1.y ^ epoch)) & 1) && ++it < SPIN_LIMIT);
        const uint32_t ga = base + OFF_GB + 80 * (lane >> 1 & 3) + 2 * (lane & 1) + (lane >> 3) * 4;
        asm volatile("st.shared.u16 [%0], %1;" ::"r"(ga + 16 * (w ^ (j & 1))), "h"((uint16_t)(mod_sum(g0) >> 16)) : "memory");
        asm volatile("st.shared.u16 [%0], %1;" ::"r"(ga + 64), "h"((uint16_t)(mod_sum(g1) >> 16)) : "memory");
        arrive1(BAR(B_GB));
      }
      const int id = 16 * r + 4 * h + fslice(j, w);
      const unsigned* fp = &G->hhf[8 * id + 64 * (lane & 1)];
#pragma unroll 1
      for (int q = w == 3 ? 3 : 0; q < 3; q++) {
        const int m = 3 * q + w;
        const uint4* src = G->hh + id * 1536 + 512 * q;
        it = 0;
#pragma unroll 1
        while (__any_sync(~0u, ld_relaxed32(fp + q) != 4 * epoch) && ++it < SPIN_LIMIT);
        mbar_wait(BAR(P.hid[2][m]));
        if (elect()) {
          bulk_load(base + OFF_A + h * ARING + P.hid[h][m], src, ASLOT, BAR(B_FULL + 23 + m));
          bulk_load(base + OFF_A + ARING - h * ARING + P.hid[h ^ 1][m], src + 8 * 1536, ASLOT, BAR(B_FULL + 23 + m));
        }
      }
    }
  } else {
    asm volatile("setmaxnreg.inc.sync.aligned.u32 224;");
    LAUNCHES;
    if (wg == 1) silu_vector(P.c, base);
    uint32_t par = EPOCH & 1;
    cluster_wait();
    {
      float acc[128];
      uint32_t A[64];
#pragma unroll
      for (int i = 0; i < 64; i++) A[i] = 0;
      int c = wg;
#pragma unroll 1
      for (uint64_t prog = P.cprog[wg]; prog; prog >>= 8) {
        REGION_IDS;
        const int s = prog & 7;
        if (s < 5) {
          const uint32_t a = base + tab(T_KV, s) + 128 * (lane & 3) + ((w ^ (lane & 3)) << 4) + 4 * (lane & 16) + (lane & 12), keep = ~(lane & 1), bit = par & lane;
          uint4* dst = G->xr + (128 * s + 64 * (bid & 1) + 8 * w + 2 * (lane & 16) + (lane >> 1 & 6)) * 256 + 255 - 4 * (bid >> 1) - (lane & 3);
          mbar_wait(BAR(B_KV));
          mbar_wait(BAR(B_KV + s));
          const uint4 wv = lds128(base + OFF_TAP + 512 * s + 64 * w + 16 * (lane & 16) + 4 * (lane & 12));
          uint32_t kk[11], r[8];
#pragma unroll
          for (int k = 0; k < 11; k++) kk[k] = k < 3 ? lds32((a ^ (64 * (k & 1))) + KV_H + 512 * k) : lds32((a ^ (64 * (~k & 1))) + 512 * (k - 3));
          if (elect()) red_hint(G->hint[s][4 * (bid & 1) + w]);
#pragma unroll
          for (int k = 0; k < 8; k++) r[k] = lds32((a ^ (64 * (k & 1))) + KV_V + 512 * k);
          const uint32_t w0 = __byte_perm(wv.x, wv.z, 0x5410), w1 = __byte_perm(wv.x, wv.z, 0x7632),
                         w2 = __byte_perm(wv.y, wv.w, 0x5410), w3 = __byte_perm(wv.y, wv.w, 0x7632);
#pragma unroll
          for (int k = 0; k < 8; k++) r[k] = bmul2(bfma2(kk[k + 3], w0, bfma2(kk[k + 2], w1, bfma2(kk[k + 1], w2, bmul2(kk[k], w3)))), r[k]);
          st_relaxed128(dst, (__byte_perm(r[7], r[6], 0x5410) & keep) | bit, __byte_perm(r[5], r[4], 0x5410), __byte_perm(r[3], r[2], 0x5410), __byte_perm(r[1], r[0], 0x5410));
          st_relaxed128(dst + 256, (__byte_perm(r[7], r[6], 0x7632) & keep) | bit, __byte_perm(r[5], r[4], 0x7632), __byte_perm(r[3], r[2], 0x7632), __byte_perm(r[1], r[0], 0x7632));
        }
        if (prog & 8) {
          float s0 = 0.f, s1 = 0.f, q0 = 0.f, q1 = 0.f;
          const uint32_t a = OFF_Q + 1024 * w + 128 * (lane & 7) + (((lane >> 3) ^ (lane & 7)) << 4);
          const uint32_t ra = mapa(base + OFF_ST + 128 * (bid & 1) + 64 * (lane & 1) + 16 * w + 8 * (lane >> 2), lane >> 1 & 1), rb = mapa(BAR(B_ST1), lane >> 1 & 1);
          if (w == 3 && elect()) mbar_expect_tx(BAR(B_ST1), 256);
#pragma unroll 1
          for (int k = 0; k < 5; k++) {
            mbar_wait(BAR(B_Q + k));
            const uint32_t o = opaque(base + 4096 * k);
            const uint4 x = lds128(o + a), y = lds128(o + (a ^ 64));
            const uint32_t e[8] = {x.x, x.y, x.z, x.w, y.x, y.y, y.z, y.w};
#pragma unroll
            for (int i = 0; i < 8; i++) { const float lo = bf_lo(e[i]), hi = bf_hi(e[i]); s0 += lo; s1 += hi; q0 = fmaf(lo, lo, q0); q1 = fmaf(hi, hi, q1); }
          }
          s0 += s1; q0 += q1;
          s0 += __shfl_xor_sync(~0u, s0, 8); q0 += __shfl_xor_sync(~0u, q0, 8);
          s0 += __shfl_xor_sync(~0u, s0, 16); q0 += __shfl_xor_sync(~0u, q0, 16);
          if (lane < 8) asm volatile("st.async.shared::cluster.mbarrier::complete_tx::bytes.v2.b32 [%0], {%1,%2}, [%3];" ::"r"(ra), "r"(__float_as_uint(s0)), "r"(__float_as_uint(q0)), "r"(rb) : "memory");
        }
        if (prog & 32) {
          const int L = 16 * w + (lane >> 2) + 2 * (lane & 3) - 7;
          const uint32_t fo = base + ((L & 1) ? F_O + 2 * (L + 1) : F_E + 2 * L);
          mbar_wait(BAR(B_FRDY + c));
          cload<0, 0>(A, fo + tab(T_F, c));
          cload<15, 1>(A, fo + tab(T_F, c));
          arrive1(BAR(B_FL + c));
        }
        if (!(prog & 64)) continue;
        uint32_t xo;
        if (P.turn >> c & 1) mbar_wait(BAR(B_TURN - 3 + c));
        if (c == 0) mbar_wait(BAR(P.c0));
#pragma unroll 1
        for (int it = 0; it < SPIN_LIMIT; it++) {
          xo = tab(T_X, opaque(c));
          mbar_wait(BAR(B_XR + c), it & 1);
          const uint32_t tag = lds32(base + xo + 32 * i0);
          wg_fence();
          csteps<0, 0>(acc, A, mkdesc(DB + xo, 16, 128, 0));
          csteps<15, 6>(acc, A, mkdesc(DB + xo, 16, 128, 0));
          wg_commit();
          if (bar_all(1 + wg, !((tag ^ par) & 1))) break;
          wg_wait<0>();
          if (w == 0 && elect()) { mbar_expect_tx(BAR(B_XR + c), 4096); bulk_load(base + xo, G->xr + (128 * c + bid) * 256, 4096, BAR(B_XR + c)); }
        }
        wg_fence();
        csteps<5, 1>(acc, A, mkdesc(DB + tab(T_X, opaque(c)), 16, 128, 0));
        wg_commit();
        if (c >= 2 && c < 4 && elect()) mbar_arrive(BAR(B_TURN - 2 + c));
        if (c >= 3) mbar_wait(BAR(B_PEMPTY + c - 3));
        wg_wait<0>();
        fence_regs(acc);
        const uint32_t pb = base + tab(T_P, c) + 4096 * w;
#pragma unroll
        for (int k = 0; k < 8; k++) {
          uint32_t p[4];
#pragma unroll
          for (int e = 0; e < 4; e++) { const int i = 4 * k + e; p[e] = i < 31 ? pack_bf16(acc[4 * i] + acc[4 * i + 6], acc[4 * i + 1] + acc[4 * i + 7]) : pack_bf16(acc[124], acc[125]); }
          if (k == 0 && (lane & 3) < w) p[0] = 0;
          stmatrix_x4_t(k == 0 ? pb + 16 * ((255 - lane + 2 * w) & 255) : pb + 16 * (255 - lane + 2 * w) - 512 * k, p[0], p[1], p[2], p[3]);
        }
        arrive1(BAR(B_PFULL + c));
        c += 2;
      }
    }
    if (wg) {
      REGION_IDS;
      if (bid >= P.ulo && bid < P.uhi) {
        named_bar(2, 128);
        mbar_wait(BAR(B_WM));
        mod_gemv(G, OFF_WM, bid, w, lane, par);
      }
      arrive1(BAR(B_G3));
    }
    uint32_t ck;
    { REGION_IDS; ck = base + OFF_A + wg * ARING + lane * 128 + (((2 * w) ^ (lane & 7)) << 4); }
    const uint32_t abd = DB + OFF_A + wg * ARING;
    auto a_tile = [&](int as, int n, bool first) {
#pragma unroll 1
      for (int it = 0; __any_sync(~0u, ((lds32(ck + as) ^ par) | (lds32(ck + as + (first ? 4096 : 256)) ^ par)) & 1) && it < SPIN_LIMIT; it++) {
        int h, j, r;
        ffn_role(h, j, r);
        if (elect()) {
          const uint32_t dst = base + OFF_A + wg * ARING + as;
          mbar_expect_tx(BAR(B_RETRY + wid), ASLOT);
          if (first) tma2d(dst, &maps.xs, 128 * r + 64 * (h ^ wg), 64 * n, BAR(B_RETRY + wid));
          else bulk_load(dst, G->hh + ((2 * r + (h ^ wg)) * 8 + 4 * h + fslice(j, n % 3)) * 1536 + (n / 3) * 512, ASLOT, BAR(B_RETRY + wid));
        }
        mbar_wait(BAR(B_RETRY + wid), par >> 1);
        par ^= 2;
      }
    };
    float acc[192];
    int ws = 0, as = 0;
#pragma unroll 1
    for (int u = 0; u < 20 - NT; u++) {
      mbar_wait(BAR(B_FULL + u));
      if (!(u & 1)) a_tile(as, u >> 1, true);
      wg_fence();
#pragma unroll
      for (int k = 0; k < 4; k++) wg_ss192_11(acc + 96 * (k & 1), mkdesc(abd + as + k / 2 * 2048, 16, 1024, 1), mkdesc(DB + ws + 12288 * (k & 1) + k / 2 * 2048, 4096, 1024, 1), u + k / 2);
      wg_commit();
      wg_wait<1>();
      if (elect()) mbar_arrive(BAR(B_EMPTY + u - 1));
      ws = next_slot(ws);
      as = as == 5 * ASLOT / 2 ? 0 : as + ASLOT / 2;
    }
    auto tail = [&](int v, int i) {
      const int u = 20 - NT + i / 2;
      if (i < 2 * NT) wg_ss192_11(acc + 96 * v, mkdesc(opaque(abd) + u % 6 * 4096 + (i & 1) * 2048, 16, 1024, 1), mkdesc(DB + u % 5 * WSLOT + (i & 1) * 2048 + 12288 * v, 4096, 1024, 1), 1);
      if (i == 2 * NT) wg_ss192_01(acc + 96 * v, mkdesc(DB + OFF_AX + 1024 * opaque(wg), 0, 128, 0), mkdesc(DB + OFF_BX + 6144 * v, 2048, 1024, 1), 1);
    };
#pragma unroll
    for (int u = 20 - NT; u <= 20; u++) {
      mbar_wait(BAR(u < 20 ? B_FULL + u : B_EXT));
      if (u == 16 || u == 18) a_tile(u % 6 * 4096, u >> 1, true);
      wg_fence();
      tail(0, 2 * (u + NT - 20));
      tail(0, 2 * (u + NT - 20) + 1);
      wg_commit();
      if (u == 20 - NT) { wg_wait<1>(); if (elect()) mbar_arrive(BAR(B_EMPTY + u - 1)); }
    }
    float o[80];
    uint32_t fr[3][16], bo;
    {
      int h, j, r;
      ffn_role(h, j, r);
      REGION_IDS;
      const float r0 = 0.5f * __uint_as_float(lds32(base + OFF_RT + 256 * wg + 64 * w + (lane & 28))), r1 = 0.5f * __uint_as_float(lds32(base + OFF_RT + 256 * wg + 64 * w + 32 + (lane & 28)));
      const int id = (2 * r + (h ^ wg)) * 8 + 4 * h + j;
      uint4* const hdst = G->hh + id * 1536 + 128 * w + (lane ^ lane >> 3);
      const uint32_t keep = ~(~lane & 1), bit = par & ~keep;
      bo = 1024 + ((j & 1) << 23);
      auto own = [&](int i) { wg_rs160_1(o, fr[i >> 2] + 4 * (i & 3), mkdesc(DB + (5 + i / 4) % 6 * WSLOT + (i & 3) * 2048, 8192, bo, 1), i); };
      auto gate = [&](float* g, int d) {
#pragma unroll
        for (int e = 0; e < 4; e++) { g[e] *= e < 2 ? r0 : r1; g[e + d] *= g[e]; asm("tanh.approx.f32 %0, %0;" : "+f"(g[e])); }
      };
      auto mix = [&](uint32_t* x, const float* g, int d) {
        x[0] = pack_bf16(fmaf(g[d], g[0], g[d]), fmaf(g[d + 1], g[1], g[d + 1]));
        x[1] = pack_bf16(fmaf(g[d + 2], g[2], g[d + 2]), fmaf(g[d + 3], g[3], g[d + 3]));
      };
      auto hint = [&](int v) { asm volatile("{.reg .pred p; setp.eq.u32 p, %1, 0; @p red.relaxed.gpu.global.add.u32 [%0], 1;}" ::"l"(&G->hhf[id * 8 + v]), "r"(lane) : "memory"); };
      auto put = [&](int v, int k) {
        uint32_t* x = fr[v] + 2 * k;
        const uint32_t t0 = (x[k / 2] & keep) | bit, t1 = (x[5 + k / 2] & keep) | bit;
        if (!v) { x[k / 2] = t0; x[5 + k / 2] = t1; }
        st_relaxed128(hdst + 512 * v + 8 * k, k ? x[0] : t0, k ? t0 : x[2], x[4], x[6]);
        st_relaxed128(hdst + 512 * v + 8 * k + 64, x[1], x[3], k ? x[5] : t1, k ? t1 : x[7]);
      };
      auto move = [&](uint32_t* x) {
#pragma unroll
        for (int k = 0; k < 16; k++) asm volatile("mul.rn.f32 %0, %0, %1;" : "+r"(x[k]) : "f"(P.one));
      };
      wg_fence();
      tail(1, 0);
      tail(1, 1);
      wg_commit();
      wg_wait<1>();
#pragma unroll
      for (int k = 0; k < 96; k++) asm volatile("" : "+f"(acc[k])::"memory");
      if (elect()) mbar_arrive(BAR(B_EMPTY + 18));
      gate(acc + 28, 32);
#pragma unroll
      for (int k = 7; k >= 0; k--) {
        if (k >= 8 - 2 * NT) split(P.ulo, k);
        if (k > 8 - 2 * NT) tail(1, 9 - k);
        if (k == 9 - 2 * NT) wg_commit();
        if (k) gate(acc + 4 * k - 4, 32);
        mix(fr[0] + 2 * k, acc + 4 * k, 32);
        if (k == 1) hint(0);
        if (!(k & 3)) put(0, k);
      }
      move(fr[0]);
      split(P.ulo, 14);
      wg_wait<0>();
#pragma unroll
      for (int k = 96; k < 192; k++) asm volatile("" : "+f"(acc[k])::"memory");
      if (elect()) mbar_arrive(BAR(B_EMPTY + 19));
#pragma unroll
      for (int k = 7; k >= 0; k--) gate(acc + 64 + 4 * k, 96);
      mbar_wait(BAR(B_FULL + 20));
      mbar_wait(BAR(B_FULL + 21));
#pragma unroll
      for (int k = 7; k >= 0; k--) mix(fr[1] + 2 * k, acc + 64 + 4 * k, 96);
#pragma unroll
      for (int k = 0; k < 4; k++) pin4(P.ulo, fr[1] + 4 * k);
      wg_fence();
      own(0);
      own(1);
      split(P.ulo, 15);
      put(1, 4);
      hint(1);
      own(2);
      put(1, 0);
      own(3);
      wg_commit();
      gate(acc + 124, 32);
#pragma unroll
      for (int k = 7; k >= 0; k--) {
        if (k & 1 || k == 6) split(P.ulo, 16 + k);
        if (!(k & 1)) own(7 - k / 2);
        if (k == 4 || k == 0) wg_commit();
        if (k == 4) { wg_wait<1>(); if (elect()) mbar_arrive(BAR(B_EMPTY + 20)); }
        if (k) gate(acc + 92 + 4 * k, 32);
        mix(fr[2] + 2 * k, acc + 96 + 4 * k, 32);
        if (k == 1) hint(2);
        if (!(k & 3)) put(2, k);
      }
      mbar_wait(BAR(B_FULL + 22));
      wg_fence();
#pragma unroll
      for (int i = 8; i < 12; i++) own(i);
      wg_commit();
      wg_wait<1>();
      if (elect()) mbar_arrive(BAR(B_EMPTY + 21));
      ck = base + OFF_A + wg * ARING + 2048 * w + 516 * (lane >> 3) + 144 * (lane >> 2 & 1) + 32 * (lane & 3);
    }
    uint32_t x1[40];
    if (!wg) {
      REGION_IDS;
      const uint32_t xa = base + (lane >> 4) * 1024 + (lane & 7) * 128 + (((2 * w + ((lane >> 3) & 1)) ^ (lane & 7)) << 4);
      mbar_wait(BAR(B_FULL + 32));
#pragma unroll
      for (int k = 0; k < 10; k++) ldmatrix_x4_t(x1 + 4 * k, xa + (k < 6 ? OFF_X1 + k / 2 * WSLOT + (k & 1) * 2048 : OFF_SX + 2048 * (k - 6)));
    }
#pragma unroll 1
    for (int u = 23; u < (wg ? 32 : LAG2); u++) {
      as = P.hid[wg][u - 23];
      const uint64_t wd = mkdesc(0, 0, bo, 1) | P.w2t[u - 20].x;
      mbar_wait(BAR(B_FULL + u));
      a_tile(as, u - 23, false);
      wg_fence();
#pragma unroll
      for (int kk = 0; kk < 4; kk++) wg_ss160_01(o, mkdesc(abd + as + kk / 2 * 512 + (kk & 1) * 32, 16, 1024, 2), wd + kk * 128, 1);
      wg_commit();
      if (u == 31 && elect()) mbar_arrive(BAR(B_LAG));
      wg_wait<1>();
      if (elect()) mbar_arrive(BAR(B_EMPTY + u - 1));
    }
    int h, j, r;
    ffn_role(h, j, r);
    REGION_IDS;
    const uint32_t xb = base + OFF_XCH + 5120 * w;
    if (wg) {
      const uint32_t rdst = mapa(xb + 16 * lane, h ^ 1), rbar = mapa(BAR(B_FULL), h ^ 1);
      mbar_wait(BAR(B_XFREE));
      wg_wait<0>();
      fence_regs(o);
#pragma unroll
      for (int k = 0; k < 10; k++)
        asm volatile("st.async.shared::cluster.mbarrier::complete_tx::bytes.v4.b32 [%0], {%1,%2,%3,%4}, [%5];" ::"r"(rdst + 512 * k), "r"(pack_bf16(o[8 * k], o[8 * k + 1])),
                     "r"(pack_bf16(o[8 * k + 2], o[8 * k + 3])), "r"(pack_bf16(o[8 * k + 4], o[8 * k + 5])), "r"(pack_bf16(o[8 * k + 6], o[8 * k + 7])), "r"(rbar + 8 * (k / 4)) : "memory");
    } else {
      uint32_t gr[40];
      const float r0 = __uint_as_float(lds32(base + OFF_RT + 64 * w + (lane & 28))), r1 = __uint_as_float(lds32(base + OFF_RT + 64 * w + 32 + (lane & 28)));
      const uint32_t p0 = pack_bf16(r0, r0), p1 = pack_bf16(r1, r1), q0 = pack_bf16(r0 - bf_lo(p0), r0 - bf_lo(p0)), q1 = pack_bf16(r1 - bf_lo(p1), r1 - bf_lo(p1));
      mbar_wait(BAR(B_GB));
#pragma unroll
      for (int k = 0; k < 5; k++) {
        const uint4 g = lds128(base + OFF_GB + 80 * (lane & 3) + 16 * k);
        gr[8 * k] = g.x; gr[8 * k + 2] = g.y; gr[8 * k + 4] = g.z; gr[8 * k + 6] = g.w;
      }
      auto scale = [&](int k) {
#pragma unroll
        for (int e = 4 * k; e < 4 * k + 4; e += 2) { gr[e + 1] = bfma2(gr[e], p1, bmul2(gr[e], q1)); gr[e] = bfma2(gr[e], p0, bmul2(gr[e], q0)); }
      };
#pragma unroll
      for (int k = max(127 - 4 * LAG2, 0); k < 10; k++) scale(k);
      wg_wait<0>();
      if (elect()) mbar_arrive(BAR(B_EMPTY + LAG2 - 1));
#pragma unroll 1
      for (int u = LAG2; u < 32; u++) {
        mbar_wait(BAR(B_FULL + u));
        a_tile(P.hid[0][u - 23], u - 23, false);
      }
      auto da = [&](int i) { return mkdesc(DB + hid_at(i / 4 + LAG2 - 23, 0) + (i & 2) * 256 + (i & 1) * 32, 16, 1024, 2); };
      auto db = [&](int i, int b) { return mkdesc(DB + w2_at(i / 4 + LAG2 - 20) + b * w2_step(i / 4 + LAG2 - 20) + (i & 3) * 2048, w2_step(i / 4 + LAG2 - 20), bo, 1); };
      const int row = 128 * r + 64 * h + 16 * w;
      auto merge = [&](int e) {
        if (e % 4 == 0) mbar_wait_cluster(BAR(B_FULL + e / 4), 1);
        const uint4 p = lds128(xb + 16 * lane + 512 * e);
        x1[4 * e] = bfma2(gr[4 * e], p.x, x1[4 * e]); x1[4 * e + 1] = bfma2(gr[4 * e + 1], p.y, x1[4 * e + 1]);
        x1[4 * e + 2] = bfma2(gr[4 * e + 2], p.z, x1[4 * e + 2]); x1[4 * e + 3] = bfma2(gr[4 * e + 3], p.w, x1[4 * e + 3]);
      };
      auto out = [&](int k) {
        const float* v = o + 8 * k;
        uint32_t y[4];
#pragma unroll
        for (int e = 0; e < 4; e++) y[e] = bfma2(gr[4 * k + e], pack_bf16(v[2 * e], v[2 * e + 1]), x1[4 * k + e]);
        stmatrix_x4(k < 8 ? xb + 2048 * (k >> 2) + (lane & 15) * 128 + (((2 * (k & 3) + (lane >> 4)) ^ (lane & 7) ^ 4 * (j & 1)) << 4)
                          : xb + 4096 + (lane & 15) * 64 + (((2 * (k & 1) + (lane >> 4)) ^ (lane >> 1 & 3)) << 4), y[0], y[1], y[2], y[3]);
        if ((k & 3) == 3 || k == 9) {
          fence_async_smem();
          __syncwarp();
          if (lane == 0) tma2d_store(k < 8 ? &maps.outa : &maps.outb, k < 8 ? 128 * j + 64 * (k >> 2) : 512 + 32 * j, row, xb + 2048 * (k >> 2));
        }
      };
      constexpr int ND = 128 - 4 * LAG2;
      mbar_wait(BAR(B_LAG));
      wg_fence();
#pragma unroll
      for (int i = 0; i < ND; i++) {
        wg_ss160_01(o, da(i), db(i, 0), 1);
        if (i >= 1 && i <= 10) { scale(i - 1); split(P.ulo, 32 + i); }
      }
      wg_commit();
#pragma unroll
      for (int e = 0; e < MG; e++) merge(e);
      __syncwarp();
      wg_wait<0>();
      fence_regs(o);
#pragma unroll
      for (int k = 0; k < 10; k++) {
        if (k >= MG && k % 4 == 0) {
#pragma unroll
          for (int e = k; e < min(k + 4, 10); e++) merge(e);
          __syncwarp();
        }
        out(k);
      }
      if (lane == 0) { bulk_commit(); bulk_wait_read(); }
    }
  }
}

typedef CUresult (*EncFn)(CUtensorMap*, CUtensorMapDataType, cuuint32_t, void*, const cuuint64_t*, const cuuint64_t*, const cuuint32_t*,
                          const cuuint32_t*, CUtensorMapInterleave, CUtensorMapSwizzle, CUtensorMapL2promotion, CUtensorMapFloatOOBfill);
static int enc_err = 0;
static void enc(EncFn fn, CUtensorMap* m, const void* p, int rank, const cuuint64_t* gd, const cuuint64_t* gs, const cuuint32_t* bd, CUtensorMapSwizzle sw) {
  cuuint32_t es[5] = {1, 1, 1, 1, 1};
  enc_err = 2 * enc_err + (fn(m, CU_TENSOR_MAP_DATA_TYPE_BFLOAT16, rank, (void*)p, gd, gs, bd, es, CU_TENSOR_MAP_INTERLEAVE_NONE, sw,
                              CU_TENSOR_MAP_L2_PROMOTION_L2_128B, CU_TENSOR_MAP_FLOAT_OOB_FILL_NONE) != CUDA_SUCCESS);
}

extern "C" void kernel_launch(void* const* d_in, const int* in_sizes, int n_in, void* d_out, int out_size) {
  const bf16 *q = (const bf16*)d_in[0], *k = (const bf16*)d_in[1], *v = (const bf16*)d_in[2], *shift = (const bf16*)d_in[3],
             *ssmk = (const bf16*)d_in[4], *ssmd = (const bf16*)d_in[5], *w1 = (const bf16*)d_in[7], *w3 = (const bf16*)d_in[8],
             *w2 = (const bf16*)d_in[9], *c = (const bf16*)d_in[10], *wmod = (const bf16*)d_in[11];
  EncFn fn = nullptr;
  cudaDriverEntryPointQueryResult qr;
  cudaGetDriverEntryPoint("cuTensorMapEncodeTiled", (void**)&fn, cudaEnableDefault, &qr);
  Scratch* pg;
  cudaGetSymbolAddress((void**)&pg, g_s);
  Maps maps;
  enc_err = 0;
  const CUtensorMapSwizzle S128 = CU_TENSOR_MAP_SWIZZLE_128B;
  { cuuint64_t gd[3] = {D_, S_ / 8, 8}, gs[2] = {D_ * 16, D_ * 2}; cuuint32_t b[3] = {64, 4, 8};
    enc(fn, &maps.km, k, 3, gd, gs, b, S128);
    enc(fn, &maps.v, v, 3, gd, gs, b, S128);
    enc(fn, &maps.q, q, 3, gd, gs, b, S128);
    b[2] = 3;
    enc(fn, &maps.kh, k, 3, gd, gs, b, S128); }
  { cuuint64_t gd[3] = {256, 2, 5}, gs[2] = {512, 1024}; cuuint32_t b[3] = {256, 1, 5};
    enc(fn, &maps.tap, shift, 3, gd, gs, b, CU_TENSOR_MAP_SWIZZLE_NONE); }
  { cuuint64_t gd[3] = {6 * D_, D_, 1}, gs[2] = {6 * D_ * 2, 6 * D_ * 2 * D_}; cuuint32_t b[3] = {64, 64, 1};
    enc(fn, &maps.wm, wmod, 3, gd, gs, b, S128); }
  { cuuint64_t gd[3] = {64, D_, F_ / 64}, gs[2] = {F_ * 2, 128}; cuuint32_t b[3] = {64, 32, 3};
    enc(fn, &maps.w1, w1, 3, gd, gs, b, S128);
    enc(fn, &maps.w3, w3, 3, gd, gs, b, S128);
    b[1] = 16;
    enc(fn, &maps.w1e, w1, 3, gd, gs, b, S128);
    enc(fn, &maps.w3e, w3, 3, gd, gs, b, S128);
    b[1] = 32; b[2] = 1;
    enc(fn, &maps.w1s, w1, 3, gd, gs, b, S128);
    enc(fn, &maps.w3s, w3, 3, gd, gs, b, S128); }
  { cuuint64_t gd[2] = {S_, D_}, gs[1] = {S_ * 2}; cuuint32_t b1[2] = {64, 64}, b2[2] = {64, 32};
    enc(fn, &maps.xs, pg->xs, 2, gd, gs, b1, S128);
    gd[1] = 2 * D_;
    enc(fn, &maps.x1b, pg->x1, 2, gd, gs, b2, S128);
    enc(fn, &maps.x1s, pg->x1, 2, gd, gs, b2, CU_TENSOR_MAP_SWIZZLE_NONE); }
  { cuuint64_t gd[5] = {D_, 2, 4, 4, 48}, gs[4] = {D_ * 2, D_ * 4, D_ * 16, D_ * 64}; cuuint32_t b[5] = {64, 2, 4, 4, 2};
    enc(fn, &maps.w2a, w2, 5, gd, gs, b, S128);
    gs[1] = D_ * 16; gs[2] = D_ * 4;
    enc(fn, &maps.w2b, w2, 5, gd, gs, b, S128); }
  { cuuint64_t gd[2] = {D_, S_}, gs[1] = {D_ * 2}; cuuint32_t b1[2] = {64, 16}, b2[2] = {32, 16};
    enc(fn, &maps.outa, d_out, 2, gd, gs, b1, S128);
    enc(fn, &maps.outb, d_out, 2, gd, gs, b2, CU_TENSOR_MAP_SWIZZLE_64B); }
  if (enc_err) return;
  cudaFuncSetAttribute(k_fused, cudaFuncAttributeMaxDynamicSharedMemorySize, SMEM_BYTES);
  cudaLaunchConfig_t cfg = {132, 512, SMEM_BYTES};
  cudaLaunchAttribute at = {cudaLaunchAttributeClusterDimension};
  at.val.clusterDim.x = 2; at.val.clusterDim.y = at.val.clusterDim.z = 1;
  cfg.attrs = &at; cfg.numAttrs = 1;
  int nc = 0;
  cudaOccupancyMaxActiveClusters(&nc, k_fused, &cfg);
  Ptrs P = {ssmk, c, ssmd, pg, 0x4E8DCBA9ull, {0x676760, 0x64620F01}, 0, 5000, 19, 64, 80, B_KV, 0, 0, 1, 1, 0x57010, 1.f};
  const char* sched = "k10v14f04q04q14q24q34q44k24v24f14k34v34f24k44v44f34f44n04n02n04n06n06n06";
  int t = 1000, pace = 420;
  for (int e = 0; e < NE; e++) {
    const char x = sched[3 * e];
    const int r = sched[3 * e + 1] - '0', kind = x == 'k' ? 0 : x == 'v' ? 1 : x == 'q' ? 2 : x == 'f' ? 3 : 4;
    t += (sched[3 * e + 2] - '0') * pace / 4;
    P.sched[e] = make_uint2(t | kind << 16 | r << 20, (kind < 2 ? tab(T_KV, r) + kind * KV_V : kind == 2 ? OFF_Q + 4096 * r : tab(T_F, r) + F_E) | (r + (kind < 2 ? B_KV : kind == 2 ? B_Q : B_FRAW)) << 18);
  }
  for (int u = 0; u < 5; u++) P.wt[u] = 9000 + 700 * u;
  const int dep[5] = {B_FL + 1, B_FL + 2, B_PFULL + 2, B_G3, B_PEMPTY + 2};
  for (int u = 0; u < 20; u++) P.wdep[u] = u % 5 * WSLOT | (~u & 1) << 12 | (u < 5 ? dep[u] : B_EMPTY + u - 5);
  for (int v = 0; v < 12; v++) P.w2t[v] = make_uint2(w2_desc(v), v ? B_EMPTY + (v > 5 ? 15 + v : v > 3 ? 14 + v : v > 1 ? 16 : 15) : B_UVD);
  for (int m = 0; m < 9; m++) { P.hid[0][m] = hid_at(m, 0) - OFF_A; P.hid[1][m] = hid_at(m, 1) - OFF_A - ARING; P.hid[2][m] = B_EMPTY + 19 + (m > 2 ? m : m / 2); }
  if (nc < 66) { P.boff = 128; k_fused<<<4, 512, SMEM_BYTES, cudaStreamPerThread>>>(P, maps); P.boff = 0; }
  k_fused<<<nc < 66 ? 128 : 132, 512, SMEM_BYTES, cudaStreamPerThread>>>(P, maps);
}
```

```cpp
#include <cuda_runtime.h>
#include <cuda.h>
#include <cuda_bf16.h>
#include <stdint.h>
#include <stdlib.h>

typedef __nv_bfloat16 bf16;
constexpr int S_ = 2048, D_ = 640, F_ = 1536;

struct Scratch {
  uint32_t st1[2][1024];
  uint32_t st2[32][4][128];
  uint2 modc[128][32];
  uint2 modv[3][D_];
  uint32_t uv[8][3072];
  unsigned hint[9][8][32];
  unsigned xsh[5][8][32], hhf[256 * 8];
  uint4 xr[D_ * 256];
  uint4 qt[D_ * 256];
  uint4 xs[D_ * 256];
  uint4 x1[2][D_ * 256];
  uint4 hh[32 * 8 * 1536];
};
__device__ __align__(1024) Scratch g_s;

__device__ __forceinline__ uint32_t smem_u32(const void* p) { return (uint32_t)__cvta_generic_to_shared(p); }
__device__ __forceinline__ void mbar_expect_tx(uint32_t b, uint32_t n) { asm volatile("mbarrier.arrive.expect_tx.shared::cta.b64 _, [%0], %1;" ::"r"(b), "r"(n) : "memory"); }
__device__ __forceinline__ void mbar_arrive(uint32_t b) { asm volatile("mbarrier.arrive.shared::cta.b64 _, [%0];" ::"r"(b) : "memory"); }
__device__ __forceinline__ void mbar_arrive2(uint32_t b) { asm volatile("mbarrier.arrive.shared::cta.b64 _, [%0], 2;" ::"r"(b) : "memory"); }
__device__ __forceinline__ uint32_t mapa(uint32_t a, uint32_t cta) { uint32_t r; asm volatile("mapa.shared::cluster.u32 %0, %1, %2;" : "=r"(r) : "r"(a), "r"(cta)); return r; }
__device__ __forceinline__ void mbar_arrive_remote(uint32_t rb) { asm volatile("mbarrier.arrive.shared::cluster.b64 _, [%0];" ::"r"(rb) : "memory"); }
constexpr int SPIN_LIMIT = 1 << 16;
template <int N> __device__ __forceinline__ void mbar_init(uint32_t b, uint32_t count) {
#pragma unroll
  for (int i = 0; i < N; i++) asm volatile("mbarrier.init.shared::cta.b64 [%0], %1;" ::"r"(b + 8 * i), "r"(count) : "memory");
}
__device__ __forceinline__ bool elect() { uint32_t p; asm volatile("{.reg .pred q; elect.sync _|q, 0xffffffff; selp.u32 %0, 1, 0, q;}" : "=r"(p)); return p; }
__device__ __forceinline__ void arrive1(uint32_t b) { __syncwarp(); if (elect()) mbar_arrive(b); }
__device__ __forceinline__ bool mbar_test(uint32_t b) {
  uint32_t ok;
  asm volatile("{.reg .pred p; mbarrier.test_wait.parity.shared::cta.b64 p, [%1], 0; selp.u32 %0,1,0,p;}" : "=r"(ok) : "r"(b) : "memory");
  return ok;
}
#define WAIT_LOOP(sem) "{.reg .pred p; mov.u32 %0, 0; W: mbarrier.try_wait.parity" sem ".shared::cta.b64 p, [%1], %2; @p bra.uni D; add.u32 %0, %0, 1; setp.lt.u32 p, %0, %3; @p bra.uni W; D:}"
__device__ __forceinline__ void mbar_wait(uint32_t b, uint32_t ph = 0) {
  int it;
  asm volatile(WAIT_LOOP("") : "=&r"(it) : "r"(b), "r"(ph), "n"(SPIN_LIMIT) : "memory");
}
__device__ __forceinline__ void mbar_wait_cluster(uint32_t b, uint32_t ph = 0) {
  int it;
  asm volatile(WAIT_LOOP(".acquire.cluster") : "=&r"(it) : "r"(b), "r"(ph), "n"(SPIN_LIMIT) : "memory");
}
__device__ __forceinline__ void wait_clock(uint32_t t) {
  asm volatile("{.reg .pred p; .reg .s32 d; W: mov.u32 d, %%clock; sub.s32 d, d, %0; setp.lt.s32 p, d, 0; @p bra.uni W;}" ::"r"(t) : "memory");
}
__device__ __forceinline__ void tma2d(uint32_t dst, const CUtensorMap* m, int c0, int c1, uint32_t bar) {
  asm volatile("cp.async.bulk.tensor.2d.shared::cluster.global.mbarrier::complete_tx::bytes [%0], [%1, {%3,%4}], [%2];" ::"r"(dst), "l"(m), "r"(bar), "r"(c0), "r"(c1) : "memory");
}
__device__ __forceinline__ void tma3d(uint32_t dst, const CUtensorMap* m, int c0, int c1, int c2, uint32_t bar) {
  asm volatile("cp.async.bulk.tensor.3d.shared::cluster.global.mbarrier::complete_tx::bytes [%0], [%1, {%3,%4,%5}], [%2];" ::"r"(dst), "l"(m), "r"(bar), "r"(c0), "r"(c1), "r"(c2) : "memory");
}
__device__ __forceinline__ void tma5d(uint32_t dst, const CUtensorMap* m, int c0, int c4, uint32_t bar) {
  asm volatile("cp.async.bulk.tensor.5d.shared::cluster.global.mbarrier::complete_tx::bytes [%0], [%1, {%4,%3,%3,%3,%5}], [%2];" ::"r"(dst), "l"(m), "r"(bar), "r"(0), "r"(c0), "r"(c4) : "memory");
}
__device__ __forceinline__ void tma2d_store(const CUtensorMap* m, int c0, int c1, uint32_t src) {
  asm volatile("cp.async.bulk.tensor.2d.global.shared::cta.bulk_group [%0, {%2,%3}], [%1];" ::"l"(m), "r"(src), "r"(c0), "r"(c1) : "memory");
}
__device__ __forceinline__ void bulk_load(uint32_t dst, const void* src, uint32_t bytes, uint32_t bar) {
  asm volatile("cp.async.bulk.shared::cluster.global.mbarrier::complete_tx::bytes [%0], [%1], %2, [%3];" ::"r"(dst), "l"(src), "r"(bytes), "r"(bar) : "memory");
}
__device__ __forceinline__ void prefetch_map(const CUtensorMap* m) { asm volatile("prefetch.tensormap [%0];" ::"l"(m) : "memory"); }
__device__ __forceinline__ void bulk_commit() { asm volatile("cp.async.bulk.commit_group;" ::: "memory"); }
__device__ __forceinline__ void bulk_wait_read() { asm volatile("cp.async.bulk.wait_group.read 0;" ::: "memory"); }
__device__ __forceinline__ void fence_async_smem() { asm volatile("fence.proxy.async.shared::cta;" ::: "memory"); }
__device__ __forceinline__ void fence_async_all() { asm volatile("fence.proxy.async.global;" ::: "memory"); }
__device__ __forceinline__ void named_bar(int id, int n) { asm volatile("bar.sync %0, %1;" ::"r"(id), "r"(n) : "memory"); }
__device__ __forceinline__ bool bar_all(int id, bool v) {
  uint32_t r;
  asm volatile("{.reg .pred p, q; setp.ne.u32 p, %2, 0; bar.red.and.pred q, %1, 128, p; selp.u32 %0, 1, 0, q;}" : "=r"(r) : "r"(id), "r"((uint32_t)v) : "memory");
  return __all_sync(~0u, r);
}
__device__ __forceinline__ void cluster_wait() { asm volatile("barrier.cluster.wait.aligned;" ::: "memory"); }
__device__ __forceinline__ void wg_fence() { asm volatile("wgmma.fence.sync.aligned;" ::: "memory"); }
__device__ __forceinline__ void wg_commit() { asm volatile("wgmma.commit_group.sync.aligned;" ::: "memory"); }
template <int N> __device__ __forceinline__ void wg_wait() { asm volatile("wgmma.wait_group.sync.aligned %0;" ::"n"(N) : "memory"); }
template <int N> __device__ __forceinline__ void fence_regs(float (&a)[N]) {
#pragma unroll
  for (int i = 0; i < N; i++) asm volatile("" : "+f"(a[i])::"memory");
}
template <int N> __device__ __forceinline__ void fence_n(float* a) {
#pragma unroll
  for (int i = 0; i < N; i++) asm volatile("" : "+f"(a[i])::"memory");
}
__device__ __forceinline__ uint64_t mkdesc(uint32_t addr, uint32_t lbo, uint32_t sbo, uint32_t swz) {
  uint32_t lo = (addr >> 4) | ((lbo >> 4) << 16), hi = (sbo >> 4) | (swz << 30);
  return ((uint64_t)hi << 32) | lo;
}
__device__ __forceinline__ void stmatrix_x4(uint32_t a, uint32_t r0, uint32_t r1, uint32_t r2, uint32_t r3) {
  asm volatile("stmatrix.sync.aligned.m8n8.x4.shared.b16 [%0], {%1,%2,%3,%4};" ::"r"(a), "r"(r0), "r"(r1), "r"(r2), "r"(r3) : "memory");
}
__device__ __forceinline__ void stmatrix_x4_t(uint32_t a, uint32_t r0, uint32_t r1, uint32_t r2, uint32_t r3) {
  asm volatile("stmatrix.sync.aligned.m8n8.x4.trans.shared.b16 [%0], {%1,%2,%3,%4};" ::"r"(a), "r"(r0), "r"(r1), "r"(r2), "r"(r3) : "memory");
}
__device__ __forceinline__ void ldmatrix_x4_t(uint32_t* r, uint32_t a) {
  asm volatile("ldmatrix.sync.aligned.m8n8.x4.trans.shared.b16 {%0,%1,%2,%3}, [%4];" : "=r"(r[0]), "=r"(r[1]), "=r"(r[2]), "=r"(r[3]) : "r"(a) : "memory");
}
__device__ __forceinline__ uint32_t lds32(uint32_t a) { uint32_t v; asm volatile("ld.shared.b32 %0, [%1];" : "=r"(v) : "r"(a) : "memory"); return v; }
__device__ __forceinline__ uint2 lds64(uint32_t a) { uint2 v; asm volatile("ld.shared.v2.b32 {%0,%1}, [%2];" : "=r"(v.x), "=r"(v.y) : "r"(a) : "memory"); return v; }
__device__ __forceinline__ uint4 lds128(uint32_t a) { uint4 v; asm volatile("ld.shared.v4.b32 {%0,%1,%2,%3}, [%4];" : "=r"(v.x), "=r"(v.y), "=r"(v.z), "=r"(v.w) : "r"(a) : "memory"); return v; }
__device__ __forceinline__ void sts32(uint32_t a, uint32_t v) { asm volatile("st.shared.b32 [%0], %1;" ::"r"(a), "r"(v) : "memory"); }
__device__ __forceinline__ void sts64(uint32_t a, uint32_t x, uint32_t y) { asm volatile("st.shared.v2.b32 [%0], {%1,%2};" ::"r"(a), "r"(x), "r"(y) : "memory"); }
__device__ __forceinline__ void sts128(uint32_t a, uint32_t x, uint32_t y, uint32_t z, uint32_t w) { asm volatile("st.shared.v4.b32 [%0], {%1,%2,%3,%4};" ::"r"(a), "r"(x), "r"(y), "r"(z), "r"(w) : "memory"); }
__device__ __forceinline__ uint4 ld_relaxed128(const void* p) { uint4 v; asm volatile("ld.relaxed.gpu.global.v4.u32 {%0,%1,%2,%3}, [%4];" : "=r"(v.x), "=r"(v.y), "=r"(v.z), "=r"(v.w) : "l"(p) : "memory"); return v; }
__device__ __forceinline__ uint2 ld_relaxed64(const void* p) { uint2 v; asm volatile("ld.relaxed.gpu.global.v2.u32 {%0,%1}, [%2];" : "=r"(v.x), "=r"(v.y) : "l"(p) : "memory"); return v; }
__device__ __forceinline__ uint32_t ld_relaxed32(const void* p) { uint32_t v; asm volatile("ld.relaxed.gpu.global.u32 %0, [%1];" : "=r"(v) : "l"(p) : "memory"); return v; }
__device__ __forceinline__ void st_relaxed128(void* p, uint32_t x, uint32_t y, uint32_t z, uint32_t w) { asm volatile("st.relaxed.gpu.global.v4.u32 [%0], {%1,%2,%3,%4};" ::"l"(p), "r"(x), "r"(y), "r"(z), "r"(w) : "memory"); }
__device__ __forceinline__ void st_relaxed32(void* p, uint32_t x) { asm volatile("st.relaxed.gpu.global.u32 [%0], %1;" ::"l"(p), "r"(x) : "memory"); }
__device__ __forceinline__ void red_hint(unsigned* p) { asm volatile("red.relaxed.gpu.global.add.u32 [%0], 1;" ::"l"(p) : "memory"); }
__device__ __forceinline__ void publish(uint32_t* p, uint32_t x) { asm volatile("{.reg .b32 t; atom.relaxed.gpu.global.exch.b32 t, [%0], %1;}" ::"l"(p), "r"(x) : "memory"); }
__device__ __forceinline__ uint32_t ldg32(const void* p) { uint32_t v; asm volatile("ld.global.nc.L1::no_allocate.b32 %0, [%1];" : "=r"(v) : "l"(p)); return v; }
__device__ __forceinline__ uint32_t pack_bf16(float lo, float hi) { uint32_t r; asm("cvt.rn.bf16x2.f32 %0, %1, %2;" : "=r"(r) : "f"(hi), "f"(lo)); return r; }
__device__ __forceinline__ float bf_lo(uint32_t v) { return __uint_as_float(v << 16); }
__device__ __forceinline__ float bf_hi(uint32_t v) { return __uint_as_float(v & 0xFFFF0000u); }
__device__ __forceinline__ uint32_t bmul2(uint32_t a, uint32_t b) { uint32_t r; asm("mul.rn.bf16x2 %0, %1, %2;" : "=r"(r) : "r"(a), "r"(b)); return r; }
__device__ __forceinline__ uint32_t badd2(uint32_t a, uint32_t b) { uint32_t r; asm("add.rn.bf16x2 %0, %1, %2;" : "=r"(r) : "r"(a), "r"(b)); return r; }
__device__ __forceinline__ uint32_t bfma2(uint32_t a, uint32_t b, uint32_t c) { uint32_t r; asm("fma.rn.bf16x2 %0, %1, %2, %3;" : "=r"(r) : "r"(a), "r"(b), "r"(c)); return r; }
__device__ __forceinline__ uint32_t set_tag(uint32_t x, uint32_t mask, uint32_t e) { uint32_t r; asm("lop3.b32 %0, %1, %2, %3, 0xB8;" : "=r"(r) : "r"(x), "r"(mask), "r"(e)); return r; }
__device__ __forceinline__ uint32_t opaque(uint32_t x) { asm volatile("" : "+r"(x)); return x; }
__device__ __forceinline__ float rbf(float x) { return __bfloat162float(__float2bfloat16(x)); }
__device__ __forceinline__ float silu_f(float x) {
  float e, r;
  asm("ex2.approx.ftz.f32 %0, %1;" : "=f"(e) : "f"(x * -1.4426950408889634f));
  asm("rcp.approx.ftz.f32 %0, %1;" : "=f"(r) : "f"(1.f + e));
  return x * r;
}
__device__ __forceinline__ float silu2(float x) {
  float t;
  asm("tanh.approx.f32 %0, %1;" : "=f"(t) : "f"(x));
  return fmaf(x, t, x);
}
__device__ __forceinline__ void pin(int off, uint32_t x) { asm volatile("{.reg .pred p; setp.lt.s32 p, %0, 0; @p st.shared.b32 [%0], %1;}" ::"r"(off), "r"(x) : "memory"); }
__device__ __forceinline__ void pin4(int off, const uint32_t* x) { asm volatile("{.reg .pred p; setp.lt.s32 p, %0, 0; @p st.shared.v4.b32 [%0], {%1,%2,%3,%4};}" ::"r"(off), "r"(x[0]), "r"(x[1]), "r"(x[2]), "r"(x[3]) : "memory"); }
__device__ __forceinline__ void split(int x, int n) { asm volatile("{.reg .pred p; setp.eq.s32 p, %0, %1; @p trap;}" ::"r"(x), "r"(~n) : "memory"); }
__device__ __forceinline__ void ln_final(float s, float q, float& m, float& sd) {
  m = s * (1.f / D_);
  asm("sqrt.approx.f32 %0, %1;" : "=f"(sd) : "f"(rbf(rbf(fmaxf(fmaf(-m, m, q * (1.f / D_)), 0.f)) + 1e-5f)));
  sd = rbf(sd);
}
__device__ __forceinline__ float rcpf(float x) { float r; asm("rcp.approx.f32 %0, %1;" : "=f"(r) : "f"(x)); return r; }

__device__ __forceinline__ void wg_rs16_0(float* d, const uint32_t* a, uint64_t db, int sc) {
  asm volatile("{.reg .pred p; setp.ne.b32 p, %13, 0; wgmma.mma_async.sync.aligned.m64n16k16.f32.bf16.bf16 {%0,%1,%2,%3,%4,%5,%6,%7}, {%8,%9,%10,%11}, %12, p, 1, 1, 0;}"
    : "+f"(d[0]),"+f"(d[1]),"+f"(d[2]),"+f"(d[3]),"+f"(d[4]),"+f"(d[5]),"+f"(d[6]),"+f"(d[7]) : "r"(a[0]),"r"(a[1]),"r"(a[2]),"r"(a[3]),"l"(db),"r"(sc));
}
__device__ __forceinline__ void wg_rs32_0(float* d, const uint32_t* a, uint64_t db, int sc) {
  asm volatile("{.reg .pred p; setp.ne.b32 p, %21, 0; wgmma.mma_async.sync.aligned.m64n32k16.f32.bf16.bf16 {%0,%1,%2,%3,%4,%5,%6,%7,%8,%9,%10,%11,%12,%13,%14,%15}, {%16,%17,%18,%19}, %20, p, 1, 1, 0;}"
    : "+f"(d[0]),"+f"(d[1]),"+f"(d[2]),"+f"(d[3]),"+f"(d[4]),"+f"(d[5]),"+f"(d[6]),"+f"(d[7]),"+f"(d[8]),"+f"(d[9]),"+f"(d[10]),"+f"(d[11]),"+f"(d[12]),"+f"(d[13]),"+f"(d[14]),"+f"(d[15]) : "r"(a[0]),"r"(a[1]),"r"(a[2]),"r"(a[3]),"l"(db),"r"(sc));
}
__device__ __forceinline__ void wg_rs48_0(float* d, const uint32_t* a, uint64_t db, int sc) {
  asm volatile("{.reg .pred p; setp.ne.b32 p, %29, 0; wgmma.mma_async.sync.aligned.m64n48k16.f32.bf16.bf16 {%0,%1,%2,%3,%4,%5,%6,%7,%8,%9,%10,%11,%12,%13,%14,%15,%16,%17,%18,%19,%20,%21,%22,%23}, {%24,%25,%26,%27}, %28, p, 1, 1, 0;}"
    : "+f"(d[0]),"+f"(d[1]),"+f"(d[2]),"+f"(d[3]),"+f"(d[4]),"+f"(d[5]),"+f"(d[6]),"+f"(d[7]),"+f"(d[8]),"+f"(d[9]),"+f"(d[10]),"+f"(d[11]),"+f"(d[12]),"+f"(d[13]),"+f"(d[14]),"+f"(d[15]),"+f"(d[16]),"+f"(d[17]),"+f"(d[18]),"+f"(d[19]),"+f"(d[20]),"+f"(d[21]),"+f"(d[22]),"+f"(d[23]) : "r"(a[0]),"r"(a[1]),"r"(a[2]),"r"(a[3]),"l"(db),"r"(sc));
}
__device__ __forceinline__ void wg_rs64_0(float* d, const uint32_t* a, uint64_t db, int sc) {
  asm volatile("{.reg .pred p; setp.ne.b32 p, %37, 0; wgmma.mma_async.sync.aligned.m64n64k16.f32.bf16.bf16 {%0,%1,%2,%3,%4,%5,%6,%7,%8,%9,%10,%11,%12,%13,%14,%15,%16,%17,%18,%19,%20,%21,%22,%23,%24,%25,%26,%27,%28,%29,%30,%31}, {%32,%33,%34,%35}, %36, p, 1, 1, 0;}"
    : "+f"(d[0]),"+f"(d[1]),"+f"(d[2]),"+f"(d[3]),"+f"(d[4]),"+f"(d[5]),"+f"(d[6]),"+f"(d[7]),"+f"(d[8]),"+f"(d[9]),"+f"(d[10]),"+f"(d[11]),"+f"(d[12]),"+f"(d[13]),"+f"(d[14]),"+f"(d[15]),"+f"(d[16]),"+f"(d[17]),"+f"(d[18]),"+f"(d[19]),"+f"(d[20]),"+f"(d[21]),"+f"(d[22]),"+f"(d[23]),"+f"(d[24]),"+f"(d[25]),"+f"(d[26]),"+f"(d[27]),"+f"(d[28]),"+f"(d[29]),"+f"(d[30]),"+f"(d[31]) : "r"(a[0]),"r"(a[1]),"r"(a[2]),"r"(a[3]),"l"(db),"r"(sc));
}
__device__ __forceinline__ void wg_rs80_0(float* d, const uint32_t* a, uint64_t db, int sc) {
  asm volatile("{.reg .pred p; setp.ne.b32 p, %45, 0; wgmma.mma_async.sync.aligned.m64n80k16.f32.bf16.bf16 {%0,%1,%2,%3,%4,%5,%6,%7,%8,%9,%10,%11,%12,%13,%14,%15,%16,%17,%18,%19,%20,%21,%22,%23,%24,%25,%26,%27,%28,%29,%30,%31,%32,%33,%34,%35,%36,%37,%38,%39}, {%40,%41,%42,%43}, %44, p, 1, 1, 0;}"
    : "+f"(d[0]),"+f"(d[1]),"+f"(d[2]),"+f"(d[3]),"+f"(d[4]),"+f"(d[5]),"+f"(d[6]),"+f"(d[7]),"+f"(d[8]),"+f"(d[9]),"+f"(d[10]),"+f"(d[11]),"+f"(d[12]),"+f"(d[13]),"+f"(d[14]),"+f"(d[15]),"+f"(d[16]),"+f"(d[17]),"+f"(d[18]),"+f"(d[19]),"+f"(d[20]),"+f"(d[21]),"+f"(d[22]),"+f"(d[23]),"+f"(d[24]),"+f"(d[25]),"+f"(d[26]),"+f"(d[27]),"+f"(d[28]),"+f"(d[29]),"+f"(d[30]),"+f"(d[31]),"+f"(d[32]),"+f"(d[33]),"+f"(d[34]),"+f"(d[35]),"+f"(d[36]),"+f"(d[37]),"+f"(d[38]),"+f"(d[39]) : "r"(a[0]),"r"(a[1]),"r"(a[2]),"r"(a[3]),"l"(db),"r"(sc));
}
__device__ __forceinline__ void wg_rs96_0(float* d, const uint32_t* a, uint64_t db, int sc) {
  asm volatile("{.reg .pred p; setp.ne.b32 p, %53, 0; wgmma.mma_async.sync.aligned.m64n96k16.f32.bf16.bf16 {%0,%1,%2,%3,%4,%5,%6,%7,%8,%9,%10,%11,%12,%13,%14,%15,%16,%17,%18,%19,%20,%21,%22,%23,%24,%25,%26,%27,%28,%29,%30,%31,%32,%33,%34,%35,%36,%37,%38,%39,%40,%41,%42,%43,%44,%45,%46,%47}, {%48,%49,%50,%51}, %52, p, 1, 1, 0;}"
    : "+f"(d[0]),"+f"(d[1]),"+f"(d[2]),"+f"(d[3]),"+f"(d[4]),"+f"(d[5]),"+f"(d[6]),"+f"(d[7]),"+f"(d[8]),"+f"(d[9]),"+f"(d[10]),"+f"(d[11]),"+f"(d[12]),"+f"(d[13]),"+f"(d[14]),"+f"(d[15]),"+f"(d[16]),"+f"(d[17]),"+f"(d[18]),"+f"(d[19]),"+f"(d[20]),"+f"(d[21]),"+f"(d[22]),"+f"(d[23]),"+f"(d[24]),"+f"(d[25]),"+f"(d[26]),"+f"(d[27]),"+f"(d[28]),"+f"(d[29]),"+f"(d[30]),"+f"(d[31]),"+f"(d[32]),"+f"(d[33]),"+f"(d[34]),"+f"(d[35]),"+f"(d[36]),"+f"(d[37]),"+f"(d[38]),"+f"(d[39]),"+f"(d[40]),"+f"(d[41]),"+f"(d[42]),"+f"(d[43]),"+f"(d[44]),"+f"(d[45]),"+f"(d[46]),"+f"(d[47]) : "r"(a[0]),"r"(a[1]),"r"(a[2]),"r"(a[3]),"l"(db),"r"(sc));
}
__device__ __forceinline__ void wg_rs112_0(float* d, const uint32_t* a, uint64_t db, int sc) {
  asm volatile("{.reg .pred p; setp.ne.b32 p, %61, 0; wgmma.mma_async.sync.aligned.m64n112k16.f32.bf16.bf16 {%0,%1,%2,%3,%4,%5,%6,%7,%8,%9,%10,%11,%12,%13,%14,%15,%16,%17,%18,%19,%20,%21,%22,%23,%24,%25,%26,%27,%28,%29,%30,%31,%32,%33,%34,%35,%36,%37,%38,%39,%40,%41,%42,%43,%44,%45,%46,%47,%48,%49,%50,%51,%52,%53,%54,%55}, {%56,%57,%58,%59}, %60, p, 1, 1, 0;}"
    : "+f"(d[0]),"+f"(d[1]),"+f"(d[2]),"+f"(d[3]),"+f"(d[4]),"+f"(d[5]),"+f"(d[6]),"+f"(d[7]),"+f"(d[8]),"+f"(d[9]),"+f"(d[10]),"+f"(d[11]),"+f"(d[12]),"+f"(d[13]),"+f"(d[14]),"+f"(d[15]),"+f"(d[16]),"+f"(d[17]),"+f"(d[18]),"+f"(d[19]),"+f"(d[20]),"+f"(d[21]),"+f"(d[22]),"+f"(d[23]),"+f"(d[24]),"+f"(d[25]),"+f"(d[26]),"+f"(d[27]),"+f"(d[28]),"+f"(d[29]),"+f"(d[30]),"+f"(d[31]),"+f"(d[32]),"+f"(d[33]),"+f"(d[34]),"+f"(d[35]),"+f"(d[36]),"+f"(d[37]),"+f"(d[38]),"+f"(d[39]),"+f"(d[40]),"+f"(d[41]),"+f"(d[42]),"+f"(d[43]),"+f"(d[44]),"+f"(d[45]),"+f"(d[46]),"+f"(d[47]),"+f"(d[48]),"+f"(d[49]),"+f"(d[50]),"+f"(d[51]),"+f"(d[52]),"+f"(d[53]),"+f"(d[54]),"+f"(d[55]) : "r"(a[0]),"r"(a[1]),"r"(a[2]),"r"(a[3]),"l"(db),"r"(sc));
}
__device__ __forceinline__ void wg_rs128_0(float* d, const uint32_t* a, uint64_t db, int sc) {
  asm volatile("{.reg .pred p; setp.ne.b32 p, %69, 0; wgmma.mma_async.sync.aligned.m64n128k16.f32.bf16.bf16 {%0,%1,%2,%3,%4,%5,%6,%7,%8,%9,%10,%11,%12,%13,%14,%15,%16,%17,%18,%19,%20,%21,%22,%23,%24,%25,%26,%27,%28,%29,%30,%31,%32,%33,%34,%35,%36,%37,%38,%39,%40,%41,%42,%43,%44,%45,%46,%47,%48,%49,%50,%51,%52,%53,%54,%55,%56,%57,%58,%59,%60,%61,%62,%63}, {%64,%65,%66,%67}, %68, p, 1, 1, 0;}"
    : "+f"(d[0]),"+f"(d[1]),"+f"(d[2]),"+f"(d[3]),"+f"(d[4]),"+f"(d[5]),"+f"(d[6]),"+f"(d[7]),"+f"(d[8]),"+f"(d[9]),"+f"(d[10]),"+f"(d[11]),"+f"(d[12]),"+f"(d[13]),"+f"(d[14]),"+f"(d[15]),"+f"(d[16]),"+f"(d[17]),"+f"(d[18]),"+f"(d[19]),"+f"(d[20]),"+f"(d[21]),"+f"(d[22]),"+f"(d[23]),"+f"(d[24]),"+f"(d[25]),"+f"(d[26]),"+f"(d[27]),"+f"(d[28]),"+f"(d[29]),"+f"(d[30]),"+f"(d[31]),"+f"(d[32]),"+f"(d[33]),"+f"(d[34]),"+f"(d[35]),"+f"(d[36]),"+f"(d[37]),"+f"(d[38]),"+f"(d[39]),"+f"(d[40]),"+f"(d[41]),"+f"(d[42]),"+f"(d[43]),"+f"(d[44]),"+f"(d[45]),"+f"(d[46]),"+f"(d[47]),"+f"(d[48]),"+f"(d[49]),"+f"(d[50]),"+f"(d[51]),"+f"(d[52]),"+f"(d[53]),"+f"(d[54]),"+f"(d[55]),"+f"(d[56]),"+f"(d[57]),"+f"(d[58]),"+f"(d[59]),"+f"(d[60]),"+f"(d[61]),"+f"(d[62]),"+f"(d[63]) : "r"(a[0]),"r"(a[1]),"r"(a[2]),"r"(a[3]),"l"(db),"r"(sc));
}
__device__ __forceinline__ void wg_rs144_0(float* d, const uint32_t* a, uint64_t db, int sc) {
  asm volatile("{.reg .pred p; setp.ne.b32 p, %77, 0; wgmma.mma_async.sync.aligned.m64n144k16.f32.bf16.bf16 {%0,%1,%2,%3,%4,%5,%6,%7,%8,%9,%10,%11,%12,%13,%14,%15,%16,%17,%18,%19,%20,%21,%22,%23,%24,%25,%26,%27,%28,%29,%30,%31,%32,%33,%34,%35,%36,%37,%38,%39,%40,%41,%42,%43,%44,%45,%46,%47,%48,%49,%50,%51,%52,%53,%54,%55,%56,%57,%58,%59,%60,%61,%62,%63,%64,%65,%66,%67,%68,%69,%70,%71}, {%72,%73,%74,%75}, %76, p, 1, 1, 0;}"
    : "+f"(d[0]),"+f"(d[1]),"+f"(d[2]),"+f"(d[3]),"+f"(d[4]),"+f"(d[5]),"+f"(d[6]),"+f"(d[7]),"+f"(d[8]),"+f"(d[9]),"+f"(d[10]),"+f"(d[11]),"+f"(d[12]),"+f"(d[13]),"+f"(d[14]),"+f"(d[15]),"+f"(d[16]),"+f"(d[17]),"+f"(d[18]),"+f"(d[19]),"+f"(d[20]),"+f"(d[21]),"+f"(d[22]),"+f"(d[23]),"+f"(d[24]),"+f"(d[25]),"+f"(d[26]),"+f"(d[27]),"+f"(d[28]),"+f"(d[29]),"+f"(d[30]),"+f"(d[31]),"+f"(d[32]),"+f"(d[33]),"+f"(d[34]),"+f"(d[35]),"+f"(d[36]),"+f"(d[37]),"+f"(d[38]),"+f"(d[39]),"+f"(d[40]),"+f"(d[41]),"+f"(d[42]),"+f"(d[43]),"+f"(d[44]),"+f"(d[45]),"+f"(d[46]),"+f"(d[47]),"+f"(d[48]),"+f"(d[49]),"+f"(d[50]),"+f"(d[51]),"+f"(d[52]),"+f"(d[53]),"+f"(d[54]),"+f"(d[55]),"+f"(d[56]),"+f"(d[57]),"+f"(d[58]),"+f"(d[59]),"+f"(d[60]),"+f"(d[61]),"+f"(d[62]),"+f"(d[63]),"+f"(d[64]),"+f"(d[65]),"+f"(d[66]),"+f"(d[67]),"+f"(d[68]),"+f"(d[69]),"+f"(d[70]),"+f"(d[71]) : "r"(a[0]),"r"(a[1]),"r"(a[2]),"r"(a[3]),"l"(db),"r"(sc));
}
__device__ __forceinline__ void wg_rs160_0(float* d, const uint32_t* a, uint64_t db, int sc) {
  asm volatile("{.reg .pred p; setp.ne.b32 p, %85, 0; wgmma.mma_async.sync.aligned.m64n160k16.f32.bf16.bf16 {%0,%1,%2,%3,%4,%5,%6,%7,%8,%9,%10,%11,%12,%13,%14,%15,%16,%17,%18,%19,%20,%21,%22,%23,%24,%25,%26,%27,%28,%29,%30,%31,%32,%33,%34,%35,%36,%37,%38,%39,%40,%41,%42,%43,%44,%45,%46,%47,%48,%49,%50,%51,%52,%53,%54,%55,%56,%57,%58,%59,%60,%61,%62,%63,%64,%65,%66,%67,%68,%69,%70,%71,%72,%73,%74,%75,%76,%77,%78,%79}, {%80,%81,%82,%83}, %84, p, 1, 1, 0;}"
    : "+f"(d[0]),"+f"(d[1]),"+f"(d[2]),"+f"(d[3]),"+f"(d[4]),"+f"(d[5]),"+f"(d[6]),"+f"(d[7]),"+f"(d[8]),"+f"(d[9]),"+f"(d[10]),"+f"(d[11]),"+f"(d[12]),"+f"(d[13]),"+f"(d[14]),"+f"(d[15]),"+f"(d[16]),"+f"(d[17]),"+f"(d[18]),"+f"(d[19]),"+f"(d[20]),"+f"(d[21]),"+f"(d[22]),"+f"(d[23]),"+f"(d[24]),"+f"(d[25]),"+f"(d[26]),"+f"(d[27]),"+f"(d[28]),"+f"(d[29]),"+f"(d[30]),"+f"(d[31]),"+f"(d[32]),"+f"(d[33]),"+f"(d[34]),"+f"(d[35]),"+f"(d[36]),"+f"(d[37]),"+f"(d[38]),"+f"(d[39]),"+f"(d[40]),"+f"(d[41]),"+f"(d[42]),"+f"(d[43]),"+f"(d[44]),"+f"(d[45]),"+f"(d[46]),"+f"(d[47]),"+f"(d[48]),"+f"(d[49]),"+f"(d[50]),"+f"(d[51]),"+f"(d[52]),"+f"(d[53]),"+f"(d[54]),"+f"(d[55]),"+f"(d[56]),"+f"(d[57]),"+f"(d[58]),"+f"(d[59]),"+f"(d[60]),"+f"(d[61]),"+f"(d[62]),"+f"(d[63]),"+f"(d[64]),"+f"(d[65]),"+f"(d[66]),"+f"(d[67]),"+f"(d[68]),"+f"(d[69]),"+f"(d[70]),"+f"(d[71]),"+f"(d[72]),"+f"(d[73]),"+f"(d[74]),"+f"(d[75]),"+f"(d[76]),"+f"(d[77]),"+f"(d[78]),"+f"(d[79]) : "r"(a[0]),"r"(a[1]),"r"(a[2]),"r"(a[3]),"l"(db),"r"(sc));
}
__device__ __forceinline__ void wg_rs176_0(float* d, const uint32_t* a, uint64_t db, int sc) {
  asm volatile("{.reg .pred p; setp.ne.b32 p, %93, 0; wgmma.mma_async.sync.aligned.m64n176k16.f32.bf16.bf16 {%0,%1,%2,%3,%4,%5,%6,%7,%8,%9,%10,%11,%12,%13,%14,%15,%16,%17,%18,%19,%20,%21,%22,%23,%24,%25,%26,%27,%28,%29,%30,%31,%32,%33,%34,%35,%36,%37,%38,%39,%40,%41,%42,%43,%44,%45,%46,%47,%48,%49,%50,%51,%52,%53,%54,%55,%56,%57,%58,%59,%60,%61,%62,%63,%64,%65,%66,%67,%68,%69,%70,%71,%72,%73,%74,%75,%76,%77,%78,%79,%80,%81,%82,%83,%84,%85,%86,%87}, {%88,%89,%90,%91}, %92, p, 1, 1, 0;}"
    : "+f"(d[0]),"+f"(d[1]),"+f"(d[2]),"+f"(d[3]),"+f"(d[4]),"+f"(d[5]),"+f"(d[6]),"+f"(d[7]),"+f"(d[8]),"+f"(d[9]),"+f"(d[10]),"+f"(d[11]),"+f"(d[12]),"+f"(d[13]),"+f"(d[14]),"+f"(d[15]),"+f"(d[16]),"+f"(d[17]),"+f"(d[18]),"+f"(d[19]),"+f"(d[20]),"+f"(d[21]),"+f"(d[22]),"+f"(d[23]),"+f"(d[24]),"+f"(d[25]),"+f"(d[26]),"+f"(d[27]),"+f"(d[28]),"+f"(d[29]),"+f"(d[30]),"+f"(d[31]),"+f"(d[32]),"+f"(d[33]),"+f"(d[34]),"+f"(d[35]),"+f"(d[36]),"+f"(d[37]),"+f"(d[38]),"+f"(d[39]),"+f"(d[40]),"+f"(d[41]),"+f"(d[42]),"+f"(d[43]),"+f"(d[44]),"+f"(d[45]),"+f"(d[46]),"+f"(d[47]),"+f"(d[48]),"+f"(d[49]),"+f"(d[50]),"+f"(d[51]),"+f"(d[52]),"+f"(d[53]),"+f"(d[54]),"+f"(d[55]),"+f"(d[56]),"+f"(d[57]),"+f"(d[58]),"+f"(d[59]),"+f"(d[60]),"+f"(d[61]),"+f"(d[62]),"+f"(d[63]),"+f"(d[64]),"+f"(d[65]),"+f"(d[66]),"+f"(d[67]),"+f"(d[68]),"+f"(d[69]),"+f"(d[70]),"+f"(d[71]),"+f"(d[72]),"+f"(d[73]),"+f"(d[74]),"+f"(d[75]),"+f"(d[76]),"+f"(d[77]),"+f"(d[78]),"+f"(d[79]),"+f"(d[80]),"+f"(d[81]),"+f"(d[82]),"+f"(d[83]),"+f"(d[84]),"+f"(d[85]),"+f"(d[86]),"+f"(d[87]) : "r"(a[0]),"r"(a[1]),"r"(a[2]),"r"(a[3]),"l"(db),"r"(sc));
}
__device__ __forceinline__ void wg_rs192_0(float* d, const uint32_t* a, uint64_t db, int sc) {
  asm volatile("{.reg .pred p; setp.ne.b32 p, %101, 0; wgmma.mma_async.sync.aligned.m64n192k16.f32.bf16.bf16 {%0,%1,%2,%3,%4,%5,%6,%7,%8,%9,%10,%11,%12,%13,%14,%15,%16,%17,%18,%19,%20,%21,%22,%23,%24,%25,%26,%27,%28,%29,%30,%31,%32,%33,%34,%35,%36,%37,%38,%39,%40,%41,%42,%43,%44,%45,%46,%47,%48,%49,%50,%51,%52,%53,%54,%55,%56,%57,%58,%59,%60,%61,%62,%63,%64,%65,%66,%67,%68,%69,%70,%71,%72,%73,%74,%75,%76,%77,%78,%79,%80,%81,%82,%83,%84,%85,%86,%87,%88,%89,%90,%91,%92,%93,%94,%95}, {%96,%97,%98,%99}, %100, p, 1, 1, 0;}"
    : "+f"(d[0]),"+f"(d[1]),"+f"(d[2]),"+f"(d[3]),"+f"(d[4]),"+f"(d[5]),"+f"(d[6]),"+f"(d[7]),"+f"(d[8]),"+f"(d[9]),"+f"(d[10]),"+f"(d[11]),"+f"(d[12]),"+f"(d[13]),"+f"(d[14]),"+f"(d[15]),"+f"(d[16]),"+f"(d[17]),"+f"(d[18]),"+f"(d[19]),"+f"(d[20]),"+f"(d[21]),"+f"(d[22]),"+f"(d[23]),"+f"(d[24]),"+f"(d[25]),"+f"(d[26]),"+f"(d[27]),"+f"(d[28]),"+f"(d[29]),"+f"(d[30]),"+f"(d[31]),"+f"(d[32]),"+f"(d[33]),"+f"(d[34]),"+f"(d[35]),"+f"(d[36]),"+f"(d[37]),"+f"(d[38]),"+f"(d[39]),"+f"(d[40]),"+f"(d[41]),"+f"(d[42]),"+f"(d[43]),"+f"(d[44]),"+f"(d[45]),"+f"(d[46]),"+f"(d[47]),"+f"(d[48]),"+f"(d[49]),"+f"(d[50]),"+f"(d[51]),"+f"(d[52]),"+f"(d[53]),"+f"(d[54]),"+f"(d[55]),"+f"(d[56]),"+f"(d[57]),"+f"(d[58]),"+f"(d[59]),"+f"(d[60]),"+f"(d[61]),"+f"(d[62]),"+f"(d[63]),"+f"(d[64]),"+f"(d[65]),"+f"(d[66]),"+f"(d[67]),"+f"(d[68]),"+f"(d[69]),"+f"(d[70]),"+f"(d[71]),"+f"(d[72]),"+f"(d[73]),"+f"(d[74]),"+f"(d[75]),"+f"(d[76]),"+f"(d[77]),"+f"(d[78]),"+f"(d[79]),"+f"(d[80]),"+f"(d[81]),"+f"(d[82]),"+f"(d[83]),"+f"(d[84]),"+f"(d[85]),"+f"(d[86]),"+f"(d[87]),"+f"(d[88]),"+f"(d[89]),"+f"(d[90]),"+f"(d[91]),"+f"(d[92]),"+f"(d[93]),"+f"(d[94]),"+f"(d[95]) : "r"(a[0]),"r"(a[1]),"r"(a[2]),"r"(a[3]),"l"(db),"r"(sc));
}
__device__ __forceinline__ void wg_ss192_11(float* d, uint64_t da, uint64_t db, int sc) {
  asm volatile("{.reg .pred p; setp.ne.b32 p, %98, 0; wgmma.mma_async.sync.aligned.m64n192k16.f32.bf16.bf16 {%0,%1,%2,%3,%4,%5,%6,%7,%8,%9,%10,%11,%12,%13,%14,%15,%16,%17,%18,%19,%20,%21,%22,%23,%24,%25,%26,%27,%28,%29,%30,%31,%32,%33,%34,%35,%36,%37,%38,%39,%40,%41,%42,%43,%44,%45,%46,%47,%48,%49,%50,%51,%52,%53,%54,%55,%56,%57,%58,%59,%60,%61,%62,%63,%64,%65,%66,%67,%68,%69,%70,%71,%72,%73,%74,%75,%76,%77,%78,%79,%80,%81,%82,%83,%84,%85,%86,%87,%88,%89,%90,%91,%92,%93,%94,%95}, %96, %97, p, 1, 1, 1, 1;}"
    : "+f"(d[0]),"+f"(d[1]),"+f"(d[2]),"+f"(d[3]),"+f"(d[4]),"+f"(d[5]),"+f"(d[6]),"+f"(d[7]),"+f"(d[8]),"+f"(d[9]),"+f"(d[10]),"+f"(d[11]),"+f"(d[12]),"+f"(d[13]),"+f"(d[14]),"+f"(d[15]),"+f"(d[16]),"+f"(d[17]),"+f"(d[18]),"+f"(d[19]),"+f"(d[20]),"+f"(d[21]),"+f"(d[22]),"+f"(d[23]),"+f"(d[24]),"+f"(d[25]),"+f"(d[26]),"+f"(d[27]),"+f"(d[28]),"+f"(d[29]),"+f"(d[30]),"+f"(d[31]),"+f"(d[32]),"+f"(d[33]),"+f"(d[34]),"+f"(d[35]),"+f"(d[36]),"+f"(d[37]),"+f"(d[38]),"+f"(d[39]),"+f"(d[40]),"+f"(d[41]),"+f"(d[42]),"+f"(d[43]),"+f"(d[44]),"+f"(d[45]),"+f"(d[46]),"+f"(d[47]),"+f"(d[48]),"+f"(d[49]),"+f"(d[50]),"+f"(d[51]),"+f"(d[52]),"+f"(d[53]),"+f"(d[54]),"+f"(d[55]),"+f"(d[56]),"+f"(d[57]),"+f"(d[58]),"+f"(d[59]),"+f"(d[60]),"+f"(d[61]),"+f"(d[62]),"+f"(d[63]),"+f"(d[64]),"+f"(d[65]),"+f"(d[66]),"+f"(d[67]),"+f"(d[68]),"+f"(d[69]),"+f"(d[70]),"+f"(d[71]),"+f"(d[72]),"+f"(d[73]),"+f"(d[74]),"+f"(d[75]),"+f"(d[76]),"+f"(d[77]),"+f"(d[78]),"+f"(d[79]),"+f"(d[80]),"+f"(d[81]),"+f"(d[82]),"+f"(d[83]),"+f"(d[84]),"+f"(d[85]),"+f"(d[86]),"+f"(d[87]),"+f"(d[88]),"+f"(d[89]),"+f"(d[90]),"+f"(d[91]),"+f"(d[92]),"+f"(d[93]),"+f"(d[94]),"+f"(d[95]) : "l"(da),"l"(db),"r"(sc));
}
__device__ __forceinline__ void wg_ss192_01(float* d, uint64_t da, uint64_t db, int sc) {
  asm volatile("{.reg .pred p; setp.ne.b32 p, %98, 0; wgmma.mma_async.sync.aligned.m64n192k16.f32.bf16.bf16 {%0,%1,%2,%3,%4,%5,%6,%7,%8,%9,%10,%11,%12,%13,%14,%15,%16,%17,%18,%19,%20,%21,%22,%23,%24,%25,%26,%27,%28,%29,%30,%31,%32,%33,%34,%35,%36,%37,%38,%39,%40,%41,%42,%43,%44,%45,%46,%47,%48,%49,%50,%51,%52,%53,%54,%55,%56,%57,%58,%59,%60,%61,%62,%63,%64,%65,%66,%67,%68,%69,%70,%71,%72,%73,%74,%75,%76,%77,%78,%79,%80,%81,%82,%83,%84,%85,%86,%87,%88,%89,%90,%91,%92,%93,%94,%95}, %96, %97, p, 1, 1, 0, 1;}"
    : "+f"(d[0]),"+f"(d[1]),"+f"(d[2]),"+f"(d[3]),"+f"(d[4]),"+f"(d[5]),"+f"(d[6]),"+f"(d[7]),"+f"(d[8]),"+f"(d[9]),"+f"(d[10]),"+f"(d[11]),"+f"(d[12]),"+f"(d[13]),"+f"(d[14]),"+f"(d[15]),"+f"(d[16]),"+f"(d[17]),"+f"(d[18]),"+f"(d[19]),"+f"(d[20]),"+f"(d[21]),"+f"(d[22]),"+f"(d[23]),"+f"(d[24]),"+f"(d[25]),"+f"(d[26]),"+f"(d[27]),"+f"(d[28]),"+f"(d[29]),"+f"(d[30]),"+f"(d[31]),"+f"(d[32]),"+f"(d[33]),"+f"(d[34]),"+f"(d[35]),"+f"(d[36]),"+f"(d[37]),"+f"(d[38]),"+f"(d[39]),"+f"(d[40]),"+f"(d[41]),"+f"(d[42]),"+f"(d[43]),"+f"(d[44]),"+f"(d[45]),"+f"(d[46]),"+f"(d[47]),"+f"(d[48]),"+f"(d[49]),"+f"(d[50]),"+f"(d[51]),"+f"(d[52]),"+f"(d[53]),"+f"(d[54]),"+f"(d[55]),"+f"(d[56]),"+f"(d[57]),"+f"(d[58]),"+f"(d[59]),"+f"(d[60]),"+f"(d[61]),"+f"(d[62]),"+f"(d[63]),"+f"(d[64]),"+f"(d[65]),"+f"(d[66]),"+f"(d[67]),"+f"(d[68]),"+f"(d[69]),"+f"(d[70]),"+f"(d[71]),"+f"(d[72]),"+f"(d[73]),"+f"(d[74]),"+f"(d[75]),"+f"(d[76]),"+f"(d[77]),"+f"(d[78]),"+f"(d[79]),"+f"(d[80]),"+f"(d[81]),"+f"(d[82]),"+f"(d[83]),"+f"(d[84]),"+f"(d[85]),"+f"(d[86]),"+f"(d[87]),"+f"(d[88]),"+f"(d[89]),"+f"(d[90]),"+f"(d[91]),"+f"(d[92]),"+f"(d[93]),"+f"(d[94]),"+f"(d[95]) : "l"(da),"l"(db),"r"(sc));
}
__device__ __forceinline__ void wg_ss160_01(float* d, uint64_t da, uint64_t db, int sc) {
  asm volatile("{.reg .pred p; setp.ne.b32 p, %82, 0; wgmma.mma_async.sync.aligned.m64n160k16.f32.bf16.bf16 {%0,%1,%2,%3,%4,%5,%6,%7,%8,%9,%10,%11,%12,%13,%14,%15,%16,%17,%18,%19,%20,%21,%22,%23,%24,%25,%26,%27,%28,%29,%30,%31,%32,%33,%34,%35,%36,%37,%38,%39,%40,%41,%42,%43,%44,%45,%46,%47,%48,%49,%50,%51,%52,%53,%54,%55,%56,%57,%58,%59,%60,%61,%62,%63,%64,%65,%66,%67,%68,%69,%70,%71,%72,%73,%74,%75,%76,%77,%78,%79}, %80, %81, p, 1, 1, 0, 1;}"
    : "+f"(d[0]),"+f"(d[1]),"+f"(d[2]),"+f"(d[3]),"+f"(d[4]),"+f"(d[5]),"+f"(d[6]),"+f"(d[7]),"+f"(d[8]),"+f"(d[9]),"+f"(d[10]),"+f"(d[11]),"+f"(d[12]),"+f"(d[13]),"+f"(d[14]),"+f"(d[15]),"+f"(d[16]),"+f"(d[17]),"+f"(d[18]),"+f"(d[19]),"+f"(d[20]),"+f"(d[21]),"+f"(d[22]),"+f"(d[23]),"+f"(d[24]),"+f"(d[25]),"+f"(d[26]),"+f"(d[27]),"+f"(d[28]),"+f"(d[29]),"+f"(d[30]),"+f"(d[31]),"+f"(d[32]),"+f"(d[33]),"+f"(d[34]),"+f"(d[35]),"+f"(d[36]),"+f"(d[37]),"+f"(d[38]),"+f"(d[39]),"+f"(d[40]),"+f"(d[41]),"+f"(d[42]),"+f"(d[43]),"+f"(d[44]),"+f"(d[45]),"+f"(d[46]),"+f"(d[47]),"+f"(d[48]),"+f"(d[49]),"+f"(d[50]),"+f"(d[51]),"+f"(d[52]),"+f"(d[53]),"+f"(d[54]),"+f"(d[55]),"+f"(d[56]),"+f"(d[57]),"+f"(d[58]),"+f"(d[59]),"+f"(d[60]),"+f"(d[61]),"+f"(d[62]),"+f"(d[63]),"+f"(d[64]),"+f"(d[65]),"+f"(d[66]),"+f"(d[67]),"+f"(d[68]),"+f"(d[69]),"+f"(d[70]),"+f"(d[71]),"+f"(d[72]),"+f"(d[73]),"+f"(d[74]),"+f"(d[75]),"+f"(d[76]),"+f"(d[77]),"+f"(d[78]),"+f"(d[79]) : "l"(da),"l"(db),"r"(sc));
}
__device__ __forceinline__ void wg_ss96_01(float* d, uint64_t da, uint64_t db, int sc) {
  asm volatile("{.reg .pred p; setp.ne.b32 p, %50, 0; wgmma.mma_async.sync.aligned.m64n96k16.f32.bf16.bf16 {%0,%1,%2,%3,%4,%5,%6,%7,%8,%9,%10,%11,%12,%13,%14,%15,%16,%17,%18,%19,%20,%21,%22,%23,%24,%25,%26,%27,%28,%29,%30,%31,%32,%33,%34,%35,%36,%37,%38,%39,%40,%41,%42,%43,%44,%45,%46,%47}, %48, %49, p, 1, 1, 0, 1;}"
    : "+f"(d[0]),"+f"(d[1]),"+f"(d[2]),"+f"(d[3]),"+f"(d[4]),"+f"(d[5]),"+f"(d[6]),"+f"(d[7]),"+f"(d[8]),"+f"(d[9]),"+f"(d[10]),"+f"(d[11]),"+f"(d[12]),"+f"(d[13]),"+f"(d[14]),"+f"(d[15]),"+f"(d[16]),"+f"(d[17]),"+f"(d[18]),"+f"(d[19]),"+f"(d[20]),"+f"(d[21]),"+f"(d[22]),"+f"(d[23]),"+f"(d[24]),"+f"(d[25]),"+f"(d[26]),"+f"(d[27]),"+f"(d[28]),"+f"(d[29]),"+f"(d[30]),"+f"(d[31]),"+f"(d[32]),"+f"(d[33]),"+f"(d[34]),"+f"(d[35]),"+f"(d[36]),"+f"(d[37]),"+f"(d[38]),"+f"(d[39]),"+f"(d[40]),"+f"(d[41]),"+f"(d[42]),"+f"(d[43]),"+f"(d[44]),"+f"(d[45]),"+f"(d[46]),"+f"(d[47]) : "l"(da),"l"(db),"r"(sc));
}
__device__ __forceinline__ void wg_ss64_01(float* d, uint64_t da, uint64_t db, int sc) {
  asm volatile("{.reg .pred p; setp.ne.b32 p, %34, 0; wgmma.mma_async.sync.aligned.m64n64k16.f32.bf16.bf16 {%0,%1,%2,%3,%4,%5,%6,%7,%8,%9,%10,%11,%12,%13,%14,%15,%16,%17,%18,%19,%20,%21,%22,%23,%24,%25,%26,%27,%28,%29,%30,%31}, %32, %33, p, 1, 1, 0, 1;}"
    : "+f"(d[0]),"+f"(d[1]),"+f"(d[2]),"+f"(d[3]),"+f"(d[4]),"+f"(d[5]),"+f"(d[6]),"+f"(d[7]),"+f"(d[8]),"+f"(d[9]),"+f"(d[10]),"+f"(d[11]),"+f"(d[12]),"+f"(d[13]),"+f"(d[14]),"+f"(d[15]),"+f"(d[16]),"+f"(d[17]),"+f"(d[18]),"+f"(d[19]),"+f"(d[20]),"+f"(d[21]),"+f"(d[22]),"+f"(d[23]),"+f"(d[24]),"+f"(d[25]),"+f"(d[26]),"+f"(d[27]),"+f"(d[28]),"+f"(d[29]),"+f"(d[30]),"+f"(d[31]) : "l"(da),"l"(db),"r"(sc));
}
__device__ __forceinline__ void wg_rs160_1(float* d, const uint32_t* a, uint64_t db, int sc) {
  asm volatile("{.reg .pred p; setp.ne.b32 p, %85, 0; wgmma.mma_async.sync.aligned.m64n160k16.f32.bf16.bf16 {%0,%1,%2,%3,%4,%5,%6,%7,%8,%9,%10,%11,%12,%13,%14,%15,%16,%17,%18,%19,%20,%21,%22,%23,%24,%25,%26,%27,%28,%29,%30,%31,%32,%33,%34,%35,%36,%37,%38,%39,%40,%41,%42,%43,%44,%45,%46,%47,%48,%49,%50,%51,%52,%53,%54,%55,%56,%57,%58,%59,%60,%61,%62,%63,%64,%65,%66,%67,%68,%69,%70,%71,%72,%73,%74,%75,%76,%77,%78,%79}, {%80,%81,%82,%83}, %84, p, 1, 1, 1;}"
    : "+f"(d[0]),"+f"(d[1]),"+f"(d[2]),"+f"(d[3]),"+f"(d[4]),"+f"(d[5]),"+f"(d[6]),"+f"(d[7]),"+f"(d[8]),"+f"(d[9]),"+f"(d[10]),"+f"(d[11]),"+f"(d[12]),"+f"(d[13]),"+f"(d[14]),"+f"(d[15]),"+f"(d[16]),"+f"(d[17]),"+f"(d[18]),"+f"(d[19]),"+f"(d[20]),"+f"(d[21]),"+f"(d[22]),"+f"(d[23]),"+f"(d[24]),"+f"(d[25]),"+f"(d[26]),"+f"(d[27]),"+f"(d[28]),"+f"(d[29]),"+f"(d[30]),"+f"(d[31]),"+f"(d[32]),"+f"(d[33]),"+f"(d[34]),"+f"(d[35]),"+f"(d[36]),"+f"(d[37]),"+f"(d[38]),"+f"(d[39]),"+f"(d[40]),"+f"(d[41]),"+f"(d[42]),"+f"(d[43]),"+f"(d[44]),"+f"(d[45]),"+f"(d[46]),"+f"(d[47]),"+f"(d[48]),"+f"(d[49]),"+f"(d[50]),"+f"(d[51]),"+f"(d[52]),"+f"(d[53]),"+f"(d[54]),"+f"(d[55]),"+f"(d[56]),"+f"(d[57]),"+f"(d[58]),"+f"(d[59]),"+f"(d[60]),"+f"(d[61]),"+f"(d[62]),"+f"(d[63]),"+f"(d[64]),"+f"(d[65]),"+f"(d[66]),"+f"(d[67]),"+f"(d[68]),"+f"(d[69]),"+f"(d[70]),"+f"(d[71]),"+f"(d[72]),"+f"(d[73]),"+f"(d[74]),"+f"(d[75]),"+f"(d[76]),"+f"(d[77]),"+f"(d[78]),"+f"(d[79]) : "r"(a[0]),"r"(a[1]),"r"(a[2]),"r"(a[3]),"l"(db),"r"(sc));
}
__device__ __forceinline__ void wg_ss8_10(float* d, uint64_t da, uint64_t db, int sc) {
  asm volatile("{.reg .pred p; setp.ne.b32 p, %6, 0; wgmma.mma_async.sync.aligned.m64n8k16.f32.bf16.bf16 {%0,%1,%2,%3}, %4, %5, p, 1, 1, 1, 0;}"
    : "+f"(d[0]),"+f"(d[1]),"+f"(d[2]),"+f"(d[3]) : "l"(da),"l"(db),"r"(sc));
}

constexpr uint32_t DB = 1024;
constexpr int WSLOT = 24576, NW = 6, ASLOT = 8192, ARING = 4 * ASLOT;
constexpr int OFF_A = NW * WSLOT;
constexpr int OFF_PB = OFF_A + 2 * ARING;
constexpr int OFF_CV = OFF_PB + 16384, OFF_ST = OFF_CV + 768, OFF_TS = OFF_ST + 256, OFF_MODR = OFF_TS + 512, OFF_BAR = OFF_MODR + 80, SMEM_BYTES = OFF_BAR + 1168;
constexpr int OFF_BX = OFF_PB, OFF_AX = OFF_BX + 12288, OFF_RT = OFF_AX + 2048, OFF_GB = OFF_RT + 512, OFF_CO = OFF_CV;
constexpr int OFF_UV = 5 * WSLOT, OFF_UVE = OFF_PB, OFF_SX = OFF_A + ARING + 3 * ASLOT, OFF_X1 = 2 * WSLOT + ASLOT, OFF_XCH = WSLOT;
constexpr int OFF_Q = 0, KV_V = 4096, KV_H = 8192, F_E = 16, F_O = 4176, OFF_WM = 3 * WSLOT, OFF_TAP = 168576, OFF_MR = OFF_A + 3 * ASLOT;
constexpr uint64_t pk5(int a, int b, int c, int d, int e) { return (uint64_t)(a / 128) | (uint64_t)(b / 128) << 12 | (uint64_t)(c / 128) << 24 | (uint64_t)(d / 128) << 36 | (uint64_t)(e / 128) << 48; }
constexpr uint64_t T_KV = pk5(20480, 30720, 40960, 180224, 190464), T_F = pk5(51200, 59648, 200192, 147456, 155904), T_X = pk5(208512, 164352, 68096, 208512, 164352),
                   T_P = pk5(131072, OFF_PB, 114688, 131072, OFF_PB);
__host__ __device__ __forceinline__ uint32_t tab(uint64_t t, int c) { return ((uint32_t)(t >> (12 * c)) & 0xFFF) << 7; }
enum { B_KV = 0, B_FRAW = 5, B_Q = 10, B_WM = 15, B_XR, B_MR = B_XR + 5, B_QTOK, B_ST1, B_MODR, B_S3 = B_MODR + 5, B_FIN, B_FL = 32, B_PFULL = B_FL + 5, B_PEMPTY = B_PFULL + 5, B_FRDY = B_PEMPTY + 5,
       B_G3 = B_FRDY + 5, B_EXT, B_QTD, B_LAG, B_GB, B_UVD, B_TURN, B_FULL = 60, B_RETRY = B_FULL + 33, B_XFREE = B_RETRY + 9, B_BX, B_UVB, B_UVE, B_SX, B_EMPTY = 109 };
static_assert(B_MODR + 5 <= B_FL && B_UVD < B_FULL && B_SX + 2 == B_EMPTY - 1, "barrier groups");
#define BAR(i) (base + OFF_BAR + 8 * (i))

constexpr int NE = 24;
struct Maps { CUtensorMap km, v, q, kh, tap, wm, w1s, w3s, xs, w1, w3, w1e, w3e, x1s, x1b, w2a, w2b, outa, outb; };
struct Ptrs { const bf16 *ssmk, *c, *ssmd; Scratch* g; uint64_t prog, cprog[2]; int boff, te, pe, th, wms, ulo, uhi; uint32_t c0, fin, turn, mr2, m3, seq; float one; uint2 sched[NE]; uint32_t wdep[20], wt[5]; uint2 w2t[12]; int hid[3][9]; };

#define REGION_IDS int tid, lane, bid; \
  asm volatile("mov.u32 %0, %%tid.x;" : "=r"(tid)); asm volatile("mov.u32 %0, %%laneid;" : "=r"(lane)); asm volatile("mov.u32 %0, %%ctaid.x;" : "=r"(bid)); \
  const int i0 = tid & 127; (void)i0; (void)lane; (void)bid

__device__ __forceinline__ void ffn_role(int& h, int& j, int& r) {
  uint32_t b;
  asm volatile("mov.u32 %0, %%ctaid.x;" : "=r"(b));
  const uint32_t c = b >> 1, q = (c - 36) * 37 >> 8, e = c - 36 - 7 * q;
  h = b & 1;
  const uint32_t k = c < 4 ? 0 : c < 36 ? (c - 4) & 7 : e + 1, p = c < 4 ? c : c < 36 ? (c - 4) >> 3 : q, up = c - 4 >= 32;
  j = 2 * (k & 1) + up;
  r = 2 * (k & 6) + p;
}
__device__ __forceinline__ int fslice(int j, int e) { return e == 2 ? j ^ 1 : (~j & 2) + e; }
__device__ __forceinline__ int mod_ch(int p) { return p < 40 ? (p >> 3) * 128 + (p & 1) * 64 : 64 * (p < 50 ? p - 40 : p - 50); }
__device__ __forceinline__ int mod_col(int p) { return mod_ch(p) + 640 * (p < 40 ? 0x4210 >> (2 * (p & 6)) & 7 : p < 50 ? 3 : 5); }
__device__ __forceinline__ uint32_t mod_sum(uint2 v) { return pack_bf16(0.f, __uint_as_float(v.x) + __uint_as_float(v.y)); }

constexpr int NT = 3, LAG2 = 29, MG = 4;
__device__ __forceinline__ int w_block(int up, int m) { return m == 1 ? 2 + 3 * up : 3 * (m >> 1) + up; }
__host__ __device__ constexpr int w2_at(int v) { return 8192 * (v ? 0x0613030008ull >> v % 5 * 8 & 255 : 15); }
__host__ __device__ constexpr int w2_step(int v) { return 8192 * (v ? 0x32113 >> v % 5 * 4 & 15 : 1); }
__host__ __device__ constexpr int hid_at(int m, int g) { return 8192 * ((g ? 0x0D07110F1816ull : 0x0A19101A1412ull) >> m % 6 * 8 & 255); }
__host__ __device__ constexpr uint32_t w2_desc(int v) { return (DB + w2_at(v)) >> 4 | w2_step(v) << 12; }
__device__ __forceinline__ int next_slot(int s) { return s >= 4 * WSLOT ? 0 : s + WSLOT; }

template <int U> __device__ __forceinline__ void cstep(float* acc, const uint32_t* A, uint64_t db) {
  const uint32_t* a = A + 4 * U;
  const uint64_t d = db + 16 * U;
  if (U == 4) { wg_rs64_0(acc + 96, A, db + 192, 0); wg_rs48_0(acc + 96, A + 4, db + 208, 1); wg_rs32_0(acc + 96, A + 8, db + 224, 1); wg_rs16_0(acc + 96, A + 12, db + 240, 1); }
  if (U <= 4) wg_rs192_0(acc, a, d, U);
  if (U == 5) wg_rs176_0(acc, a, d, 1);
  if (U == 6) wg_rs160_0(acc, a, d, 1);
  if (U == 7) wg_rs144_0(acc, a, d, 1);
  if (U == 8) wg_rs128_0(acc, a, d, 1);
  if (U == 9) wg_rs112_0(acc, a, d, 1);
  if (U == 10) wg_rs96_0(acc, a, d, 1);
  if (U == 11) wg_rs80_0(acc, a, d, 1);
  if (U == 12) wg_rs64_0(acc, a, d, 1);
  if (U == 13) wg_rs48_0(acc, a, d, 1);
  if (U == 14) wg_rs32_0(acc, a, d, 1);
  if (U == 15) wg_rs16_0(acc, a, d, 1);
}
template <int U0, int U1> __device__ __forceinline__ void csteps(float* acc, const uint32_t* A, uint64_t db) {
  cstep<U0>(acc, A, db);
  if constexpr (U0 > U1) csteps<U0 - 1, U1>(acc, A, db);
}
template <int U0, int U1> __device__ __forceinline__ void cload(uint32_t* A, uint32_t fa) {
  asm volatile("{ld.shared.b32 %0, [%4+%5]; ld.shared.b32 %1, [%4+%5+128]; ld.shared.b32 %2, [%4+%5+16]; ld.shared.b32 %3, [%4+%5+144];}"
               : "=r"(A[4 * U0]), "=r"(A[4 * U0 + 1]), "=r"(A[4 * U0 + 2]), "=r"(A[4 * U0 + 3]) : "r"(fa), "n"(256 * U0) : "memory");
  if constexpr (U0 > U1) cload<U0 - 1, U1>(A, fa);
}

__device__ __forceinline__ void mod_gemv(Scratch* G, uint32_t wm, int unit, int w, int lane, uint32_t par) {
  float d[4] = {};
  fence_regs(d);
  wg_fence();
#pragma unroll 1
  for (int k = 0; k < 20; k += 2) {
    wg_ss8_10(d, mkdesc(DB + wm + 2048 * k, 16, 1024, 1), mkdesc(DB + OFF_CV + 32 * k, 16, 128, 0), 1);
    wg_ss8_10(d, mkdesc(DB + wm + 2048 * k + 2048, 16, 1024, 1), mkdesc(DB + OFF_CV + 32 * k + 32, 16, 128, 0), 1);
  }
  wg_commit();
  const int p = unit >> 1, ch = mod_ch(p) + 16 * w + (lane >> 2);
  uint32_t* dst = (uint32_t*)(p < 40 ? &G->modc[ch & 127][8 + (p >> 1)] : &G->modv[p >= 50][ch]) + (unit & 1);
  wg_wait<0>();
  fence_regs(d);
  if (!(lane & 3)) {
    publish(dst, (__float_as_uint(d[0]) & ~1u) | par);
    publish(dst + (p < 40 ? 512 : 16), (__float_as_uint(d[2]) & ~1u) | par);
    if (p < 40 && (p & 6) == 6) {
      dst = (uint32_t*)&G->modv[2][ch] + (unit & 1);
      publish(dst, (__float_as_uint(d[0]) & ~1u) | par);
      publish(dst + 16, (__float_as_uint(d[2]) & ~1u) | par);
    }
  }
}
__device__ __forceinline__ uint2 c_load(const bf16* c) {
  REGION_IDS;
  return make_uint2(ldg32(c + 320 * (bid & 1) + 2 * i0), ldg32(c + 320 * (bid & 1) + 256 + 2 * lane));
}
__device__ __forceinline__ void silu_vector(uint2 c, uint32_t base) {
  REGION_IDS;
  sts32(base + OFF_CV + 4 * i0, pack_bf16(silu_f(bf_lo(c.x)), silu_f(bf_hi(c.x))));
  sts32(base + OFF_CV + 512 + 4 * lane, pack_bf16(silu_f(bf_lo(c.y)), silu_f(bf_hi(c.y))));
  fence_async_smem();
}

__device__ __forceinline__ void mod_poll(Scratch* G, uint32_t base, int c, int n, uint32_t epoch) {
  REGION_IDS;
  const int e = 4 * c + (lane & (4 * n - 1));
  uint2 m;
  int it = 0;
#pragma unroll 1
  do m = ld_relaxed64(&G->modc[bid][8 + e]); while (__any_sync(~0u, ((m.x ^ epoch) | (m.y ^ epoch)) & 1) && ++it < SPIN_LIMIT);
  sts32(base + OFF_MODR + 4 * e, __byte_perm(badd2(mod_sum(m), (lane & 1) * 0x3F800000u), 0, 0x3232));
  __syncwarp();
  if (elect()) { mbar_arrive(BAR(B_MODR + c)); if (n > 1) mbar_arrive(BAR(B_MODR + c + 1)); }
}
__device__ __forceinline__ void row_stats(Scratch* G, uint32_t base, uint32_t epoch) {
  REGION_IDS;
  mbar_wait_cluster(BAR(B_ST1));
  if (lane < 8) red_hint(G->hint[5][lane]);
  const uint2 x = lds64(base + OFF_ST + 8 * (lane & 15)), y = lds64(base + OFF_ST + 128 + 8 * (lane & 15));
  float m, sd;
  ln_final(__uint_as_float(x.x) + __uint_as_float(y.x), __uint_as_float(x.y) + __uint_as_float(y.y), m, sd);
  sd = rbf(rcpf(sd));
  const uint32_t mr = pack_bf16(sd, -rbf(m) * sd), tg = lane & 7 ? 0 : lane & 8 ? 1 : 0x8000;
  const uint32_t o = __byte_perm(__shfl_sync(~0u, mr, 2 * lane & 14), __shfl_sync(~0u, mr, (2 * lane & 14) + 1), (lane & 8) ? 0x7632 : 0x5410);
  if (lane < 16) st_relaxed32(&G->st1[lane >> 3][8 * bid + (lane & 7)], (o & ~tg) | ((epoch & 1) * tg));
  if (elect()) mbar_arrive(BAR(B_FIN));
}
template <int B, int NEXT> __device__ __forceinline__ void strip(Scratch* G, const CUtensorMap* map, uint32_t base, int c, uint32_t epoch, uint32_t& ph, uint32_t& pre, float4& s) {
  REGION_IDS;
  int h, j, r, it = 0;
  ffn_role(h, j, r);
  const uint32_t buf = base + OFF_SX + 4096 * B, a = buf + 32 * lane;
#pragma unroll 1
  while (__any_sync(~0u, pre != 64 * epoch) && ++it < SPIN_LIMIT) pre = ld_relaxed32(G->xsh[c][(r & 6) + (j >> 1)]);
#pragma unroll 1
  for (it = 0; it < SPIN_LIMIT; it++) {
    if (elect()) { mbar_expect_tx(BAR(B_SX + B), 4096); tma2d(buf, map, 128 * r + 64 * h, D_ * (epoch & 1) + 128 * c + 32 * j, BAR(B_SX + B)); }
    mbar_wait(BAR(B_SX + B), ph);
    ph ^= 1;
    if (__all_sync(~0u, min(min(lds32(a), lds32(a + 1024)), min(lds32(a + 2048), lds32(a + 3072))))) break;
  }
  pre = 0;
  if (c == NEXT - 1 || c == NEXT - 2) pre = ld_relaxed32(G->xsh[c + 1][(r & 6) + (j >> 1)]);
#pragma unroll 1
  for (uint32_t o = buf + 4 * lane; o < buf + 4096; o += 1024) {
    uint32_t x[8];
#pragma unroll
    for (int i = 0; i < 8; i++) x[i] = lds32(o + 128 * i);
#pragma unroll
    for (int i = 0; i < 8; i++) { const float lo = bf_lo(x[i]), hi = bf_hi(x[i]); s.x += lo; s.y = fmaf(lo, lo, s.y); s.z += hi; s.w = fmaf(hi, hi, s.w); }
  }
}
__device__ __forceinline__ void planes(uint32_t a, uint4& y) {
  uint4 z = lds128(a + 4096);
  y.x = badd2(y.x, z.x); y.y = badd2(y.y, z.y); y.z = badd2(y.z, z.z); y.w = badd2(y.w, z.w);
  z = lds128(a + 8192);
  const uint4 m = lds128(a + 12288);
  y.x = badd2(y.x, badd2(z.x, m.x)); y.y = badd2(y.y, badd2(z.y, m.y)); y.z = badd2(y.z, badd2(z.z, m.z)); y.w = badd2(y.w, badd2(z.w, m.w));
}
__device__ __forceinline__ void mr_poll(Scratch* G, uint32_t base, uint32_t epoch) {
  int it = 0;
#pragma unroll 1
  while (__any_sync(~0u, ld_relaxed32(G->hint[5][4 * (blockIdx.x >> 6) + (blockIdx.x >> 3 & 3)]) != epoch << 7) && ++it < SPIN_LIMIT);
  if (elect()) { mbar_expect_tx(BAR(B_MR), 8192); bulk_load(base + OFF_MR, G->st1, 8192, BAR(B_MR)); mbar_arrive(BAR(B_QTOK)); }
}

__global__ void __cluster_dims__(2, 1, 1) __launch_bounds__(512, 1) k_fused(const __grid_constant__ Ptrs P, const __grid_constant__ Maps maps) {
  Scratch* const G = P.g;
  extern __shared__ __align__(1024) uint8_t smem_raw[];
  const uint32_t t_start = clock();
  const uint32_t base = __shfl_sync(~0u, smem_u32(smem_raw), 0);
  uint32_t t_iss = 0;
  if (threadIdx.x < 32 && blockIdx.x < 128) {
    mbar_init<1>(BAR(0), 1);
    if (elect()) {
      const int c0 = 64 * (blockIdx.x & 1), c1 = 2 * (blockIdx.x & 126);
      mbar_expect_tx(BAR(B_KV), 12288);
      tma3d(base + tab(T_KV, 0), &maps.km, c0, c1, 0, BAR(B_KV));
      tma3d(base + tab(T_KV, 0) + KV_V, &maps.v, c0, c1, 0, BAR(B_KV));
      tma3d(base + tab(T_KV, 0) + KV_H, &maps.kh, c0, c1 - 1, 5, BAR(B_KV));
      tma3d(base + OFF_TAP, &maps.tap, 0, blockIdx.x & 1, 0, BAR(B_KV));
    }
    if (P.boff) mbar_wait(BAR(0));
  }
  if ((base & 0xFFFFFFu) != DB) __trap();
  const int wid = __shfl_sync(~0u, threadIdx.x >> 5, 0), wg = wid >> 2, w = wid & 3;
  if (blockIdx.x + P.boff >= 128) {
    REGION_IDS;
    const int nu = 30 - (P.uhi - P.ulo) / 4;
    auto tile = [&](int n) { return 2 * (n < P.ulo / 4 ? n : n + 30 - nu) + (blockIdx.x >> 1 & 1); };
    auto fetch = [&](int n, int b) {
      if (elect()) {
        mbar_expect_tx(BAR(n), 40960);
#pragma unroll
        for (int k = 0; k < 5; k++) tma3d(base + 40960 * b + 8192 * k, &maps.wm, mod_col(tile(n)), 320 * (blockIdx.x & 1) + 64 * k, 0, BAR(n));
      }
    };
    if (P.boff) __syncthreads();
    if (wid == 12) {
      mbar_init<4>(BAR(0), 1);
#pragma unroll 1
      for (int n = 0; n < 4; n++) fetch(n, n);
      mbar_init<26>(BAR(4), 1);
      mbar_init<60>(BAR(32), 4);
    }
    const uint32_t par = ~ld_relaxed32(G->hint[7][0]) >> 7 & 1;
    silu_vector(c_load(P.c), base);
    __syncthreads();
    if (wid == 12) {
      wait_clock(t_start + P.th);
#pragma unroll 1
      for (int n = 4, b = 4; n < nu; n++) {
        if (n >= 5) mbar_wait(BAR(27 + n));
        fetch(n, b);
        b = b == 4 ? 0 : b + 1;
      }
    } else if (wg < 2) {
      uint32_t cv[40];
#pragma unroll
      for (int k = 0; k < 40; k++) cv[k] = lds32(base + OFF_CV + 16 * k + 4 * (lane & 3));
      const uint32_t a0 = base + 128 * ((lane & 7) + (lane >> 4) * 8) + (((2 * w + (lane >> 3 & 1)) ^ (lane & 7)) << 4);
#pragma unroll 1
      for (int n = wg; n < nu; n += 2) {
        float d[16] = {};
        mbar_wait(BAR(n));
#pragma unroll
        for (int k0 = 0; k0 < 20; k0 += 10) {
          uint32_t a[40];
#pragma unroll
          for (int k = 0; k < 10; k++) ldmatrix_x4_t(a + 4 * k, a0 + 40960 * (n % 5) + 2048 * (k0 + k));
#pragma unroll
          for (int k = 0; k < 10; k++)
            asm("mma.sync.aligned.m16n8k16.row.col.f32.bf16.bf16.f32 {%0,%1,%2,%3}, {%4,%5,%6,%7}, {%8,%9}, {%0,%1,%2,%3};"
                : "+f"(d[4 * (k & 3)]), "+f"(d[4 * (k & 3) + 1]), "+f"(d[4 * (k & 3) + 2]), "+f"(d[4 * (k & 3) + 3])
                : "r"(a[4 * k]), "r"(a[4 * k + 1]), "r"(a[4 * k + 2]), "r"(a[4 * k + 3]), "r"(cv[2 * (k0 + k)]), "r"(cv[2 * (k0 + k) + 1]));
        }
        arrive1(BAR(32 + n));
        if (!(lane & 3)) {
          sts32(base + 204800 + 256 * n + 64 * w + lane, __float_as_uint(d[0] + d[4] + (d[8] + d[12])));
          sts32(base + 204800 + 256 * n + 64 * w + lane + 32, __float_as_uint(d[2] + d[6] + (d[10] + d[14])));
        }
        arrive1(BAR(62 + n));
      }
    } else if (wg == 2) {
#pragma unroll 1
      for (int n = w; n < nu; n += 4) {
        const int t = tile(n), ch = mod_ch(t) + lane;
        uint32_t* q = (uint32_t*)(t < 40 ? &G->modc[ch & 127][8 + (t >> 1)] : &G->modv[t >= 50][ch]) + (bid & 1);
        mbar_wait(BAR(62 + n));
        const uint32_t x = (lds32(base + 204800 + 256 * n + 4 * lane) & ~1u) | par, y = (lds32(base + 204928 + 256 * n + 4 * lane) & ~1u) | par;
        publish(q, x);
        publish(q + (t < 40 ? 2048 : 64), y);
        if (t < 40 && (t & 6) == 6) {
          q = (uint32_t*)&G->modv[2][ch] + (bid & 1);
          publish(q, x);
          publish(q + 64, y);
        }
      }
    }
    return;
  }
  if (wid < 15) mbar_init<4>(BAR(4 * wid + (wid == 0)), wid < 8 ? 1 : 4);
  asm volatile("fence.mbarrier_init.release.cluster; bar.sync 0, 512;" ::: "memory");
  asm volatile("barrier.cluster.arrive.relaxed.aligned;" ::: "memory");
  if (wid == 4) {
    const int c0 = 64 * (blockIdx.x & 1), c1 = 2 * (blockIdx.x & 126);
    wait_clock(t_start + P.te);
    if (elect()) { tma3d(base + tab(T_KV, 1), &maps.km, 128 + c0, c1, 0, BAR(B_KV + 1)); tma3d(base + tab(T_KV, 1) + KV_H, &maps.kh, 128 + c0, c1 - 1, 5, BAR(B_KV + 1)); }
    wait_clock(t_start + P.te + P.pe);
    if (elect()) tma3d(base + tab(T_KV, 1) + KV_V, &maps.v, 128 + c0, c1, 0, BAR(B_KV + 1));
    wait_clock(t_start + P.te + 2 * P.pe);
    if (elect()) bulk_load(base + tab(T_F, 0) + F_E, P.ssmk + blockIdx.x * S_, 4096, BAR(B_FRAW));
    wait_clock(t_start + P.te + 3 * P.pe);
    if (elect()) tma3d(base + OFF_Q, &maps.q, c0, c1, 0, BAR(B_Q));
  }
#define LAUNCHES const uint32_t launches = ld_relaxed32(G->hint[7][blockIdx.x >> 4])
#define EPOCH ((__shfl_sync(~0u, launches, 0) >> 7) + 1)
  if (wg == 3) {
    asm volatile("setmaxnreg.dec.sync.aligned.u32 24;");
    if (w == 1) {
      {
        REGION_IDS;
        const int c1 = 2 * (bid & 126), ws = bid >= P.ulo && bid < P.uhi ? P.wms : 99;
#pragma unroll 1
        for (int e = 4; e < NE; e++) {
          const uint2 x = P.sched[e];
          const uint32_t kind = x.x >> 16 & 15, ch = x.x >> 13 & 0x380, dst = base + (x.y & 0x3FFFF), b = BAR(x.y >> 18);
          wait_clock(t_start + (x.x & 0xFFFF));
          if (kind < 3 && elect()) tma3d(dst, &maps.km + kind, ch + 64 * (bid & 1), c1, 0, b);
          if (kind == 0 && elect()) tma3d(dst + KV_H, &maps.kh, ch + 64 * (bid & 1), c1 - 1, 5, b);
          if (kind == 3 && elect()) bulk_load(dst, P.ssmk + (ch + bid) * S_, 4096, b);
          if ((uint32_t)(e - ws) < 5 && elect()) tma3d(base + OFF_WM + 8192 * (e - ws), &maps.wm, mod_col(bid >> 1), 320 * (bid & 1) + 64 * (e - ws), 0, BAR(B_WM));
          if ((uint32_t)(e - 8) < 13 && elect()) prefetch_map(&maps.w1s + (e - 8));
        }
      }
      cluster_wait();
      int h, j, r;
      ffn_role(h, j, r);
      mbar_wait(BAR(B_QTD));
      mbar_wait(BAR(B_FL));
#pragma unroll 1
      for (int u = 0; u < 20; u++) {
        const uint32_t x = P.wdep[u], s = base + (x & ~8191u);
        if (u < 5) wait_clock(t_start + P.wt[u]);
        mbar_wait(BAR(opaque(x & 255)));
        if (elect()) {
          mbar_expect_tx(BAR(B_FULL + u), WSLOT + 4 * (x & 4096));
#pragma unroll
          for (int k = 0; k < 6; k++) tma3d(s + 4096 * w_block(k & 1, k >> 1), &maps.w1s + (k & 1), 0, 32 * u, 3 * (4 * h + j) + (k >> 1), BAR(B_FULL + u));
        }
      }
#pragma unroll 1
      for (int v = 0; v < 12; v++) {
        const int q = v * 11 >> 5, e = v - 3 * q, k32 = 24 * h + (q ? 6 * fslice(j, e) + 2 * q - 2 : 6 * j + 2 * e);
        const uint2 x = P.w2t[v];
        mbar_wait(BAR(x.y));
        if (elect()) {
          mbar_expect_tx(BAR(B_FULL + 20 + v), q ? WSLOT + 2 * ASLOT : WSLOT);
#pragma unroll
          for (int k = 0; k < 3; k++) tma5d(base - DB + 16 * ((x.x & 0xFFFF) + k * (x.x >> 16)), &maps.w2a + (q > 0), k < 2 ? 128 * j + 64 * k : 512 + 32 * (j & 2), k32, BAR(B_FULL + 20 + v));
        }
      }
    } else if (w == 0) {
      LAUNCHES;
      uint32_t epoch;
      {
        REGION_IDS;
        const unsigned* hp = G->hint[0][4 * (bid >> 6) + (bid >> 3 & 3)];
        uint32_t v = ld_relaxed32(hp + 256 * min(lane, 5));
        if (lane < 3) sts128(base + tab(T_X, lane) + 4096, 0, 0, 0, 0);
        if (lane && lane <= B_WM) mbar_expect_tx(BAR(lane), lane < B_FRAW ? 9728 : lane == B_WM ? 40960 : 4096);
        epoch = EPOCH;
        fence_async_smem();
        const uint32_t rdy = __ballot_sync(~0u, v == epoch << 6);
        uint32_t nx = 0, nm = 0;
#pragma unroll 1
        for (uint32_t seq = P.seq; seq; seq >>= 2) {
          int it = 0;
          if (seq & 1) {
            if (!(seq & 2)) mod_poll(G, base, nm, 1 + (seq == 13), epoch);
            nm++;
          } else if (seq & 2) {
            mr_poll(G, base, epoch);
          } else {
            if (!(rdy >> nx & 1)) {
#pragma unroll 1
              while (__any_sync(~0u, ld_relaxed32(hp + 256 * nx) != epoch << 6) && ++it < SPIN_LIMIT);
            }
            if (nx >= 3) mbar_wait(BAR(B_PFULL - 3 + nx));
            if (elect()) { mbar_expect_tx(BAR(B_XR + nx), 4096); bulk_load(base + tab(T_X, nx), G->xr + (128 * nx + bid) * 256, 4096, BAR(B_XR + nx)); }
            nx++;
          }
        }
      }
      REGION_IDS;
      int h, j, r;
      ffn_role(h, j, r);
      mbar_wait(BAR(B_G3));
      {
        const uint2* mp = &G->modv[lane & 4 ? 0 : 2][40 * (r & 14) + (lane & 24) + 2 * (lane & 3)];
        uint4 v[3];
        int it = 0;
#pragma unroll 1
        do {
          v[0] = ld_relaxed128(mp); v[1] = ld_relaxed128(mp + 32); v[2] = ld_relaxed128(mp + 64 - (lane & 16));
        } while (__any_sync(~0u, ((v[0].x ^ epoch) | (v[0].y ^ epoch) | (v[0].z ^ epoch) | (v[0].w ^ epoch) | (v[1].x ^ epoch) | (v[1].y ^ epoch) | (v[1].z ^ epoch) | (v[1].w ^ epoch) |
                                  (v[2].x ^ epoch) | (v[2].y ^ epoch) | (v[2].z ^ epoch) | (v[2].w ^ epoch)) & 1) && ++it < SPIN_LIMIT);
#pragma unroll
        for (int i = 0; i < 3; i++)
          sts32(base + OFF_CO + 128 * i + 4 * lane, badd2(pack_bf16(__uint_as_float(v[i].x) + __uint_as_float(v[i].y), __uint_as_float(v[i].z) + __uint_as_float(v[i].w)), lane & 4 ? 0 : 0x3F803F80u));
      }
      fence_async_smem();
      __syncwarp();
      ffn_role(h, j, r);
      mbar_wait(BAR(B_PEMPTY + 3));
      if (elect()) {
        mbar_expect_tx(BAR(B_UVB), WSLOT);
        tma3d(base + OFF_UV, &maps.w1 + (r & 1), 0, 40 * (r & 14), 3 * (4 * h + j), BAR(B_UVB));
        tma3d(base + OFF_UV + 12288, &maps.w1 + (r & 1), 0, 40 * (r & 14) + 32, 3 * (4 * h + j), BAR(B_UVB));
      }
      {
        float4 s = {};
        uint32_t ph = 0, pre = 0;
#pragma unroll 1
        for (int c = 2; c < 4; c++) strip<1, 3>(G, &maps.x1s, base, c, epoch, ph, pre, s);
        __syncwarp();
        sts128(base + OFF_SX + 4096 + 16 * lane, __float_as_uint(s.x), __float_as_uint(s.y), __float_as_uint(s.z), __float_as_uint(s.w));
        arrive1(BAR(B_S3));
      }
      ffn_role(h, j, r);
      cluster_wait();
      mbar_wait(BAR(B_UVD));
      asm volatile("fence.acq_rel.gpu;" ::: "memory");
      if (lane < 8) red_hint(G->hint[7][lane]);
      unsigned x;
      int it = 0;
#pragma unroll 1
      do { asm volatile("ld.acquire.gpu.global.u32 %0, [%1];" : "=r"(x) : "l"(G->hint[7][bid >> 4]) : "memory"); } while (__any_sync(~0u, x != 128 * epoch) && ++it < SPIN_LIMIT);
      fence_async_all();
      const int ch = D_ * (epoch & 1);
      mbar_wait(BAR(B_EXT));
      mbar_wait(BAR(B_EMPTY + 18));
      if (elect()) {
        mbar_expect_tx(BAR(B_FULL + 32), 20480);
#pragma unroll
        for (int k = 0; k < 4; k++) tma2d(base + (k < 3 ? OFF_X1 + k * WSLOT : OFF_SX), &maps.x1b, 128 * r + 64 * h, ch + 128 * j + 32 * (k ^ (j & 1)), BAR(B_FULL + 32));
        tma2d(base + OFF_SX + 4096, &maps.x1b, 128 * r + 64 * h, ch + 512 + 32 * j, BAR(B_FULL + 32));
        mbar_expect_tx(BAR(B_FULL), 8192); mbar_expect_tx(BAR(B_FULL + 1), 8192); mbar_expect_tx(BAR(B_FULL + 2), 4096);
      }
      mbar_wait(BAR(B_EMPTY + 27));
      if (elect()) mbar_arrive_remote(mapa(BAR(B_XFREE), h ^ 1));
    } else {
      LAUNCHES;
      uint32_t epoch;
      {
        REGION_IDS;
        uint32_t dv;
        asm volatile("ld.global.nc.u16 %0, [%1];" : "=r"(dv) : "l"(P.ssmd + 128 * (lane & 7) % D_ + bid));
        if (lane < 5) sts128(base + tab(T_F, lane) + (w & 1) * (F_O - 16), 0, 0, 0, 0);
        epoch = EPOCH;
        __syncwarp();
#pragma unroll 1
        for (int c = 0; c < 5; c++) {
          const float d = i0 == 64 ? bf_lo(dv) : 0.f;
          dv = __shfl_down_sync(~0u, dv, 1);
          const uint32_t a = base + tab(T_F, c) + 16 * (i0 - 64);
          mbar_wait(BAR(B_FRAW + c));
#pragma unroll
          for (int k = 0; k < 4; k++) {
            uint4 x = lds128(a + F_E + 1024 * k);
            const uint32_t pv = lds32(a + F_E - 4 + 1024 * k);
            if (k == 0) { x.x = pack_bf16(bf_lo(x.x) + d, bf_hi(x.x)); sts32(a + F_E, x.x); }
            sts128(a + F_O + 1024 * k, __byte_perm(pv, x.x, 0x5432), __byte_perm(x.x, x.y, 0x5432), __byte_perm(x.y, x.z, 0x5432), __byte_perm(x.z, x.w, 0x5432));
          }
          __syncwarp();
          if (elect()) mbar_arrive2(BAR(B_FRDY + c));
          if (c == 0 && w == P.fin) row_stats(G, base, epoch);
        }
      }
      REGION_IDS;
      int h, j, r;
      ffn_role(h, j, r);
      cluster_wait();
      if (w == 2) {
        const unsigned* fp = G->xsh[lane < 10 ? lane >> 1 : 0][(r & 6) + (lane & 1)];
        uint32_t rdy = 0, s = 0;
        mbar_wait(BAR(B_QTD));
        mbar_wait(BAR(B_FL + 2));
#pragma unroll 1
        for (int n = 0; n < 10; n++) {
          mbar_wait(BAR(n < 2 ? B_FL + 3 + n : n == 2 ? B_PFULL + 4 : B_EMPTY + 2 * n - 5));
#pragma unroll 1
          for (int it = 0; !(rdy >> n & 1) && it < SPIN_LIMIT; it++) rdy = __ballot_sync(~0u, ld_relaxed32(fp) == 64 * epoch);
          if (elect()) {
            tma2d(base + OFF_A + s, &maps.xs, 128 * r + 64 * h, 64 * n, BAR(B_FULL + 2 * n));
            tma2d(base + OFF_A + ARING + s, &maps.xs, 128 * r + 64 - 64 * h, 64 * n, BAR(B_FULL + 2 * n));
          }
          s = s == 2 * ASLOT ? 0 : s + ASLOT;
        }
      } else {
        if (P.m3 < 5) mod_poll(G, base, P.m3, 1, epoch);
        float4 s = {};
        uint32_t ph = 0, pre = 0;
        mbar_wait(BAR(B_FL + 2));
        mbar_wait(BAR(B_PFULL + 3));
#pragma unroll 1
        for (int c = 0; c < 5; c = c == 1 ? 4 : c + 1) {
          if (c == 4) {
            ffn_role(h, j, r);
            mbar_wait(BAR(B_PEMPTY + 4));
            if (elect()) {
              mbar_expect_tx(BAR(B_UVE), 6144);
              tma3d(base + OFF_UVE, &maps.w1e + (r & 1), 0, 40 * (r & 14) + 64, 3 * (4 * h + j), BAR(B_UVE));
            }
          }
          strip<0, 1>(G, &maps.x1s, base, c, epoch, ph, pre, s);
        }
        mbar_wait(BAR(B_S3));
        const uint4 y = lds128(base + OFF_SX + 4096 + 16 * lane);
        const float s0 = s.x + __uint_as_float(y.x), q0 = s.y + __uint_as_float(y.y), s1 = s.z + __uint_as_float(y.z), q1 = s.w + __uint_as_float(y.w);
        ffn_role(h, j, r);
        asm volatile("{.reg .b128 t, x; .reg .b64 a, b; mov.b64 a, {%1,%2}; mov.b64 b, {%3,%4}; mov.b128 x, {a,b}; atom.relaxed.gpu.global.exch.b128 t, [%0], x;}"
                     ::"l"(&G->st2[2 * r + h][j][4 * lane]), "r"((__float_as_uint(s0) & ~1u) | (epoch & 1)), "f"(q0), "r"((__float_as_uint(s1) & ~1u) | (epoch & 1)), "f"(q1) : "memory");
        uint4* z = G->x1[~epoch & 1] + 1280 * bid + lane;
#pragma unroll 1
        for (int k = 0; k < 40; k++) st_relaxed128(z + 32 * k, 0, 0, 0, 0);
      }
    }
  } else if (wg == 2) {
    asm volatile("setmaxnreg.dec.sync.aligned.u32 40;");
    mbar_init<12>(BAR(B_FULL + 12 * w), 1);
    mbar_init<9>(BAR(B_EMPTY - 1 + 9 * w), 8);
    asm volatile("fence.mbarrier_init.release.cluster;" ::: "memory");
    LAUNCHES;
    const uint32_t epoch = EPOCH;
    cluster_wait();
#pragma unroll 1
    for (uint64_t prog = P.prog; prog; prog >>= 4) {
      REGION_IDS;
      const int s = (prog & 7) - 1;
      if (!(prog & 8)) {
        const uint32_t a = base + tab(T_KV, s) + 128 * (lane & 3) + ((w ^ (lane & 3)) << 4) + 4 * (lane & 16) + (lane & 12), keep = ~(lane & 1), bit = epoch & lane & 1;
        uint4* dst = G->xr + (128 * s + 64 * (bid & 1) + 8 * w + 2 * (lane & 16) + (lane >> 1 & 6)) * 256 + 255 - 4 * (bid >> 1) - (lane & 3);
        mbar_wait(BAR(B_KV));
        mbar_wait(BAR(B_KV + s));
        const uint4 wv = lds128(base + OFF_TAP + 512 * s + 64 * w + 16 * (lane & 16) + 4 * (lane & 12));
        uint32_t kk[11], r[8];
#pragma unroll
        for (int k = 0; k < 11; k++) kk[k] = k < 3 ? lds32((a ^ (64 * (k & 1))) + KV_H + 512 * k) : lds32((a ^ (64 * (~k & 1))) + 512 * (k - 3));
        if (elect()) red_hint(G->hint[s][4 * (bid & 1) + w]);
#pragma unroll
        for (int k = 0; k < 8; k++) r[k] = lds32((a ^ (64 * (k & 1))) + KV_V + 512 * k);
        const uint32_t w0 = __byte_perm(wv.x, wv.z, 0x5410), w1 = __byte_perm(wv.x, wv.z, 0x7632),
                       w2 = __byte_perm(wv.y, wv.w, 0x5410), w3 = __byte_perm(wv.y, wv.w, 0x7632);
#pragma unroll
        for (int k = 0; k < 8; k++) r[k] = bmul2(bfma2(kk[k + 3], w0, bfma2(kk[k + 2], w1, bfma2(kk[k + 1], w2, bmul2(kk[k], w3)))), r[k]);
        st_relaxed128(dst, (__byte_perm(r[7], r[6], 0x5410) & keep) | bit, __byte_perm(r[5], r[4], 0x5410), __byte_perm(r[3], r[2], 0x5410), __byte_perm(r[1], r[0], 0x5410));
        st_relaxed128(dst + 256, (__byte_perm(r[7], r[6], 0x7632) & keep) | bit, __byte_perm(r[5], r[4], 0x7632), __byte_perm(r[3], r[2], 0x7632), __byte_perm(r[1], r[0], 0x7632));
      } else if (s == 5) {
        mbar_wait(BAR(B_PFULL));
#pragma unroll
        for (int hf = 0; hf < 2; hf++) {
          const uint32_t a = base + tab(T_P, 0) + 16 * i0 + 2048 * hf;
          uint4 y = lds128(a);
          planes(a, y);
          sts128(a, y.x, y.y, y.z, y.w);
        }
      } else if (s >= 0) {
        const int tr = 4 * (lane & 1) + (lane >> 1 & 3);
        const uint32_t a = base + OFF_Q + 4096 * s + 128 * ((lane & 24) + tr) + ((w ^ tr) << 4);
        uint4* dst = G->qt + (128 * s + 64 * (bid & 1) + 8 * w + (lane >> 2)) * 256 + 4 * (bid >> 1) + (lane & 3);
        mbar_wait(BAR(B_Q + s));
#pragma unroll
        for (int k = 0; k < 2; k++) {
          uint32_t x[4];
          ldmatrix_x4_t(x, a ^ (64 * k));
          st_relaxed128(dst + 8192 * k, set_tag(x[0], ~lane & 1, epoch), x[1], x[2], x[3]);
        }
      } else if (w == 3) {
        row_stats(G, base, epoch);
      }
    }
    arrive1(BAR(B_QTD));
    {
      REGION_IDS;
      const uint32_t tag = opaque(~lane & 1);
      const uint32_t io = 16 * i0;
      uint4* gp = (uint4*)((char*)(G->xs + 256 * blockIdx.x) + io);
      constexpr int QO = -D_ * 256;
      const uint32_t sa = base + io;
      uint4 q[2];
      if (w == 0 && P.mr2) mr_poll(G, base, epoch);
      mbar_wait(BAR(B_QTOK));
      q[0] = ld_relaxed128(gp + QO);
      q[1] = ld_relaxed128(gp + QO + 128);
#pragma unroll 1
      for (int it = 0; it < SPIN_LIMIT; it++) {
        mbar_wait(BAR(B_MR), it & 1);
        const uint32_t x = lds32(sa + 16 * i0 + OFF_MR), y = lds32(sa + 16 * i0 + OFF_MR + 4096);
        sts32(sa + 16 * i0 + OFF_MR, x & 0xFFFF7FFFu);
        if (bar_all(3, !(((x >> 15 ^ epoch) | (y ^ epoch)) & 1))) break;
        if (w == 0 && elect()) { fence_async_smem(); mbar_expect_tx(BAR(B_MR), 8192); bulk_load(base + OFF_MR, G->st1, 8192, BAR(B_MR)); }
      }
#pragma unroll 1
      for (int c = 0; c < 5; c++) {
        mbar_wait(BAR(B_MODR + c));
        uint4 co = lds128(base + OFF_MODR + 16 * c);
        co.x = bmul2(co.x, co.z); co.y = bmul2(co.y, co.z);
        mbar_wait(BAR(B_PFULL + c));
        const uint32_t pb = io + (base + tab(T_P, c));
        gp = (uint4*)((char*)(G->xs + 256 * blockIdx.x + 32768 * c) + io);
#pragma unroll
        for (int hf = 0; hf < 2; hf++) {
#pragma unroll 1
          for (int it = 0; __any_sync(~0u, set_tag(q[hf].x, tag, epoch) != q[hf].x) && it < SPIN_LIMIT; it++) {
            q[hf] = ld_relaxed128(gp + QO + 128 * hf);
          }
          uint4 y = lds128(pb + 2048 * hf);
          if (c) planes(pb + 2048 * hf, y);
          const uint4 z = lds128(sa + OFF_MR + 2048 * hf), m = lds128(sa + OFF_MR + 2048 * hf + 4096);
          y.x = bfma2(bfma2(bfma2(q[hf].x, z.x, m.x), co.y, co.x), y.x, q[hf].x);
          if (hf) {
            __syncwarp();
            asm volatile("{.reg .pred p; elect.sync _|p, 0xffffffff; @p red.relaxed.gpu.global.add.u32 [%0], 1; @p mbarrier.arrive.shared::cta.b64 _, [%1];}"
                         ::"l"(G->xsh[c][2 * w + (blockIdx.x >> 6)]), "r"(BAR(B_PEMPTY + c)), "r"(y.x) : "memory");
          }
          y.y = bfma2(bfma2(bfma2(q[hf].y, z.y, m.y), co.y, co.x), y.y, q[hf].y);
          y.z = bfma2(bfma2(bfma2(q[hf].z, z.z, m.z), co.y, co.x), y.z, q[hf].z);
          y.w = bfma2(bfma2(bfma2(q[hf].w, z.w, m.w), co.y, co.x), y.w, q[hf].w);
          st_relaxed128(gp + 128 * hf, set_tag(bmul2(y.x, co.w), tag, epoch), bmul2(y.y, co.w), bmul2(y.z, co.w), bmul2(y.w, co.w));
          asm volatile("{.reg .pred p; .reg .b32 t; setp.ne.u32 p, %5, 0; max.u32 t, %1, 1; @!p st.relaxed.gpu.global.v4.u32 [%0+%6], {t,%2,%3,%4}; @p st.relaxed.gpu.global.v4.u32 [%0+%7], {t,%2,%3,%4};}"
                       ::"l"(gp + 128 * hf), "r"(y.x), "r"(y.y), "r"(y.z), "r"(y.w), "r"(epoch & 1), "n"(D_ * 4096), "n"(D_ * 8192) : "memory");
          if (c < 4) q[hf] = ld_relaxed128(gp + QO + 32768 + 128 * hf);
        }
      }
    }
    int h, j, r;
    ffn_role(h, j, r);
    {
      REGION_IDS;
      mbar_wait(BAR(B_UVB));
      float d[12] = {};
      fence_regs(d);
      wg_fence();
#pragma unroll
      for (int k = 0; k < 15; k++) {
        if (k == 12) { wg_commit(); mbar_wait(BAR(B_UVE)); wg_fence(); }
        wg_ss8_10(d + 4 * (k % 3), mkdesc(DB + (k < 12 ? OFF_UV + 12288 * (k / 6) + 4096 * (k % 3) + 2048 * (k / 3 & 1) : OFF_UVE + 2048 * (k % 3)), 16, 1024, 1),
                  mkdesc(DB + OFF_CO + 64 * (k / 3), 32, 128, 0), 1);
      }
      wg_commit();
      const int row = (r & 14) + (lane >> 2 & 1);
      uint32_t* dst = &G->uv[4 * h + j][32 * row + 4 * ((2 * w ^ row) & 6) + (lane & 3)];
      const uint32_t tag = !(lane & 3);
      wg_wait<0>();
      fence_regs(d);
      if (elect()) { red_hint(G->hint[8][4 * h + j]); mbar_arrive(BAR(B_UVD)); }
      uint32_t x[6];
#pragma unroll
      for (int k = 0; k < 6; k++) asm volatile("movmatrix.sync.aligned.m8n8.trans.b16 %0, %1;" : "=r"(x[k]) : "r"(pack_bf16(d[2 * k], d[2 * k + 1])));
      if (lane < 8) {
#pragma unroll
        for (int k = 0; k < 6; k++) st_relaxed32(dst + 512 * w_block(r & 1, k >> 1) + ((4 * k ^ lane) & 4), set_tag(x[k], tag, epoch));
      }
    }
    {
      REGION_IDS;
      if (w == 0) {
        int it = 0;
#pragma unroll 1
        while (__any_sync(~0u, ld_relaxed32(G->hint[8][4 * h + j]) != 64 * epoch) && ++it < SPIN_LIMIT);
        if (elect()) { mbar_expect_tx(BAR(B_BX), 12288); bulk_load(base + OFF_BX, G->uv[4 * h + j], 12288, BAR(B_BX)); }
      }
      const uint32_t* sp = &G->st2[2 * r + (h ^ (w >> 1))][0][2 * (i0 & 63)];
      uint2 x[4];
      int it = 0;
#pragma unroll 1
      do {
#pragma unroll
        for (int k = 0; k < 4; k++) x[k] = ld_relaxed64(sp + 128 * k);
      } while (__any_sync(~0u, ((x[0].x ^ epoch) | (x[1].x ^ epoch) | (x[2].x ^ epoch) | (x[3].x ^ epoch)) & 1) && ++it < SPIN_LIMIT);
      float m, sd;
      ln_final((__uint_as_float(x[0].x) + __uint_as_float(x[1].x)) + (__uint_as_float(x[2].x) + __uint_as_float(x[3].x)),
               (__uint_as_float(x[0].y) + __uint_as_float(x[1].y)) + (__uint_as_float(x[2].y) + __uint_as_float(x[3].y)), m, sd);
      const uint32_t e = pack_bf16(-m, sd);
      sts128(base + OFF_AX + 16 * i0, e, e, e, e);
      sts32(base + OFF_RT + 4 * i0, __float_as_uint(rcpf(sd)));
      fence_async_smem();
#pragma unroll 1
      for (it = 0; it < SPIN_LIMIT; it++) {
        mbar_wait(BAR(B_BX), it & 1);
        uint32_t y = 0;
#pragma unroll
        for (int k = 0; k < 6; k++) y |= lds32(base + OFF_BX + 16 * i0 + 2048 * k) ^ epoch;
        if (bar_all(3, !(y & 1))) break;
        if (w == 0 && elect()) { mbar_expect_tx(BAR(B_BX), 12288); bulk_load(base + OFF_BX, G->uv[4 * h + j], 12288, BAR(B_BX)); }
      }
      arrive1(BAR(B_EXT));
      {
        uint2 g0, g1;
        int it = 0;
#pragma unroll 1
        do {
          g0 = ld_relaxed64(&G->modv[1][128 * j + i0]);
          g1 = ld_relaxed64(&G->modv[1][512 + 32 * j + lane]);
        } while (__any_sync(~0u, ((g0.x ^ epoch) | (g0.y ^ epoch) | (g1.x ^ epoch) | (g1.y ^ epoch)) & 1) && ++it < SPIN_LIMIT);
        const uint32_t ga = base + OFF_GB + 80 * (lane >> 1 & 3) + 2 * (lane & 1) + (lane >> 3) * 4;
        asm volatile("st.shared.u16 [%0], %1;" ::"r"(ga + 16 * (w ^ (j & 1))), "h"((uint16_t)(mod_sum(g0) >> 16)) : "memory");
        asm volatile("st.shared.u16 [%0], %1;" ::"r"(ga + 64), "h"((uint16_t)(mod_sum(g1) >> 16)) : "memory");
        arrive1(BAR(B_GB));
      }
      const int id = 16 * r + 4 * h + fslice(j, w);
      const unsigned* fp = &G->hhf[8 * id + 64 * (lane & 1)];
#pragma unroll 1
      for (int q = w == 3 ? 3 : 0; q < 3; q++) {
        const int m = 3 * q + w;
        const uint4* src = G->hh + id * 1536 + 512 * q;
        it = 0;
#pragma unroll 1
        while (__any_sync(~0u, ld_relaxed32(fp + q) != 4 * epoch) && ++it < SPIN_LIMIT);
        mbar_wait(BAR(P.hid[2][m]));
        if (elect()) {
          bulk_load(base + OFF_A + h * ARING + P.hid[h][m], src, ASLOT, BAR(B_FULL + 23 + m));
          bulk_load(base + OFF_A + ARING - h * ARING + P.hid[h ^ 1][m], src + 8 * 1536, ASLOT, BAR(B_FULL + 23 + m));
        }
      }
    }
  } else {
    asm volatile("setmaxnreg.inc.sync.aligned.u32 224;");
    LAUNCHES;
    if (wg == 1 && blockIdx.x >= P.ulo && blockIdx.x < P.uhi) silu_vector(c_load(P.c), base);
    uint32_t par = EPOCH & 1;
    cluster_wait();
    {
      float acc[128];
      uint32_t A[64];
#pragma unroll
      for (int i = 0; i < 64; i++) A[i] = 0;
      int c = wg;
#pragma unroll 1
      for (uint64_t prog = P.cprog[wg]; prog; prog >>= 8) {
        REGION_IDS;
        const int s = prog & 7;
        if (s < 5) {
          const uint32_t a = base + tab(T_KV, s) + 128 * (lane & 3) + ((w ^ (lane & 3)) << 4) + 4 * (lane & 16) + (lane & 12), keep = ~(lane & 1), bit = par & lane;
          uint4* dst = G->xr + (128 * s + 64 * (bid & 1) + 8 * w + 2 * (lane & 16) + (lane >> 1 & 6)) * 256 + 255 - 4 * (bid >> 1) - (lane & 3);
          mbar_wait(BAR(B_KV));
          mbar_wait(BAR(B_KV + s));
          const uint4 wv = lds128(base + OFF_TAP + 512 * s + 64 * w + 16 * (lane & 16) + 4 * (lane & 12));
          uint32_t kk[11], r[8];
#pragma unroll
          for (int k = 0; k < 11; k++) kk[k] = k < 3 ? lds32((a ^ (64 * (k & 1))) + KV_H + 512 * k) : lds32((a ^ (64 * (~k & 1))) + 512 * (k - 3));
          if (elect()) red_hint(G->hint[s][4 * (bid & 1) + w]);
#pragma unroll
          for (int k = 0; k < 8; k++) r[k] = lds32((a ^ (64 * (k & 1))) + KV_V + 512 * k);
          const uint32_t w0 = __byte_perm(wv.x, wv.z, 0x5410), w1 = __byte_perm(wv.x, wv.z, 0x7632),
                         w2 = __byte_perm(wv.y, wv.w, 0x5410), w3 = __byte_perm(wv.y, wv.w, 0x7632);
#pragma unroll
          for (int k = 0; k < 8; k++) r[k] = bmul2(bfma2(kk[k + 3], w0, bfma2(kk[k + 2], w1, bfma2(kk[k + 1], w2, bmul2(kk[k], w3)))), r[k]);
          st_relaxed128(dst, (__byte_perm(r[7], r[6], 0x5410) & keep) | bit, __byte_perm(r[5], r[4], 0x5410), __byte_perm(r[3], r[2], 0x5410), __byte_perm(r[1], r[0], 0x5410));
          st_relaxed128(dst + 256, (__byte_perm(r[7], r[6], 0x7632) & keep) | bit, __byte_perm(r[5], r[4], 0x7632), __byte_perm(r[3], r[2], 0x7632), __byte_perm(r[1], r[0], 0x7632));
        }
        if (prog & 8) {
          float s0 = 0.f, s1 = 0.f, q0 = 0.f, q1 = 0.f;
          const uint32_t a = OFF_Q + 1024 * w + 128 * (lane & 7) + (((lane >> 3) ^ (lane & 7)) << 4);
          const uint32_t ra = mapa(base + OFF_ST + 128 * (bid & 1) + 64 * (lane & 1) + 16 * w + 8 * (lane >> 2), lane >> 1 & 1), rb = mapa(BAR(B_ST1), lane >> 1 & 1);
          if (w == 3 && elect()) mbar_expect_tx(BAR(B_ST1), 256);
#pragma unroll 1
          for (int k = 0; k < 5; k++) {
            mbar_wait(BAR(B_Q + k));
            const uint32_t o = opaque(base + 4096 * k);
            const uint4 x = lds128(o + a), y = lds128(o + (a ^ 64));
            const uint32_t e[8] = {x.x, x.y, x.z, x.w, y.x, y.y, y.z, y.w};
#pragma unroll
            for (int i = 0; i < 8; i++) { const float lo = bf_lo(e[i]), hi = bf_hi(e[i]); s0 += lo; s1 += hi; q0 = fmaf(lo, lo, q0); q1 = fmaf(hi, hi, q1); }
          }
          s0 += s1; q0 += q1;
          s0 += __shfl_xor_sync(~0u, s0, 8); q0 += __shfl_xor_sync(~0u, q0, 8);
          s0 += __shfl_xor_sync(~0u, s0, 16); q0 += __shfl_xor_sync(~0u, q0, 16);
          if (lane < 8) asm volatile("st.async.shared::cluster.mbarrier::complete_tx::bytes.v2.b32 [%0], {%1,%2}, [%3];" ::"r"(ra), "r"(__float_as_uint(s0)), "r"(__float_as_uint(q0)), "r"(rb) : "memory");
        }
        if (prog & 32) {
          const int L = 16 * w + (lane >> 2) + 2 * (lane & 3) - 7;
          const uint32_t fo = base + ((L & 1) ? F_O + 2 * (L + 1) : F_E + 2 * L);
          mbar_wait(BAR(B_FRDY + c));
          cload<0, 0>(A, fo + tab(T_F, c));
          cload<15, 1>(A, fo + tab(T_F, c));
          arrive1(BAR(B_FL + c));
        }
        if (!(prog & 64)) continue;
        uint32_t xo;
        if (P.turn >> c & 1) mbar_wait(BAR(B_TURN - 3 + c));
        if (c == 0) mbar_wait(BAR(P.c0));
#pragma unroll 1
        for (int it = 0; it < SPIN_LIMIT; it++) {
          xo = tab(T_X, opaque(c));
          mbar_wait(BAR(B_XR + c), it & 1);
          const uint32_t tag = lds32(base + xo + 32 * i0);
          wg_fence();
          csteps<0, 0>(acc, A, mkdesc(DB + xo, 16, 128, 0));
          csteps<15, 6>(acc, A, mkdesc(DB + xo, 16, 128, 0));
          wg_commit();
          if (bar_all(1 + wg, !((tag ^ par) & 1))) break;
          wg_wait<0>();
          if (w == 0 && elect()) { mbar_expect_tx(BAR(B_XR + c), 4096); bulk_load(base + xo, G->xr + (128 * c + bid) * 256, 4096, BAR(B_XR + c)); }
        }
        wg_fence();
        csteps<5, 1>(acc, A, mkdesc(DB + tab(T_X, opaque(c)), 16, 128, 0));
        wg_commit();
        if (c >= 2 && c < 4 && elect()) mbar_arrive(BAR(B_TURN - 2 + c));
        if (c >= 3) mbar_wait(BAR(B_PEMPTY + c - 3));
        wg_wait<0>();
        fence_regs(acc);
        const uint32_t pb = base + tab(T_P, c) + 4096 * w;
#pragma unroll
        for (int k = 0; k < 8; k++) {
          uint32_t p[4];
#pragma unroll
          for (int e = 0; e < 4; e++) { const int i = 4 * k + e; p[e] = i < 31 ? pack_bf16(acc[4 * i] + acc[4 * i + 6], acc[4 * i + 1] + acc[4 * i + 7]) : pack_bf16(acc[124], acc[125]); }
          if (k == 0 && (lane & 3) < w) p[0] = 0;
          stmatrix_x4_t(k == 0 ? pb + 16 * ((255 - lane + 2 * w) & 255) : pb + 16 * (255 - lane + 2 * w) - 512 * k, p[0], p[1], p[2], p[3]);
        }
        arrive1(BAR(B_PFULL + c));
        c += 2;
      }
    }
    if (wg) {
      REGION_IDS;
      if (bid >= P.ulo && bid < P.uhi) {
        named_bar(2, 128);
        mbar_wait(BAR(B_WM));
        mod_gemv(G, OFF_WM, bid, w, lane, par);
      }
      arrive1(BAR(B_G3));
    }
    uint32_t ck;
    { REGION_IDS; ck = base + OFF_A + wg * ARING + lane * 128 + (((2 * w) ^ (lane & 7)) << 4); }
    const uint32_t abd = DB + OFF_A + wg * ARING;
    auto a_tile = [&](int as, int n, bool first) {
#pragma unroll 1
      for (int it = 0; __any_sync(~0u, ((lds32(ck + as) ^ par) | (lds32(ck + as + (first ? 4096 : 256)) ^ par)) & 1) && it < SPIN_LIMIT; it++) {
        int h, j, r;
        ffn_role(h, j, r);
        if (elect()) {
          const uint32_t dst = base + OFF_A + wg * ARING + as;
          mbar_expect_tx(BAR(B_RETRY + wid), ASLOT);
          if (first) tma2d(dst, &maps.xs, 128 * r + 64 * (h ^ wg), 64 * n, BAR(B_RETRY + wid));
          else bulk_load(dst, G->hh + ((2 * r + (h ^ wg)) * 8 + 4 * h + fslice(j, n % 3)) * 1536 + (n / 3) * 512, ASLOT, BAR(B_RETRY + wid));
        }
        mbar_wait(BAR(B_RETRY + wid), par >> 1);
        par ^= 2;
      }
    };
    float acc[192];
    int ws = 0, as = 0;
#pragma unroll 1
    for (int u = 0; u < 20 - NT; u++) {
      mbar_wait(BAR(B_FULL + u));
      if (!(u & 1)) a_tile(as, u >> 1, true);
      wg_fence();
#pragma unroll
      for (int k = 0; k < 4; k++) wg_ss192_11(acc + 96 * (k & 1), mkdesc(abd + as + k / 2 * 2048, 16, 1024, 1), mkdesc(DB + ws + 12288 * (k & 1) + k / 2 * 2048, 4096, 1024, 1), u + k / 2);
      wg_commit();
      wg_wait<1>();
      if (elect()) mbar_arrive(BAR(B_EMPTY + u - 1));
      ws = next_slot(ws);
      as = as == 5 * ASLOT / 2 ? 0 : as + ASLOT / 2;
    }
    auto tail = [&](int v, int i) {
      const int u = 20 - NT + i / 2;
      if (i < 2 * NT) wg_ss192_11(acc + 96 * v, mkdesc(opaque(abd) + u % 6 * 4096 + (i & 1) * 2048, 16, 1024, 1), mkdesc(DB + u % 5 * WSLOT + (i & 1) * 2048 + 12288 * v, 4096, 1024, 1), 1);
      if (i == 2 * NT) wg_ss192_01(acc + 96 * v, mkdesc(DB + OFF_AX + 1024 * opaque(wg), 0, 128, 0), mkdesc(DB + OFF_BX + 6144 * v, 2048, 1024, 1), 1);
    };
#pragma unroll
    for (int u = 20 - NT; u <= 20; u++) {
      mbar_wait(BAR(u < 20 ? B_FULL + u : B_EXT));
      if (u == 16 || u == 18) a_tile(u % 6 * 4096, u >> 1, true);
      wg_fence();
      tail(0, 2 * (u + NT - 20));
      tail(0, 2 * (u + NT - 20) + 1);
      wg_commit();
      if (u == 20 - NT) { wg_wait<1>(); if (elect()) mbar_arrive(BAR(B_EMPTY + u - 1)); }
    }
    float o[80];
    uint32_t fr[3][16], bo;
    {
      int h, j, r;
      ffn_role(h, j, r);
      REGION_IDS;
      const float r0 = 0.5f * __uint_as_float(lds32(base + OFF_RT + 256 * wg + 64 * w + (lane & 28))), r1 = 0.5f * __uint_as_float(lds32(base + OFF_RT + 256 * wg + 64 * w + 32 + (lane & 28)));
      const int id = (2 * r + (h ^ wg)) * 8 + 4 * h + j;
      uint4* const hdst = G->hh + id * 1536 + 128 * w + (lane ^ lane >> 3);
      const uint32_t keep = ~(~lane & 1), bit = par & ~keep;
      bo = 1024 + ((j & 1) << 23);
      auto own = [&](int i) { wg_rs160_1(o, fr[i >> 2] + 4 * (i & 3), mkdesc(DB + (5 + i / 4) % 6 * WSLOT + (i & 3) * 2048, 8192, bo, 1), i); };
      auto gate = [&](float* g, int d) {
#pragma unroll
        for (int e = 0; e < 4; e++) { g[e] *= e < 2 ? r0 : r1; g[e + d] *= g[e]; asm("tanh.approx.f32 %0, %0;" : "+f"(g[e])); }
      };
      auto mix = [&](uint32_t* x, const float* g, int d) {
        x[0] = pack_bf16(fmaf(g[d], g[0], g[d]), fmaf(g[d + 1], g[1], g[d + 1]));
        x[1] = pack_bf16(fmaf(g[d + 2], g[2], g[d + 2]), fmaf(g[d + 3], g[3], g[d + 3]));
      };
      auto hint = [&](int v) { asm volatile("{.reg .pred p; setp.eq.u32 p, %1, 0; @p red.relaxed.gpu.global.add.u32 [%0], 1;}" ::"l"(&G->hhf[id * 8 + v]), "r"(lane) : "memory"); };
      auto put = [&](int v, int k) {
        uint32_t* x = fr[v] + 2 * k;
        const uint32_t t0 = (x[k / 2] & keep) | bit, t1 = (x[5 + k / 2] & keep) | bit;
        if (!v) { x[k / 2] = t0; x[5 + k / 2] = t1; }
        st_relaxed128(hdst + 512 * v + 8 * k, k ? x[0] : t0, k ? t0 : x[2], x[4], x[6]);
        st_relaxed128(hdst + 512 * v + 8 * k + 64, x[1], x[3], k ? x[5] : t1, k ? t1 : x[7]);
      };
      auto move = [&](uint32_t* x) {
#pragma unroll
        for (int k = 0; k < 16; k++) asm volatile("mul.rn.f32 %0, %0, %1;" : "+r"(x[k]) : "f"(P.one));
      };
      wg_fence();
      tail(1, 0);
      tail(1, 1);
      wg_commit();
      wg_wait<1>();
#pragma unroll
      for (int k = 0; k < 96; k++) asm volatile("" : "+f"(acc[k])::"memory");
      if (elect()) mbar_arrive(BAR(B_EMPTY + 18));
      gate(acc + 28, 32);
#pragma unroll
      for (int k = 7; k >= 0; k--) {
        if (k >= 8 - 2 * NT) split(P.ulo, k);
        if (k > 8 - 2 * NT) tail(1, 9 - k);
        if (k == 9 - 2 * NT) wg_commit();
        if (k) gate(acc + 4 * k - 4, 32);
        mix(fr[0] + 2 * k, acc + 4 * k, 32);
        if (k == 1) hint(0);
        if (!(k & 3)) put(0, k);
      }
      move(fr[0]);
      split(P.ulo, 14);
      wg_wait<0>();
#pragma unroll
      for (int k = 96; k < 192; k++) asm volatile("" : "+f"(acc[k])::"memory");
      if (elect()) mbar_arrive(BAR(B_EMPTY + 19));
#pragma unroll
      for (int k = 7; k >= 0; k--) gate(acc + 64 + 4 * k, 96);
      mbar_wait(BAR(B_FULL + 20));
      mbar_wait(BAR(B_FULL + 21));
#pragma unroll
      for (int k = 7; k >= 0; k--) mix(fr[1] + 2 * k, acc + 64 + 4 * k, 96);
#pragma unroll
      for (int k = 0; k < 4; k++) pin4(P.ulo, fr[1] + 4 * k);
      wg_fence();
      own(0);
      own(1);
      split(P.ulo, 15);
      put(1, 4);
      hint(1);
      own(2);
      put(1, 0);
      own(3);
      wg_commit();
      gate(acc + 124, 32);
#pragma unroll
      for (int k = 7; k >= 0; k--) {
        if (k & 1 || k == 6) split(P.ulo, 16 + k);
        if (!(k & 1)) own(7 - k / 2);
        if (k == 4 || k == 0) wg_commit();
        if (k == 4) { wg_wait<1>(); if (elect()) mbar_arrive(BAR(B_EMPTY + 20)); }
        if (k) gate(acc + 92 + 4 * k, 32);
        mix(fr[2] + 2 * k, acc + 96 + 4 * k, 32);
        if (k == 1) hint(2);
        if (!(k & 3)) put(2, k);
      }
      mbar_wait(BAR(B_FULL + 22));
      wg_fence();
#pragma unroll
      for (int i = 8; i < 12; i++) own(i);
      wg_commit();
      wg_wait<1>();
      if (elect()) mbar_arrive(BAR(B_EMPTY + 21));
      ck = base + OFF_A + wg * ARING + 2048 * w + 516 * (lane >> 3) + 144 * (lane >> 2 & 1) + 32 * (lane & 3);
    }
    uint32_t x1[40];
    if (!wg) {
      REGION_IDS;
      const uint32_t xa = base + (lane >> 4) * 1024 + (lane & 7) * 128 + (((2 * w + ((lane >> 3) & 1)) ^ (lane & 7)) << 4);
      mbar_wait(BAR(B_FULL + 32));
#pragma unroll
      for (int k = 0; k < 10; k++) ldmatrix_x4_t(x1 + 4 * k, xa + (k < 6 ? OFF_X1 + k / 2 * WSLOT + (k & 1) * 2048 : OFF_SX + 2048 * (k - 6)));
    }
#pragma unroll 1
    for (int u = 23; u < (wg ? 32 : LAG2); u++) {
      as = P.hid[wg][u - 23];
      const uint64_t wd = mkdesc(0, 0, bo, 1) | P.w2t[u - 20].x;
      mbar_wait(BAR(B_FULL + u));
      a_tile(as, u - 23, false);
      wg_fence();
#pragma unroll
      for (int kk = 0; kk < 4; kk++) wg_ss160_01(o, mkdesc(abd + as + kk / 2 * 512 + (kk & 1) * 32, 16, 1024, 2), wd + kk * 128, 1);
      wg_commit();
      if (u == 31 && elect()) mbar_arrive(BAR(B_LAG));
      wg_wait<1>();
      if (elect()) mbar_arrive(BAR(B_EMPTY + u - 1));
    }
    int h, j, r;
    ffn_role(h, j, r);
    REGION_IDS;
    const uint32_t xb = base + OFF_XCH + 5120 * w;
    if (wg) {
      const uint32_t rdst = mapa(xb + 16 * lane, h ^ 1), rbar = mapa(BAR(B_FULL), h ^ 1);
      mbar_wait(BAR(B_XFREE));
      wg_wait<0>();
      fence_regs(o);
#pragma unroll
      for (int k = 0; k < 10; k++)
        asm volatile("st.async.shared::cluster.mbarrier::complete_tx::bytes.v4.b32 [%0], {%1,%2,%3,%4}, [%5];" ::"r"(rdst + 512 * k), "r"(pack_bf16(o[8 * k], o[8 * k + 1])),
                     "r"(pack_bf16(o[8 * k + 2], o[8 * k + 3])), "r"(pack_bf16(o[8 * k + 4], o[8 * k + 5])), "r"(pack_bf16(o[8 * k + 6], o[8 * k + 7])), "r"(rbar + 8 * (k / 4)) : "memory");
    } else {
      uint32_t gr[40];
      const float r0 = __uint_as_float(lds32(base + OFF_RT + 64 * w + (lane & 28))), r1 = __uint_as_float(lds32(base + OFF_RT + 64 * w + 32 + (lane & 28)));
      const uint32_t p0 = pack_bf16(r0, r0), p1 = pack_bf16(r1, r1), q0 = pack_bf16(r0 - bf_lo(p0), r0 - bf_lo(p0)), q1 = pack_bf16(r1 - bf_lo(p1), r1 - bf_lo(p1));
      mbar_wait(BAR(B_GB));
#pragma unroll
      for (int k = 0; k < 5; k++) {
        const uint4 g = lds128(base + OFF_GB + 80 * (lane & 3) + 16 * k);
        gr[8 * k] = g.x; gr[8 * k + 2] = g.y; gr[8 * k + 4] = g.z; gr[8 * k + 6] = g.w;
      }
      auto scale = [&](int k) {
#pragma unroll
        for (int e = 4 * k; e < 4 * k + 4; e += 2) { gr[e + 1] = bfma2(gr[e], p1, bmul2(gr[e], q1)); gr[e] = bfma2(gr[e], p0, bmul2(gr[e], q0)); }
      };
#pragma unroll
      for (int k = max(127 - 4 * LAG2, 0); k < 10; k++) scale(k);
      wg_wait<0>();
      if (elect()) mbar_arrive(BAR(B_EMPTY + LAG2 - 1));
#pragma unroll 1
      for (int u = LAG2; u < 32; u++) {
        mbar_wait(BAR(B_FULL + u));
        a_tile(P.hid[0][u - 23], u - 23, false);
      }
      auto da = [&](int i) { return mkdesc(DB + hid_at(i / 4 + LAG2 - 23, 0) + (i & 2) * 256 + (i & 1) * 32, 16, 1024, 2); };
      auto db = [&](int i, int b) { return mkdesc(DB + w2_at(i / 4 + LAG2 - 20) + b * w2_step(i / 4 + LAG2 - 20) + (i & 3) * 2048, w2_step(i / 4 + LAG2 - 20), bo, 1); };
      const int row = 128 * r + 64 * h + 16 * w;
      auto merge = [&](int e) {
        if (e % 4 == 0) mbar_wait_cluster(BAR(B_FULL + e / 4), 1);
        const uint4 p = lds128(xb + 16 * lane + 512 * e);
        x1[4 * e] = bfma2(gr[4 * e], p.x, x1[4 * e]); x1[4 * e + 1] = bfma2(gr[4 * e + 1], p.y, x1[4 * e + 1]);
        x1[4 * e + 2] = bfma2(gr[4 * e + 2], p.z, x1[4 * e + 2]); x1[4 * e + 3] = bfma2(gr[4 * e + 3], p.w, x1[4 * e + 3]);
      };
      auto out = [&](int k) {
        const float* v = o + 8 * k;
        uint32_t y[4];
#pragma unroll
        for (int e = 0; e < 4; e++) y[e] = bfma2(gr[4 * k + e], pack_bf16(v[2 * e], v[2 * e + 1]), x1[4 * k + e]);
        stmatrix_x4(k < 8 ? xb + 2048 * (k >> 2) + (lane & 15) * 128 + (((2 * (k & 3) + (lane >> 4)) ^ (lane & 7) ^ 4 * (j & 1)) << 4)
                          : xb + 4096 + (lane & 15) * 64 + (((2 * (k & 1) + (lane >> 4)) ^ (lane >> 1 & 3)) << 4), y[0], y[1], y[2], y[3]);
        if ((k & 3) == 3 || k == 9) {
          fence_async_smem();
          __syncwarp();
          if (lane == 0) tma2d_store(k < 8 ? &maps.outa : &maps.outb, k < 8 ? 128 * j + 64 * (k >> 2) : 512 + 32 * j, row, xb + 2048 * (k >> 2));
        }
      };
      constexpr int ND = 128 - 4 * LAG2;
      mbar_wait(BAR(B_LAG));
      wg_fence();
#pragma unroll
      for (int i = 0; i < ND; i++) {
        wg_ss160_01(o, da(i), db(i, 0), 1);
        if (i >= 1 && i <= 10) { scale(i - 1); split(P.ulo, 32 + i); }
      }
      wg_commit();
#pragma unroll
      for (int e = 0; e < MG; e++) merge(e);
      __syncwarp();
      wg_wait<0>();
      fence_regs(o);
#pragma unroll
      for (int k = 0; k < 10; k++) {
        if (k >= MG && k % 4 == 0) {
#pragma unroll
          for (int e = k; e < min(k + 4, 10); e++) merge(e);
          __syncwarp();
        }
        out(k);
      }
      if (lane == 0) { bulk_commit(); bulk_wait_read(); }
    }
  }
}

typedef CUresult (*EncFn)(CUtensorMap*, CUtensorMapDataType, cuuint32_t, void*, const cuuint64_t*, const cuuint64_t*, const cuuint32_t*,
                          const cuuint32_t*, CUtensorMapInterleave, CUtensorMapSwizzle, CUtensorMapL2promotion, CUtensorMapFloatOOBfill);
static int enc_err = 0;
static void enc(EncFn fn, CUtensorMap* m, const void* p, int rank, const cuuint64_t* gd, const cuuint64_t* gs, const cuuint32_t* bd, CUtensorMapSwizzle sw) {
  cuuint32_t es[5] = {1, 1, 1, 1, 1};
  enc_err = 2 * enc_err + (fn(m, CU_TENSOR_MAP_DATA_TYPE_BFLOAT16, rank, (void*)p, gd, gs, bd, es, CU_TENSOR_MAP_INTERLEAVE_NONE, sw,
                              CU_TENSOR_MAP_L2_PROMOTION_L2_128B, CU_TENSOR_MAP_FLOAT_OOB_FILL_NONE) != CUDA_SUCCESS);
}

extern "C" void kernel_launch(void* const* d_in, const int* in_sizes, int n_in, void* d_out, int out_size) {
  const bf16 *q = (const bf16*)d_in[0], *k = (const bf16*)d_in[1], *v = (const bf16*)d_in[2], *shift = (const bf16*)d_in[3],
             *ssmk = (const bf16*)d_in[4], *ssmd = (const bf16*)d_in[5], *w1 = (const bf16*)d_in[7], *w3 = (const bf16*)d_in[8],
             *w2 = (const bf16*)d_in[9], *c = (const bf16*)d_in[10], *wmod = (const bf16*)d_in[11];
  EncFn fn = nullptr;
  cudaDriverEntryPointQueryResult qr;
  cudaGetDriverEntryPoint("cuTensorMapEncodeTiled", (void**)&fn, cudaEnableDefault, &qr);
  Scratch* pg;
  cudaGetSymbolAddress((void**)&pg, g_s);
  Maps maps;
  enc_err = 0;
  const CUtensorMapSwizzle S128 = CU_TENSOR_MAP_SWIZZLE_128B;
  { cuuint64_t gd[3] = {D_, S_ / 8, 8}, gs[2] = {D_ * 16, D_ * 2}; cuuint32_t b[3] = {64, 4, 8};
    enc(fn, &maps.km, k, 3, gd, gs, b, S128);
    enc(fn, &maps.v, v, 3, gd, gs, b, S128);
    enc(fn, &maps.q, q, 3, gd, gs, b, S128);
    b[2] = 3;
    enc(fn, &maps.kh, k, 3, gd, gs, b, S128); }
  { cuuint64_t gd[3] = {256, 2, 5}, gs[2] = {512, 1024}; cuuint32_t b[3] = {256, 1, 5};
    enc(fn, &maps.tap, shift, 3, gd, gs, b, CU_TENSOR_MAP_SWIZZLE_NONE); }
  { cuuint64_t gd[3] = {6 * D_, D_, 1}, gs[2] = {6 * D_ * 2, 6 * D_ * 2 * D_}; cuuint32_t b[3] = {64, 64, 1};
    enc(fn, &maps.wm, wmod, 3, gd, gs, b, S128); }
  { cuuint64_t gd[3] = {64, D_, F_ / 64}, gs[2] = {F_ * 2, 128}; cuuint32_t b[3] = {64, 32, 3};
    enc(fn, &maps.w1, w1, 3, gd, gs, b, S128);
    enc(fn, &maps.w3, w3, 3, gd, gs, b, S128);
    b[1] = 16;
    enc(fn, &maps.w1e, w1, 3, gd, gs, b, S128);
    enc(fn, &maps.w3e, w3, 3, gd, gs, b, S128);
    b[1] = 32; b[2] = 1;
    enc(fn, &maps.w1s, w1, 3, gd, gs, b, S128);
    enc(fn, &maps.w3s, w3, 3, gd, gs, b, S128); }
  { cuuint64_t gd[2] = {S_, D_}, gs[1] = {S_ * 2}; cuuint32_t b1[2] = {64, 64}, b2[2] = {64, 32};
    enc(fn, &maps.xs, pg->xs, 2, gd, gs, b1, S128);
    gd[1] = 2 * D_;
    enc(fn, &maps.x1b, pg->x1, 2, gd, gs, b2, S128);
    enc(fn, &maps.x1s, pg->x1, 2, gd, gs, b2, CU_TENSOR_MAP_SWIZZLE_NONE); }
  { cuuint64_t gd[5] = {D_, 2, 4, 4, 48}, gs[4] = {D_ * 2, D_ * 4, D_ * 16, D_ * 64}; cuuint32_t b[5] = {64, 2, 4, 4, 2};
    enc(fn, &maps.w2a, w2, 5, gd, gs, b, S128);
    gs[1] = D_ * 16; gs[2] = D_ * 4;
    enc(fn, &maps.w2b, w2, 5, gd, gs, b, S128); }
  { cuuint64_t gd[2] = {D_, S_}, gs[1] = {D_ * 2}; cuuint32_t b1[2] = {64, 16}, b2[2] = {32, 16};
    enc(fn, &maps.outa, d_out, 2, gd, gs, b1, S128);
    enc(fn, &maps.outb, d_out, 2, gd, gs, b2, CU_TENSOR_MAP_SWIZZLE_64B); }
  if (enc_err) return;
  cudaFuncSetAttribute(k_fused, cudaFuncAttributeMaxDynamicSharedMemorySize, SMEM_BYTES);
  cudaLaunchConfig_t cfg = {132, 512, SMEM_BYTES};
  cudaLaunchAttribute at = {cudaLaunchAttributeClusterDimension};
  at.val.clusterDim.x = 2; at.val.clusterDim.y = at.val.clusterDim.z = 1;
  cfg.attrs = &at; cfg.numAttrs = 1;
  int nc = 0;
  cudaOccupancyMaxActiveClusters(&nc, k_fused, &cfg);
  Ptrs P = {ssmk, c, ssmd, pg, 0x4E8DCBA9ull, {0x676760, 0x64620F01}, 0, 700, 420, 5000, 19, 64, 80, B_KV, 0, 0, 1, 1, 0x57010, 1.f};
  const char* sched = "k10v14f04q04q14q24q34q44k24v24f14k34v34f24k44v44f34f44n04n02n04n06n06n06";
  int t = 700, pace = 420;
  for (int e = 0; e < NE; e++) {
    const char x = sched[3 * e];
    const int r = sched[3 * e + 1] - '0', kind = x == 'k' ? 0 : x == 'v' ? 1 : x == 'q' ? 2 : x == 'f' ? 3 : 4;
    t += (sched[3 * e + 2] - '0') * pace / 4;
    P.sched[e] = make_uint2(t | kind << 16 | r << 20, (kind < 2 ? tab(T_KV, r) + kind * KV_V : kind == 2 ? OFF_Q + 4096 * r : tab(T_F, r) + F_E) | (r + (kind < 2 ? B_KV : kind == 2 ? B_Q : B_FRAW)) << 18);
  }
  for (int u = 0; u < 5; u++) P.wt[u] = 9000 + 700 * u;
  const int dep[5] = {B_FL + 1, B_FL + 2, B_PFULL + 2, B_G3, B_PEMPTY + 2};
  for (int u = 0; u < 20; u++) P.wdep[u] = u % 5 * WSLOT | (~u & 1) << 12 | (u < 5 ? dep[u] : B_EMPTY + u - 5);
  for (int v = 0; v < 12; v++) P.w2t[v] = make_uint2(w2_desc(v), v ? B_EMPTY + (v > 5 ? 15 + v : v > 3 ? 14 + v : v > 1 ? 16 : 15) : B_UVD);
  for (int m = 0; m < 9; m++) { P.hid[0][m] = hid_at(m, 0) - OFF_A; P.hid[1][m] = hid_at(m, 1) - OFF_A - ARING; P.hid[2][m] = B_EMPTY + 19 + (m > 2 ? m : m / 2); }
  if (nc < 66) { P.boff = 128; k_fused<<<4, 512, SMEM_BYTES, cudaStreamPerThread>>>(P, maps); P.boff = 0; }
  k_fused<<<nc < 66 ? 128 : 132, 512, SMEM_BYTES, cudaStreamPerThread>>>(P, maps);
}
```

```cpp
#include <cuda_runtime.h>
#include <cuda.h>
#include <cuda_bf16.h>
#include <stdint.h>
#include <stdlib.h>

typedef __nv_bfloat16 bf16;
constexpr int S_ = 2048, D_ = 640, F_ = 1536;

struct Scratch {
  uint32_t st1[2][1024];
  uint32_t st2[32][4][128];
  uint2 modc[128][32];
  uint2 modv[3][D_];
  uint32_t uv[8][3072];
  unsigned hint[9][8][32];
  unsigned xsh[5][8][32], hhf[256 * 8];
  uint4 xr[D_ * 256];
  uint4 qt[D_ * 256];
  uint4 xs[D_ * 256];
  uint4 x1[2][D_ * 256];
  uint4 hh[32 * 8 * 1536];
};
__device__ __align__(1024) Scratch g_s;

__device__ __forceinline__ uint32_t smem_u32(const void* p) { return (uint32_t)__cvta_generic_to_shared(p); }
__device__ __forceinline__ void mbar_expect_tx(uint32_t b, uint32_t n) { asm volatile("mbarrier.arrive.expect_tx.shared::cta.b64 _, [%0], %1;" ::"r"(b), "r"(n) : "memory"); }
__device__ __forceinline__ void mbar_arrive(uint32_t b) { asm volatile("mbarrier.arrive.shared::cta.b64 _, [%0];" ::"r"(b) : "memory"); }
__device__ __forceinline__ void mbar_arrive2(uint32_t b) { asm volatile("mbarrier.arrive.shared::cta.b64 _, [%0], 2;" ::"r"(b) : "memory"); }
__device__ __forceinline__ uint32_t mapa(uint32_t a, uint32_t cta) { uint32_t r; asm volatile("mapa.shared::cluster.u32 %0, %1, %2;" : "=r"(r) : "r"(a), "r"(cta)); return r; }
__device__ __forceinline__ void mbar_arrive_remote(uint32_t rb) { asm volatile("mbarrier.arrive.shared::cluster.b64 _, [%0];" ::"r"(rb) : "memory"); }
constexpr int SPIN_LIMIT = 1 << 16;
template <int N> __device__ __forceinline__ void mbar_init(uint32_t b, uint32_t count) {
#pragma unroll
  for (int i = 0; i < N; i++) asm volatile("mbarrier.init.shared::cta.b64 [%0], %1;" ::"r"(b + 8 * i), "r"(count) : "memory");
}
__device__ __forceinline__ bool elect() { uint32_t p; asm volatile("{.reg .pred q; elect.sync _|q, 0xffffffff; selp.u32 %0, 1, 0, q;}" : "=r"(p)); return p; }
__device__ __forceinline__ void arrive1(uint32_t b) { __syncwarp(); if (elect()) mbar_arrive(b); }
__device__ __forceinline__ bool mbar_test(uint32_t b) {
  uint32_t ok;
  asm volatile("{.reg .pred p; mbarrier.test_wait.parity.shared::cta.b64 p, [%1], 0; selp.u32 %0,1,0,p;}" : "=r"(ok) : "r"(b) : "memory");
  return ok;
}
#define WAIT_LOOP(sem) "{.reg .pred p; mov.u32 %0, 0; W: mbarrier.try_wait.parity" sem ".shared::cta.b64 p, [%1], %2; @p bra.uni D; add.u32 %0, %0, 1; setp.lt.u32 p, %0, %3; @p bra.uni W; D:}"
__device__ __forceinline__ void mbar_wait(uint32_t b, uint32_t ph = 0) {
  int it;
  asm volatile(WAIT_LOOP("") : "=&r"(it) : "r"(b), "r"(ph), "n"(SPIN_LIMIT) : "memory");
}
__device__ __forceinline__ void mbar_wait_cluster(uint32_t b, uint32_t ph = 0) {
  int it;
  asm volatile(WAIT_LOOP(".acquire.cluster") : "=&r"(it) : "r"(b), "r"(ph), "n"(SPIN_LIMIT) : "memory");
}
__device__ __forceinline__ void wait_clock(uint32_t t) {
  asm volatile("{.reg .pred p; .reg .s32 d; W: mov.u32 d, %%clock; sub.s32 d, d, %0; setp.lt.s32 p, d, 0; @p bra.uni W;}" ::"r"(t) : "memory");
}
__device__ __forceinline__ void tma2d(uint32_t dst, const CUtensorMap* m, int c0, int c1, uint32_t bar) {
  asm volatile("cp.async.bulk.tensor.2d.shared::cluster.global.mbarrier::complete_tx::bytes [%0], [%1, {%3,%4}], [%2];" ::"r"(dst), "l"(m), "r"(bar), "r"(c0), "r"(c1) : "memory");
}
__device__ __forceinline__ void tma3d(uint32_t dst, const CUtensorMap* m, int c0, int c1, int c2, uint32_t bar) {
  asm volatile("cp.async.bulk.tensor.3d.shared::cluster.global.mbarrier::complete_tx::bytes [%0], [%1, {%3,%4,%5}], [%2];" ::"r"(dst), "l"(m), "r"(bar), "r"(c0), "r"(c1), "r"(c2) : "memory");
}
__device__ __forceinline__ void tma5d(uint32_t dst, const CUtensorMap* m, int c0, int c4, uint32_t bar) {
  asm volatile("cp.async.bulk.tensor.5d.shared::cluster.global.mbarrier::complete_tx::bytes [%0], [%1, {%4,%3,%3,%3,%5}], [%2];" ::"r"(dst), "l"(m), "r"(bar), "r"(0), "r"(c0), "r"(c4) : "memory");
}
__device__ __forceinline__ void tma2d_store(const CUtensorMap* m, int c0, int c1, uint32_t src) {
  asm volatile("cp.async.bulk.tensor.2d.global.shared::cta.bulk_group [%0, {%2,%3}], [%1];" ::"l"(m), "r"(src), "r"(c0), "r"(c1) : "memory");
}
__device__ __forceinline__ void bulk_load(uint32_t dst, const void* src, uint32_t bytes, uint32_t bar) {
  asm volatile("cp.async.bulk.shared::cluster.global.mbarrier::complete_tx::bytes [%0], [%1], %2, [%3];" ::"r"(dst), "l"(src), "r"(bytes), "r"(bar) : "memory");
}
__device__ __forceinline__ void prefetch_map(const CUtensorMap* m) { asm volatile("prefetch.tensormap [%0];" ::"l"(m) : "memory"); }
__device__ __forceinline__ void bulk_commit() { asm volatile("cp.async.bulk.commit_group;" ::: "memory"); }
__device__ __forceinline__ void bulk_wait_read() { asm volatile("cp.async.bulk.wait_group.read 0;" ::: "memory"); }
__device__ __forceinline__ void fence_async_smem() { asm volatile("fence.proxy.async.shared::cta;" ::: "memory"); }
__device__ __forceinline__ void fence_async_all() { asm volatile("fence.proxy.async.global;" ::: "memory"); }
__device__ __forceinline__ void named_bar(int id, int n) { asm volatile("bar.sync %0, %1;" ::"r"(id), "r"(n) : "memory"); }
__device__ __forceinline__ bool bar_all(int id, bool v) {
  uint32_t r;
  asm volatile("{.reg .pred p, q; setp.ne.u32 p, %2, 0; bar.red.and.pred q, %1, 128, p; selp.u32 %0, 1, 0, q;}" : "=r"(r) : "r"(id), "r"((uint32_t)v) : "memory");
  return __all_sync(~0u, r);
}
__device__ __forceinline__ void cluster_wait() { asm volatile("barrier.cluster.wait.aligned;" ::: "memory"); }
__device__ __forceinline__ void wg_fence() { asm volatile("wgmma.fence.sync.aligned;" ::: "memory"); }
__device__ __forceinline__ void wg_commit() { asm volatile("wgmma.commit_group.sync.aligned;" ::: "memory"); }
template <int N> __device__ __forceinline__ void wg_wait() { asm volatile("wgmma.wait_group.sync.aligned %0;" ::"n"(N) : "memory"); }
template <int N> __device__ __forceinline__ void fence_regs(float (&a)[N]) {
#pragma unroll
  for (int i = 0; i < N; i++) asm volatile("" : "+f"(a[i])::"memory");
}
template <int N> __device__ __forceinline__ void fence_n(float* a) {
#pragma unroll
  for (int i = 0; i < N; i++) asm volatile("" : "+f"(a[i])::"memory");
}
__device__ __forceinline__ uint64_t mkdesc(uint32_t addr, uint32_t lbo, uint32_t sbo, uint32_t swz) {
  uint32_t lo = (addr >> 4) | ((lbo >> 4) << 16), hi = (sbo >> 4) | (swz << 30);
  return ((uint64_t)hi << 32) | lo;
}
__device__ __forceinline__ void stmatrix_x4(uint32_t a, uint32_t r0, uint32_t r1, uint32_t r2, uint32_t r3) {
  asm volatile("stmatrix.sync.aligned.m8n8.x4.shared.b16 [%0], {%1,%2,%3,%4};" ::"r"(a), "r"(r0), "r"(r1), "r"(r2), "r"(r3) : "memory");
}
__device__ __forceinline__ void stmatrix_x4_t(uint32_t a, uint32_t r0, uint32_t r1, uint32_t r2, uint32_t r3) {
  asm volatile("stmatrix.sync.aligned.m8n8.x4.trans.shared.b16 [%0], {%1,%2,%3,%4};" ::"r"(a), "r"(r0), "r"(r1), "r"(r2), "r"(r3) : "memory");
}
__device__ __forceinline__ void ldmatrix_x4_t(uint32_t* r, uint32_t a) {
  asm volatile("ldmatrix.sync.aligned.m8n8.x4.trans.shared.b16 {%0,%1,%2,%3}, [%4];" : "=r"(r[0]), "=r"(r[1]), "=r"(r[2]), "=r"(r[3]) : "r"(a) : "memory");
}
__device__ __forceinline__ uint32_t lds32(uint32_t a) { uint32_t v; asm volatile("ld.shared.b32 %0, [%1];" : "=r"(v) : "r"(a) : "memory"); return v; }
__device__ __forceinline__ uint2 lds64(uint32_t a) { uint2 v; asm volatile("ld.shared.v2.b32 {%0,%1}, [%2];" : "=r"(v.x), "=r"(v.y) : "r"(a) : "memory"); return v; }
__device__ __forceinline__ uint4 lds128(uint32_t a) { uint4 v; asm volatile("ld.shared.v4.b32 {%0,%1,%2,%3}, [%4];" : "=r"(v.x), "=r"(v.y), "=r"(v.z), "=r"(v.w) : "r"(a) : "memory"); return v; }
__device__ __forceinline__ void sts32(uint32_t a, uint32_t v) { asm volatile("st.shared.b32 [%0], %1;" ::"r"(a), "r"(v) : "memory"); }
__device__ __forceinline__ void sts64(uint32_t a, uint32_t x, uint32_t y) { asm volatile("st.shared.v2.b32 [%0], {%1,%2};" ::"r"(a), "r"(x), "r"(y) : "memory"); }
__device__ __forceinline__ void sts128(uint32_t a, uint32_t x, uint32_t y, uint32_t z, uint32_t w) { asm volatile("st.shared.v4.b32 [%0], {%1,%2,%3,%4};" ::"r"(a), "r"(x), "r"(y), "r"(z), "r"(w) : "memory"); }
__device__ __forceinline__ uint4 ld_relaxed128(const void* p) { uint4 v; asm volatile("ld.relaxed.gpu.global.v4.u32 {%0,%1,%2,%3}, [%4];" : "=r"(v.x), "=r"(v.y), "=r"(v.z), "=r"(v.w) : "l"(p) : "memory"); return v; }
__device__ __forceinline__ uint2 ld_relaxed64(const void* p) { uint2 v; asm volatile("ld.relaxed.gpu.global.v2.u32 {%0,%1}, [%2];" : "=r"(v.x), "=r"(v.y) : "l"(p) : "memory"); return v; }
__device__ __forceinline__ uint32_t ld_relaxed32(const void* p) { uint32_t v; asm volatile("ld.relaxed.gpu.global.u32 %0, [%1];" : "=r"(v) : "l"(p) : "memory"); return v; }
__device__ __forceinline__ void st_relaxed128(void* p, uint32_t x, uint32_t y, uint32_t z, uint32_t w) { asm volatile("st.relaxed.gpu.global.v4.u32 [%0], {%1,%2,%3,%4};" ::"l"(p), "r"(x), "r"(y), "r"(z), "r"(w) : "memory"); }
__device__ __forceinline__ void st_relaxed32(void* p, uint32_t x) { asm volatile("st.relaxed.gpu.global.u32 [%0], %1;" ::"l"(p), "r"(x) : "memory"); }
__device__ __forceinline__ void red_hint(unsigned* p) { asm volatile("red.relaxed.gpu.global.add.u32 [%0], 1;" ::"l"(p) : "memory"); }
__device__ __forceinline__ void publish(uint32_t* p, uint32_t x) { asm volatile("{.reg .b32 t; atom.relaxed.gpu.global.exch.b32 t, [%0], %1;}" ::"l"(p), "r"(x) : "memory"); }
__device__ __forceinline__ uint32_t ldg32(const void* p) { uint32_t v; asm volatile("ld.global.nc.L1::no_allocate.b32 %0, [%1];" : "=r"(v) : "l"(p)); return v; }
__device__ __forceinline__ uint32_t pack_bf16(float lo, float hi) { uint32_t r; asm("cvt.rn.bf16x2.f32 %0, %1, %2;" : "=r"(r) : "f"(hi), "f"(lo)); return r; }
__device__ __forceinline__ float bf_lo(uint32_t v) { return __uint_as_float(v << 16); }
__device__ __forceinline__ float bf_hi(uint32_t v) { return __uint_as_float(v & 0xFFFF0000u); }
__device__ __forceinline__ uint32_t bmul2(uint32_t a, uint32_t b) { uint32_t r; asm("mul.rn.bf16x2 %0, %1, %2;" : "=r"(r) : "r"(a), "r"(b)); return r; }
__device__ __forceinline__ uint32_t badd2(uint32_t a, uint32_t b) { uint32_t r; asm("add.rn.bf16x2 %0, %1, %2;" : "=r"(r) : "r"(a), "r"(b)); return r; }
__device__ __forceinline__ uint32_t bfma2(uint32_t a, uint32_t b, uint32_t c) { uint32_t r; asm("fma.rn.bf16x2 %0, %1, %2, %3;" : "=r"(r) : "r"(a), "r"(b), "r"(c)); return r; }
__device__ __forceinline__ uint32_t set_tag(uint32_t x, uint32_t mask, uint32_t e) { uint32_t r; asm("lop3.b32 %0, %1, %2, %3, 0xB8;" : "=r"(r) : "r"(x), "r"(mask), "r"(e)); return r; }
__device__ __forceinline__ uint32_t opaque(uint32_t x) { asm volatile("" : "+r"(x)); return x; }
__device__ __forceinline__ float rbf(float x) { return __bfloat162float(__float2bfloat16(x)); }
__device__ __forceinline__ float silu_f(float x) {
  float e, r;
  asm("ex2.approx.ftz.f32 %0, %1;" : "=f"(e) : "f"(x * -1.4426950408889634f));
  asm("rcp.approx.ftz.f32 %0, %1;" : "=f"(r) : "f"(1.f + e));
  return x * r;
}
__device__ __forceinline__ float silu2(float x) {
  float t;
  asm("tanh.approx.f32 %0, %1;" : "=f"(t) : "f"(x));
  return fmaf(x, t, x);
}
__device__ __forceinline__ void pin(int off, uint32_t x) { asm volatile("{.reg .pred p; setp.lt.s32 p, %0, 0; @p st.shared.b32 [%0], %1;}" ::"r"(off), "r"(x) : "memory"); }
__device__ __forceinline__ void pin4(int off, const uint32_t* x) { asm volatile("{.reg .pred p; setp.lt.s32 p, %0, 0; @p st.shared.v4.b32 [%0], {%1,%2,%3,%4};}" ::"r"(off), "r"(x[0]), "r"(x[1]), "r"(x[2]), "r"(x[3]) : "memory"); }
__device__ __forceinline__ void split(int x, int n) { asm volatile("{.reg .pred p; setp.eq.s32 p, %0, %1; @p trap;}" ::"r"(x), "r"(~n) : "memory"); }
__device__ __forceinline__ void ln_final(float s, float q, float& m, float& sd) {
  m = s * (1.f / D_);
  asm("sqrt.approx.f32 %0, %1;" : "=f"(sd) : "f"(rbf(rbf(fmaxf(fmaf(-m, m, q * (1.f / D_)), 0.f)) + 1e-5f)));
  sd = rbf(sd);
}
__device__ __forceinline__ float rcpf(float x) { float r; asm("rcp.approx.f32 %0, %1;" : "=f"(r) : "f"(x)); return r; }

__device__ __forceinline__ void wg_rs16_0(float* d, const uint32_t* a, uint64_t db, int sc) {
  asm volatile("{.reg .pred p; setp.ne.b32 p, %13, 0; wgmma.mma_async.sync.aligned.m64n16k16.f32.bf16.bf16 {%0,%1,%2,%3,%4,%5,%6,%7}, {%8,%9,%10,%11}, %12, p, 1, 1, 0;}"
    : "+f"(d[0]),"+f"(d[1]),"+f"(d[2]),"+f"(d[3]),"+f"(d[4]),"+f"(d[5]),"+f"(d[6]),"+f"(d[7]) : "r"(a[0]),"r"(a[1]),"r"(a[2]),"r"(a[3]),"l"(db),"r"(sc));
}
__device__ __forceinline__ void wg_rs32_0(float* d, const uint32_t* a, uint64_t db, int sc) {
  asm volatile("{.reg .pred p; setp.ne.b32 p, %21, 0; wgmma.mma_async.sync.aligned.m64n32k16.f32.bf16.bf16 {%0,%1,%2,%3,%4,%5,%6,%7,%8,%9,%10,%11,%12,%13,%14,%15}, {%16,%17,%18,%19}, %20, p, 1, 1, 0;}"
    : "+f"(d[0]),"+f"(d[1]),"+f"(d[2]),"+f"(d[3]),"+f"(d[4]),"+f"(d[5]),"+f"(d[6]),"+f"(d[7]),"+f"(d[8]),"+f"(d[9]),"+f"(d[10]),"+f"(d[11]),"+f"(d[12]),"+f"(d[13]),"+f"(d[14]),"+f"(d[15]) : "r"(a[0]),"r"(a[1]),"r"(a[2]),"r"(a[3]),"l"(db),"r"(sc));
}
__device__ __forceinline__ void wg_rs48_0(float* d, const uint32_t* a, uint64_t db, int sc) {
  asm volatile("{.reg .pred p; setp.ne.b32 p, %29, 0; wgmma.mma_async.sync.aligned.m64n48k16.f32.bf16.bf16 {%0,%1,%2,%3,%4,%5,%6,%7,%8,%9,%10,%11,%12,%13,%14,%15,%16,%17,%18,%19,%20,%21,%22,%23}, {%24,%25,%26,%27}, %28, p, 1, 1, 0;}"
    : "+f"(d[0]),"+f"(d[1]),"+f"(d[2]),"+f"(d[3]),"+f"(d[4]),"+f"(d[5]),"+f"(d[6]),"+f"(d[7]),"+f"(d[8]),"+f"(d[9]),"+f"(d[10]),"+f"(d[11]),"+f"(d[12]),"+f"(d[13]),"+f"(d[14]),"+f"(d[15]),"+f"(d[16]),"+f"(d[17]),"+f"(d[18]),"+f"(d[19]),"+f"(d[20]),"+f"(d[21]),"+f"(d[22]),"+f"(d[23]) : "r"(a[0]),"r"(a[1]),"r"(a[2]),"r"(a[3]),"l"(db),"r"(sc));
}
__device__ __forceinline__ void wg_rs64_0(float* d, const uint32_t* a, uint64_t db, int sc) {
  asm volatile("{.reg .pred p; setp.ne.b32 p, %37, 0; wgmma.mma_async.sync.aligned.m64n64k16.f32.bf16.bf16 {%0,%1,%2,%3,%4,%5,%6,%7,%8,%9,%10,%11,%12,%13,%14,%15,%16,%17,%18,%19,%20,%21,%22,%23,%24,%25,%26,%27,%28,%29,%30,%31}, {%32,%33,%34,%35}, %36, p, 1, 1, 0;}"
    : "+f"(d[0]),"+f"(d[1]),"+f"(d[2]),"+f"(d[3]),"+f"(d[4]),"+f"(d[5]),"+f"(d[6]),"+f"(d[7]),"+f"(d[8]),"+f"(d[9]),"+f"(d[10]),"+f"(d[11]),"+f"(d[12]),"+f"(d[13]),"+f"(d[14]),"+f"(d[15]),"+f"(d[16]),"+f"(d[17]),"+f"(d[18]),"+f"(d[19]),"+f"(d[20]),"+f"(d[21]),"+f"(d[22]),"+f"(d[23]),"+f"(d[24]),"+f"(d[25]),"+f"(d[26]),"+f"(d[27]),"+f"(d[28]),"+f"(d[29]),"+f"(d[30]),"+f"(d[31]) : "r"(a[0]),"r"(a[1]),"r"(a[2]),"r"(a[3]),"l"(db),"r"(sc));
}
__device__ __forceinline__ void wg_rs80_0(float* d, const uint32_t* a, uint64_t db, int sc) {
  asm volatile("{.reg .pred p; setp.ne.b32 p, %45, 0; wgmma.mma_async.sync.aligned.m64n80k16.f32.bf16.bf16 {%0,%1,%2,%3,%4,%5,%6,%7,%8,%9,%10,%11,%12,%13,%14,%15,%16,%17,%18,%19,%20,%21,%22,%23,%24,%25,%26,%27,%28,%29,%30,%31,%32,%33,%34,%35,%36,%37,%38,%39}, {%40,%41,%42,%43}, %44, p, 1, 1, 0;}"
    : "+f"(d[0]),"+f"(d[1]),"+f"(d[2]),"+f"(d[3]),"+f"(d[4]),"+f"(d[5]),"+f"(d[6]),"+f"(d[7]),"+f"(d[8]),"+f"(d[9]),"+f"(d[10]),"+f"(d[11]),"+f"(d[12]),"+f"(d[13]),"+f"(d[14]),"+f"(d[15]),"+f"(d[16]),"+f"(d[17]),"+f"(d[18]),"+f"(d[19]),"+f"(d[20]),"+f"(d[21]),"+f"(d[22]),"+f"(d[23]),"+f"(d[24]),"+f"(d[25]),"+f"(d[26]),"+f"(d[27]),"+f"(d[28]),"+f"(d[29]),"+f"(d[30]),"+f"(d[31]),"+f"(d[32]),"+f"(d[33]),"+f"(d[34]),"+f"(d[35]),"+f"(d[36]),"+f"(d[37]),"+f"(d[38]),"+f"(d[39]) : "r"(a[0]),"r"(a[1]),"r"(a[2]),"r"(a[3]),"l"(db),"r"(sc));
}
__device__ __forceinline__ void wg_rs96_0(float* d, const uint32_t* a, uint64_t db, int sc) {
  asm volatile("{.reg .pred p; setp.ne.b32 p, %53, 0; wgmma.mma_async.sync.aligned.m64n96k16.f32.bf16.bf16 {%0,%1,%2,%3,%4,%5,%6,%7,%8,%9,%10,%11,%12,%13,%14,%15,%16,%17,%18,%19,%20,%21,%22,%23,%24,%25,%26,%27,%28,%29,%30,%31,%32,%33,%34,%35,%36,%37,%38,%39,%40,%41,%42,%43,%44,%45,%46,%47}, {%48,%49,%50,%51}, %52, p, 1, 1, 0;}"
    : "+f"(d[0]),"+f"(d[1]),"+f"(d[2]),"+f"(d[3]),"+f"(d[4]),"+f"(d[5]),"+f"(d[6]),"+f"(d[7]),"+f"(d[8]),"+f"(d[9]),"+f"(d[10]),"+f"(d[11]),"+f"(d[12]),"+f"(d[13]),"+f"(d[14]),"+f"(d[15]),"+f"(d[16]),"+f"(d[17]),"+f"(d[18]),"+f"(d[19]),"+f"(d[20]),"+f"(d[21]),"+f"(d[22]),"+f"(d[23]),"+f"(d[24]),"+f"(d[25]),"+f"(d[26]),"+f"(d[27]),"+f"(d[28]),"+f"(d[29]),"+f"(d[30]),"+f"(d[31]),"+f"(d[32]),"+f"(d[33]),"+f"(d[34]),"+f"(d[35]),"+f"(d[36]),"+f"(d[37]),"+f"(d[38]),"+f"(d[39]),"+f"(d[40]),"+f"(d[41]),"+f"(d[42]),"+f"(d[43]),"+f"(d[44]),"+f"(d[45]),"+f"(d[46]),"+f"(d[47]) : "r"(a[0]),"r"(a[1]),"r"(a[2]),"r"(a[3]),"l"(db),"r"(sc));
}
__device__ __forceinline__ void wg_rs112_0(float* d, const uint32_t* a, uint64_t db, int sc) {
  asm volatile("{.reg .pred p; setp.ne.b32 p, %61, 0; wgmma.mma_async.sync.aligned.m64n112k16.f32.bf16.bf16 {%0,%1,%2,%3,%4,%5,%6,%7,%8,%9,%10,%11,%12,%13,%14,%15,%16,%17,%18,%19,%20,%21,%22,%23,%24,%25,%26,%27,%28,%29,%30,%31,%32,%33,%34,%35,%36,%37,%38,%39,%40,%41,%42,%43,%44,%45,%46,%47,%48,%49,%50,%51,%52,%53,%54,%55}, {%56,%57,%58,%59}, %60, p, 1, 1, 0;}"
    : "+f"(d[0]),"+f"(d[1]),"+f"(d[2]),"+f"(d[3]),"+f"(d[4]),"+f"(d[5]),"+f"(d[6]),"+f"(d[7]),"+f"(d[8]),"+f"(d[9]),"+f"(d[10]),"+f"(d[11]),"+f"(d[12]),"+f"(d[13]),"+f"(d[14]),"+f"(d[15]),"+f"(d[16]),"+f"(d[17]),"+f"(d[18]),"+f"(d[19]),"+f"(d[20]),"+f"(d[21]),"+f"(d[22]),"+f"(d[23]),"+f"(d[24]),"+f"(d[25]),"+f"(d[26]),"+f"(d[27]),"+f"(d[28]),"+f"(d[29]),"+f"(d[30]),"+f"(d[31]),"+f"(d[32]),"+f"(d[33]),"+f"(d[34]),"+f"(d[35]),"+f"(d[36]),"+f"(d[37]),"+f"(d[38]),"+f"(d[39]),"+f"(d[40]),"+f"(d[41]),"+f"(d[42]),"+f"(d[43]),"+f"(d[44]),"+f"(d[45]),"+f"(d[46]),"+f"(d[47]),"+f"(d[48]),"+f"(d[49]),"+f"(d[50]),"+f"(d[51]),"+f"(d[52]),"+f"(d[53]),"+f"(d[54]),"+f"(d[55]) : "r"(a[0]),"r"(a[1]),"r"(a[2]),"r"(a[3]),"l"(db),"r"(sc));
}
__device__ __forceinline__ void wg_rs128_0(float* d, const uint32_t* a, uint64_t db, int sc) {
  asm volatile("{.reg .pred p; setp.ne.b32 p, %69, 0; wgmma.mma_async.sync.aligned.m64n128k16.f32.bf16.bf16 {%0,%1,%2,%3,%4,%5,%6,%7,%8,%9,%10,%11,%12,%13,%14,%15,%16,%17,%18,%19,%20,%21,%22,%23,%24,%25,%26,%27,%28,%29,%30,%31,%32,%33,%34,%35,%36,%37,%38,%39,%40,%41,%42,%43,%44,%45,%46,%47,%48,%49,%50,%51,%52,%53,%54,%55,%56,%57,%58,%59,%60,%61,%62,%63}, {%64,%65,%66,%67}, %68, p, 1, 1, 0;}"
    : "+f"(d[0]),"+f"(d[1]),"+f"(d[2]),"+f"(d[3]),"+f"(d[4]),"+f"(d[5]),"+f"(d[6]),"+f"(d[7]),"+f"(d[8]),"+f"(d[9]),"+f"(d[10]),"+f"(d[11]),"+f"(d[12]),"+f"(d[13]),"+f"(d[14]),"+f"(d[15]),"+f"(d[16]),"+f"(d[17]),"+f"(d[18]),"+f"(d[19]),"+f"(d[20]),"+f"(d[21]),"+f"(d[22]),"+f"(d[23]),"+f"(d[24]),"+f"(d[25]),"+f"(d[26]),"+f"(d[27]),"+f"(d[28]),"+f"(d[29]),"+f"(d[30]),"+f"(d[31]),"+f"(d[32]),"+f"(d[33]),"+f"(d[34]),"+f"(d[35]),"+f"(d[36]),"+f"(d[37]),"+f"(d[38]),"+f"(d[39]),"+f"(d[40]),"+f"(d[41]),"+f"(d[42]),"+f"(d[43]),"+f"(d[44]),"+f"(d[45]),"+f"(d[46]),"+f"(d[47]),"+f"(d[48]),"+f"(d[49]),"+f"(d[50]),"+f"(d[51]),"+f"(d[52]),"+f"(d[53]),"+f"(d[54]),"+f"(d[55]),"+f"(d[56]),"+f"(d[57]),"+f"(d[58]),"+f"(d[59]),"+f"(d[60]),"+f"(d[61]),"+f"(d[62]),"+f"(d[63]) : "r"(a[0]),"r"(a[1]),"r"(a[2]),"r"(a[3]),"l"(db),"r"(sc));
}
__device__ __forceinline__ void wg_rs144_0(float* d, const uint32_t* a, uint64_t db, int sc) {
  asm volatile("{.reg .pred p; setp.ne.b32 p, %77, 0; wgmma.mma_async.sync.aligned.m64n144k16.f32.bf16.bf16 {%0,%1,%2,%3,%4,%5,%6,%7,%8,%9,%10,%11,%12,%13,%14,%15,%16,%17,%18,%19,%20,%21,%22,%23,%24,%25,%26,%27,%28,%29,%30,%31,%32,%33,%34,%35,%36,%37,%38,%39,%40,%41,%42,%43,%44,%45,%46,%47,%48,%49,%50,%51,%52,%53,%54,%55,%56,%57,%58,%59,%60,%61,%62,%63,%64,%65,%66,%67,%68,%69,%70,%71}, {%72,%73,%74,%75}, %76, p, 1, 1, 0;}"
    : "+f"(d[0]),"+f"(d[1]),"+f"(d[2]),"+f"(d[3]),"+f"(d[4]),"+f"(d[5]),"+f"(d[6]),"+f"(d[7]),"+f"(d[8]),"+f"(d[9]),"+f"(d[10]),"+f"(d[11]),"+f"(d[12]),"+f"(d[13]),"+f"(d[14]),"+f"(d[15]),"+f"(d[16]),"+f"(d[17]),"+f"(d[18]),"+f"(d[19]),"+f"(d[20]),"+f"(d[21]),"+f"(d[22]),"+f"(d[23]),"+f"(d[24]),"+f"(d[25]),"+f"(d[26]),"+f"(d[27]),"+f"(d[28]),"+f"(d[29]),"+f"(d[30]),"+f"(d[31]),"+f"(d[32]),"+f"(d[33]),"+f"(d[34]),"+f"(d[35]),"+f"(d[36]),"+f"(d[37]),"+f"(d[38]),"+f"(d[39]),"+f"(d[40]),"+f"(d[41]),"+f"(d[42]),"+f"(d[43]),"+f"(d[44]),"+f"(d[45]),"+f"(d[46]),"+f"(d[47]),"+f"(d[48]),"+f"(d[49]),"+f"(d[50]),"+f"(d[51]),"+f"(d[52]),"+f"(d[53]),"+f"(d[54]),"+f"(d[55]),"+f"(d[56]),"+f"(d[57]),"+f"(d[58]),"+f"(d[59]),"+f"(d[60]),"+f"(d[61]),"+f"(d[62]),"+f"(d[63]),"+f"(d[64]),"+f"(d[65]),"+f"(d[66]),"+f"(d[67]),"+f"(d[68]),"+f"(d[69]),"+f"(d[70]),"+f"(d[71]) : "r"(a[0]),"r"(a[1]),"r"(a[2]),"r"(a[3]),"l"(db),"r"(sc));
}
__device__ __forceinline__ void wg_rs160_0(float* d, const uint32_t* a, uint64_t db, int sc) {
  asm volatile("{.reg .pred p; setp.ne.b32 p, %85, 0; wgmma.mma_async.sync.aligned.m64n160k16.f32.bf16.bf16 {%0,%1,%2,%3,%4,%5,%6,%7,%8,%9,%10,%11,%12,%13,%14,%15,%16,%17,%18,%19,%20,%21,%22,%23,%24,%25,%26,%27,%28,%29,%30,%31,%32,%33,%34,%35,%36,%37,%38,%39,%40,%41,%42,%43,%44,%45,%46,%47,%48,%49,%50,%51,%52,%53,%54,%55,%56,%57,%58,%59,%60,%61,%62,%63,%64,%65,%66,%67,%68,%69,%70,%71,%72,%73,%74,%75,%76,%77,%78,%79}, {%80,%81,%82,%83}, %84, p, 1, 1, 0;}"
    : "+f"(d[0]),"+f"(d[1]),"+f"(d[2]),"+f"(d[3]),"+f"(d[4]),"+f"(d[5]),"+f"(d[6]),"+f"(d[7]),"+f"(d[8]),"+f"(d[9]),"+f"(d[10]),"+f"(d[11]),"+f"(d[12]),"+f"(d[13]),"+f"(d[14]),"+f"(d[15]),"+f"(d[16]),"+f"(d[17]),"+f"(d[18]),"+f"(d[19]),"+f"(d[20]),"+f"(d[21]),"+f"(d[22]),"+f"(d[23]),"+f"(d[24]),"+f"(d[25]),"+f"(d[26]),"+f"(d[27]),"+f"(d[28]),"+f"(d[29]),"+f"(d[30]),"+f"(d[31]),"+f"(d[32]),"+f"(d[33]),"+f"(d[34]),"+f"(d[35]),"+f"(d[36]),"+f"(d[37]),"+f"(d[38]),"+f"(d[39]),"+f"(d[40]),"+f"(d[41]),"+f"(d[42]),"+f"(d[43]),"+f"(d[44]),"+f"(d[45]),"+f"(d[46]),"+f"(d[47]),"+f"(d[48]),"+f"(d[49]),"+f"(d[50]),"+f"(d[51]),"+f"(d[52]),"+f"(d[53]),"+f"(d[54]),"+f"(d[55]),"+f"(d[56]),"+f"(d[57]),"+f"(d[58]),"+f"(d[59]),"+f"(d[60]),"+f"(d[61]),"+f"(d[62]),"+f"(d[63]),"+f"(d[64]),"+f"(d[65]),"+f"(d[66]),"+f"(d[67]),"+f"(d[68]),"+f"(d[69]),"+f"(d[70]),"+f"(d[71]),"+f"(d[72]),"+f"(d[73]),"+f"(d[74]),"+f"(d[75]),"+f"(d[76]),"+f"(d[77]),"+f"(d[78]),"+f"(d[79]) : "r"(a[0]),"r"(a[1]),"r"(a[2]),"r"(a[3]),"l"(db),"r"(sc));
}
__device__ __forceinline__ void wg_rs176_0(float* d, const uint32_t* a, uint64_t db, int sc) {
  asm volatile("{.reg .pred p; setp.ne.b32 p, %93, 0; wgmma.mma_async.sync.aligned.m64n176k16.f32.bf16.bf16 {%0,%1,%2,%3,%4,%5,%6,%7,%8,%9,%10,%11,%12,%13,%14,%15,%16,%17,%18,%19,%20,%21,%22,%23,%24,%25,%26,%27,%28,%29,%30,%31,%32,%33,%34,%35,%36,%37,%38,%39,%40,%41,%42,%43,%44,%45,%46,%47,%48,%49,%50,%51,%52,%53,%54,%55,%56,%57,%58,%59,%60,%61,%62,%63,%64,%65,%66,%67,%68,%69,%70,%71,%72,%73,%74,%75,%76,%77,%78,%79,%80,%81,%82,%83,%84,%85,%86,%87}, {%88,%89,%90,%91}, %92, p, 1, 1, 0;}"
    : "+f"(d[0]),"+f"(d[1]),"+f"(d[2]),"+f"(d[3]),"+f"(d[4]),"+f"(d[5]),"+f"(d[6]),"+f"(d[7]),"+f"(d[8]),"+f"(d[9]),"+f"(d[10]),"+f"(d[11]),"+f"(d[12]),"+f"(d[13]),"+f"(d[14]),"+f"(d[15]),"+f"(d[16]),"+f"(d[17]),"+f"(d[18]),"+f"(d[19]),"+f"(d[20]),"+f"(d[21]),"+f"(d[22]),"+f"(d[23]),"+f"(d[24]),"+f"(d[25]),"+f"(d[26]),"+f"(d[27]),"+f"(d[28]),"+f"(d[29]),"+f"(d[30]),"+f"(d[31]),"+f"(d[32]),"+f"(d[33]),"+f"(d[34]),"+f"(d[35]),"+f"(d[36]),"+f"(d[37]),"+f"(d[38]),"+f"(d[39]),"+f"(d[40]),"+f"(d[41]),"+f"(d[42]),"+f"(d[43]),"+f"(d[44]),"+f"(d[45]),"+f"(d[46]),"+f"(d[47]),"+f"(d[48]),"+f"(d[49]),"+f"(d[50]),"+f"(d[51]),"+f"(d[52]),"+f"(d[53]),"+f"(d[54]),"+f"(d[55]),"+f"(d[56]),"+f"(d[57]),"+f"(d[58]),"+f"(d[59]),"+f"(d[60]),"+f"(d[61]),"+f"(d[62]),"+f"(d[63]),"+f"(d[64]),"+f"(d[65]),"+f"(d[66]),"+f"(d[67]),"+f"(d[68]),"+f"(d[69]),"+f"(d[70]),"+f"(d[71]),"+f"(d[72]),"+f"(d[73]),"+f"(d[74]),"+f"(d[75]),"+f"(d[76]),"+f"(d[77]),"+f"(d[78]),"+f"(d[79]),"+f"(d[80]),"+f"(d[81]),"+f"(d[82]),"+f"(d[83]),"+f"(d[84]),"+f"(d[85]),"+f"(d[86]),"+f"(d[87]) : "r"(a[0]),"r"(a[1]),"r"(a[2]),"r"(a[3]),"l"(db),"r"(sc));
}
__device__ __forceinline__ void wg_rs192_0(float* d, const uint32_t* a, uint64_t db, int sc) {
  asm volatile("{.reg .pred p; setp.ne.b32 p, %101, 0; wgmma.mma_async.sync.aligned.m64n192k16.f32.bf16.bf16 {%0,%1,%2,%3,%4,%5,%6,%7,%8,%9,%10,%11,%12,%13,%14,%15,%16,%17,%18,%19,%20,%21,%22,%23,%24,%25,%26,%27,%28,%29,%30,%31,%32,%33,%34,%35,%36,%37,%38,%39,%40,%41,%42,%43,%44,%45,%46,%47,%48,%49,%50,%51,%52,%53,%54,%55,%56,%57,%58,%59,%60,%61,%62,%63,%64,%65,%66,%67,%68,%69,%70,%71,%72,%73,%74,%75,%76,%77,%78,%79,%80,%81,%82,%83,%84,%85,%86,%87,%88,%89,%90,%91,%92,%93,%94,%95}, {%96,%97,%98,%99}, %100, p, 1, 1, 0;}"
    : "+f"(d[0]),"+f"(d[1]),"+f"(d[2]),"+f"(d[3]),"+f"(d[4]),"+f"(d[5]),"+f"(d[6]),"+f"(d[7]),"+f"(d[8]),"+f"(d[9]),"+f"(d[10]),"+f"(d[11]),"+f"(d[12]),"+f"(d[13]),"+f"(d[14]),"+f"(d[15]),"+f"(d[16]),"+f"(d[17]),"+f"(d[18]),"+f"(d[19]),"+f"(d[20]),"+f"(d[21]),"+f"(d[22]),"+f"(d[23]),"+f"(d[24]),"+f"(d[25]),"+f"(d[26]),"+f"(d[27]),"+f"(d[28]),"+f"(d[29]),"+f"(d[30]),"+f"(d[31]),"+f"(d[32]),"+f"(d[33]),"+f"(d[34]),"+f"(d[35]),"+f"(d[36]),"+f"(d[37]),"+f"(d[38]),"+f"(d[39]),"+f"(d[40]),"+f"(d[41]),"+f"(d[42]),"+f"(d[43]),"+f"(d[44]),"+f"(d[45]),"+f"(d[46]),"+f"(d[47]),"+f"(d[48]),"+f"(d[49]),"+f"(d[50]),"+f"(d[51]),"+f"(d[52]),"+f"(d[53]),"+f"(d[54]),"+f"(d[55]),"+f"(d[56]),"+f"(d[57]),"+f"(d[58]),"+f"(d[59]),"+f"(d[60]),"+f"(d[61]),"+f"(d[62]),"+f"(d[63]),"+f"(d[64]),"+f"(d[65]),"+f"(d[66]),"+f"(d[67]),"+f"(d[68]),"+f"(d[69]),"+f"(d[70]),"+f"(d[71]),"+f"(d[72]),"+f"(d[73]),"+f"(d[74]),"+f"(d[75]),"+f"(d[76]),"+f"(d[77]),"+f"(d[78]),"+f"(d[79]),"+f"(d[80]),"+f"(d[81]),"+f"(d[82]),"+f"(d[83]),"+f"(d[84]),"+f"(d[85]),"+f"(d[86]),"+f"(d[87]),"+f"(d[88]),"+f"(d[89]),"+f"(d[90]),"+f"(d[91]),"+f"(d[92]),"+f"(d[93]),"+f"(d[94]),"+f"(d[95]) : "r"(a[0]),"r"(a[1]),"r"(a[2]),"r"(a[3]),"l"(db),"r"(sc));
}
__device__ __forceinline__ void wg_ss192_11(float* d, uint64_t da, uint64_t db, int sc) {
  asm volatile("{.reg .pred p; setp.ne.b32 p, %98, 0; wgmma.mma_async.sync.aligned.m64n192k16.f32.bf16.bf16 {%0,%1,%2,%3,%4,%5,%6,%7,%8,%9,%10,%11,%12,%13,%14,%15,%16,%17,%18,%19,%20,%21,%22,%23,%24,%25,%26,%27,%28,%29,%30,%31,%32,%33,%34,%35,%36,%37,%38,%39,%40,%41,%42,%43,%44,%45,%46,%47,%48,%49,%50,%51,%52,%53,%54,%55,%56,%57,%58,%59,%60,%61,%62,%63,%64,%65,%66,%67,%68,%69,%70,%71,%72,%73,%74,%75,%76,%77,%78,%79,%80,%81,%82,%83,%84,%85,%86,%87,%88,%89,%90,%91,%92,%93,%94,%95}, %96, %97, p, 1, 1, 1, 1;}"
    : "+f"(d[0]),"+f"(d[1]),"+f"(d[2]),"+f"(d[3]),"+f"(d[4]),"+f"(d[5]),"+f"(d[6]),"+f"(d[7]),"+f"(d[8]),"+f"(d[9]),"+f"(d[10]),"+f"(d[11]),"+f"(d[12]),"+f"(d[13]),"+f"(d[14]),"+f"(d[15]),"+f"(d[16]),"+f"(d[17]),"+f"(d[18]),"+f"(d[19]),"+f"(d[20]),"+f"(d[21]),"+f"(d[22]),"+f"(d[23]),"+f"(d[24]),"+f"(d[25]),"+f"(d[26]),"+f"(d[27]),"+f"(d[28]),"+f"(d[29]),"+f"(d[30]),"+f"(d[31]),"+f"(d[32]),"+f"(d[33]),"+f"(d[34]),"+f"(d[35]),"+f"(d[36]),"+f"(d[37]),"+f"(d[38]),"+f"(d[39]),"+f"(d[40]),"+f"(d[41]),"+f"(d[42]),"+f"(d[43]),"+f"(d[44]),"+f"(d[45]),"+f"(d[46]),"+f"(d[47]),"+f"(d[48]),"+f"(d[49]),"+f"(d[50]),"+f"(d[51]),"+f"(d[52]),"+f"(d[53]),"+f"(d[54]),"+f"(d[55]),"+f"(d[56]),"+f"(d[57]),"+f"(d[58]),"+f"(d[59]),"+f"(d[60]),"+f"(d[61]),"+f"(d[62]),"+f"(d[63]),"+f"(d[64]),"+f"(d[65]),"+f"(d[66]),"+f"(d[67]),"+f"(d[68]),"+f"(d[69]),"+f"(d[70]),"+f"(d[71]),"+f"(d[72]),"+f"(d[73]),"+f"(d[74]),"+f"(d[75]),"+f"(d[76]),"+f"(d[77]),"+f"(d[78]),"+f"(d[79]),"+f"(d[80]),"+f"(d[81]),"+f"(d[82]),"+f"(d[83]),"+f"(d[84]),"+f"(d[85]),"+f"(d[86]),"+f"(d[87]),"+f"(d[88]),"+f"(d[89]),"+f"(d[90]),"+f"(d[91]),"+f"(d[92]),"+f"(d[93]),"+f"(d[94]),"+f"(d[95]) : "l"(da),"l"(db),"r"(sc));
}
__device__ __forceinline__ void wg_ss192_01(float* d, uint64_t da, uint64_t db, int sc) {
  asm volatile("{.reg .pred p; setp.ne.b32 p, %98, 0; wgmma.mma_async.sync.aligned.m64n192k16.f32.bf16.bf16 {%0,%1,%2,%3,%4,%5,%6,%7,%8,%9,%10,%11,%12,%13,%14,%15,%16,%17,%18,%19,%20,%21,%22,%23,%24,%25,%26,%27,%28,%29,%30,%31,%32,%33,%34,%35,%36,%37,%38,%39,%40,%41,%42,%43,%44,%45,%46,%47,%48,%49,%50,%51,%52,%53,%54,%55,%56,%57,%58,%59,%60,%61,%62,%63,%64,%65,%66,%67,%68,%69,%70,%71,%72,%73,%74,%75,%76,%77,%78,%79,%80,%81,%82,%83,%84,%85,%86,%87,%88,%89,%90,%91,%92,%93,%94,%95}, %96, %97, p, 1, 1, 0, 1;}"
    : "+f"(d[0]),"+f"(d[1]),"+f"(d[2]),"+f"(d[3]),"+f"(d[4]),"+f"(d[5]),"+f"(d[6]),"+f"(d[7]),"+f"(d[8]),"+f"(d[9]),"+f"(d[10]),"+f"(d[11]),"+f"(d[12]),"+f"(d[13]),"+f"(d[14]),"+f"(d[15]),"+f"(d[16]),"+f"(d[17]),"+f"(d[18]),"+f"(d[19]),"+f"(d[20]),"+f"(d[21]),"+f"(d[22]),"+f"(d[23]),"+f"(d[24]),"+f"(d[25]),"+f"(d[26]),"+f"(d[27]),"+f"(d[28]),"+f"(d[29]),"+f"(d[30]),"+f"(d[31]),"+f"(d[32]),"+f"(d[33]),"+f"(d[34]),"+f"(d[35]),"+f"(d[36]),"+f"(d[37]),"+f"(d[38]),"+f"(d[39]),"+f"(d[40]),"+f"(d[41]),"+f"(d[42]),"+f"(d[43]),"+f"(d[44]),"+f"(d[45]),"+f"(d[46]),"+f"(d[47]),"+f"(d[48]),"+f"(d[49]),"+f"(d[50]),"+f"(d[51]),"+f"(d[52]),"+f"(d[53]),"+f"(d[54]),"+f"(d[55]),"+f"(d[56]),"+f"(d[57]),"+f"(d[58]),"+f"(d[59]),"+f"(d[60]),"+f"(d[61]),"+f"(d[62]),"+f"(d[63]),"+f"(d[64]),"+f"(d[65]),"+f"(d[66]),"+f"(d[67]),"+f"(d[68]),"+f"(d[69]),"+f"(d[70]),"+f"(d[71]),"+f"(d[72]),"+f"(d[73]),"+f"(d[74]),"+f"(d[75]),"+f"(d[76]),"+f"(d[77]),"+f"(d[78]),"+f"(d[79]),"+f"(d[80]),"+f"(d[81]),"+f"(d[82]),"+f"(d[83]),"+f"(d[84]),"+f"(d[85]),"+f"(d[86]),"+f"(d[87]),"+f"(d[88]),"+f"(d[89]),"+f"(d[90]),"+f"(d[91]),"+f"(d[92]),"+f"(d[93]),"+f"(d[94]),"+f"(d[95]) : "l"(da),"l"(db),"r"(sc));
}
__device__ __forceinline__ void wg_ss160_01(float* d, uint64_t da, uint64_t db, int sc) {
  asm volatile("{.reg .pred p; setp.ne.b32 p, %82, 0; wgmma.mma_async.sync.aligned.m64n160k16.f32.bf16.bf16 {%0,%1,%2,%3,%4,%5,%6,%7,%8,%9,%10,%11,%12,%13,%14,%15,%16,%17,%18,%19,%20,%21,%22,%23,%24,%25,%26,%27,%28,%29,%30,%31,%32,%33,%34,%35,%36,%37,%38,%39,%40,%41,%42,%43,%44,%45,%46,%47,%48,%49,%50,%51,%52,%53,%54,%55,%56,%57,%58,%59,%60,%61,%62,%63,%64,%65,%66,%67,%68,%69,%70,%71,%72,%73,%74,%75,%76,%77,%78,%79}, %80, %81, p, 1, 1, 0, 1;}"
    : "+f"(d[0]),"+f"(d[1]),"+f"(d[2]),"+f"(d[3]),"+f"(d[4]),"+f"(d[5]),"+f"(d[6]),"+f"(d[7]),"+f"(d[8]),"+f"(d[9]),"+f"(d[10]),"+f"(d[11]),"+f"(d[12]),"+f"(d[13]),"+f"(d[14]),"+f"(d[15]),"+f"(d[16]),"+f"(d[17]),"+f"(d[18]),"+f"(d[19]),"+f"(d[20]),"+f"(d[21]),"+f"(d[22]),"+f"(d[23]),"+f"(d[24]),"+f"(d[25]),"+f"(d[26]),"+f"(d[27]),"+f"(d[28]),"+f"(d[29]),"+f"(d[30]),"+f"(d[31]),"+f"(d[32]),"+f"(d[33]),"+f"(d[34]),"+f"(d[35]),"+f"(d[36]),"+f"(d[37]),"+f"(d[38]),"+f"(d[39]),"+f"(d[40]),"+f"(d[41]),"+f"(d[42]),"+f"(d[43]),"+f"(d[44]),"+f"(d[45]),"+f"(d[46]),"+f"(d[47]),"+f"(d[48]),"+f"(d[49]),"+f"(d[50]),"+f"(d[51]),"+f"(d[52]),"+f"(d[53]),"+f"(d[54]),"+f"(d[55]),"+f"(d[56]),"+f"(d[57]),"+f"(d[58]),"+f"(d[59]),"+f"(d[60]),"+f"(d[61]),"+f"(d[62]),"+f"(d[63]),"+f"(d[64]),"+f"(d[65]),"+f"(d[66]),"+f"(d[67]),"+f"(d[68]),"+f"(d[69]),"+f"(d[70]),"+f"(d[71]),"+f"(d[72]),"+f"(d[73]),"+f"(d[74]),"+f"(d[75]),"+f"(d[76]),"+f"(d[77]),"+f"(d[78]),"+f"(d[79]) : "l"(da),"l"(db),"r"(sc));
}
__device__ __forceinline__ void wg_ss96_01(float* d, uint64_t da, uint64_t db, int sc) {
  asm volatile("{.reg .pred p; setp.ne.b32 p, %50, 0; wgmma.mma_async.sync.aligned.m64n96k16.f32.bf16.bf16 {%0,%1,%2,%3,%4,%5,%6,%7,%8,%9,%10,%11,%12,%13,%14,%15,%16,%17,%18,%19,%20,%21,%22,%23,%24,%25,%26,%27,%28,%29,%30,%31,%32,%33,%34,%35,%36,%37,%38,%39,%40,%41,%42,%43,%44,%45,%46,%47}, %48, %49, p, 1, 1, 0, 1;}"
    : "+f"(d[0]),"+f"(d[1]),"+f"(d[2]),"+f"(d[3]),"+f"(d[4]),"+f"(d[5]),"+f"(d[6]),"+f"(d[7]),"+f"(d[8]),"+f"(d[9]),"+f"(d[10]),"+f"(d[11]),"+f"(d[12]),"+f"(d[13]),"+f"(d[14]),"+f"(d[15]),"+f"(d[16]),"+f"(d[17]),"+f"(d[18]),"+f"(d[19]),"+f"(d[20]),"+f"(d[21]),"+f"(d[22]),"+f"(d[23]),"+f"(d[24]),"+f"(d[25]),"+f"(d[26]),"+f"(d[27]),"+f"(d[28]),"+f"(d[29]),"+f"(d[30]),"+f"(d[31]),"+f"(d[32]),"+f"(d[33]),"+f"(d[34]),"+f"(d[35]),"+f"(d[36]),"+f"(d[37]),"+f"(d[38]),"+f"(d[39]),"+f"(d[40]),"+f"(d[41]),"+f"(d[42]),"+f"(d[43]),"+f"(d[44]),"+f"(d[45]),"+f"(d[46]),"+f"(d[47]) : "l"(da),"l"(db),"r"(sc));
}
__device__ __forceinline__ void wg_ss64_01(float* d, uint64_t da, uint64_t db, int sc) {
  asm volatile("{.reg .pred p; setp.ne.b32 p, %34, 0; wgmma.mma_async.sync.aligned.m64n64k16.f32.bf16.bf16 {%0,%1,%2,%3,%4,%5,%6,%7,%8,%9,%10,%11,%12,%13,%14,%15,%16,%17,%18,%19,%20,%21,%22,%23,%24,%25,%26,%27,%28,%29,%30,%31}, %32, %33, p, 1, 1, 0, 1;}"
    : "+f"(d[0]),"+f"(d[1]),"+f"(d[2]),"+f"(d[3]),"+f"(d[4]),"+f"(d[5]),"+f"(d[6]),"+f"(d[7]),"+f"(d[8]),"+f"(d[9]),"+f"(d[10]),"+f"(d[11]),"+f"(d[12]),"+f"(d[13]),"+f"(d[14]),"+f"(d[15]),"+f"(d[16]),"+f"(d[17]),"+f"(d[18]),"+f"(d[19]),"+f"(d[20]),"+f"(d[21]),"+f"(d[22]),"+f"(d[23]),"+f"(d[24]),"+f"(d[25]),"+f"(d[26]),"+f"(d[27]),"+f"(d[28]),"+f"(d[29]),"+f"(d[30]),"+f"(d[31]) : "l"(da),"l"(db),"r"(sc));
}
__device__ __forceinline__ void wg_rs160_1(float* d, const uint32_t* a, uint64_t db, int sc) {
  asm volatile("{.reg .pred p; setp.ne.b32 p, %85, 0; wgmma.mma_async.sync.aligned.m64n160k16.f32.bf16.bf16 {%0,%1,%2,%3,%4,%5,%6,%7,%8,%9,%10,%11,%12,%13,%14,%15,%16,%17,%18,%19,%20,%21,%22,%23,%24,%25,%26,%27,%28,%29,%30,%31,%32,%33,%34,%35,%36,%37,%38,%39,%40,%41,%42,%43,%44,%45,%46,%47,%48,%49,%50,%51,%52,%53,%54,%55,%56,%57,%58,%59,%60,%61,%62,%63,%64,%65,%66,%67,%68,%69,%70,%71,%72,%73,%74,%75,%76,%77,%78,%79}, {%80,%81,%82,%83}, %84, p, 1, 1, 1;}"
    : "+f"(d[0]),"+f"(d[1]),"+f"(d[2]),"+f"(d[3]),"+f"(d[4]),"+f"(d[5]),"+f"(d[6]),"+f"(d[7]),"+f"(d[8]),"+f"(d[9]),"+f"(d[10]),"+f"(d[11]),"+f"(d[12]),"+f"(d[13]),"+f"(d[14]),"+f"(d[15]),"+f"(d[16]),"+f"(d[17]),"+f"(d[18]),"+f"(d[19]),"+f"(d[20]),"+f"(d[21]),"+f"(d[22]),"+f"(d[23]),"+f"(d[24]),"+f"(d[25]),"+f"(d[26]),"+f"(d[27]),"+f"(d[28]),"+f"(d[29]),"+f"(d[30]),"+f"(d[31]),"+f"(d[32]),"+f"(d[33]),"+f"(d[34]),"+f"(d[35]),"+f"(d[36]),"+f"(d[37]),"+f"(d[38]),"+f"(d[39]),"+f"(d[40]),"+f"(d[41]),"+f"(d[42]),"+f"(d[43]),"+f"(d[44]),"+f"(d[45]),"+f"(d[46]),"+f"(d[47]),"+f"(d[48]),"+f"(d[49]),"+f"(d[50]),"+f"(d[51]),"+f"(d[52]),"+f"(d[53]),"+f"(d[54]),"+f"(d[55]),"+f"(d[56]),"+f"(d[57]),"+f"(d[58]),"+f"(d[59]),"+f"(d[60]),"+f"(d[61]),"+f"(d[62]),"+f"(d[63]),"+f"(d[64]),"+f"(d[65]),"+f"(d[66]),"+f"(d[67]),"+f"(d[68]),"+f"(d[69]),"+f"(d[70]),"+f"(d[71]),"+f"(d[72]),"+f"(d[73]),"+f"(d[74]),"+f"(d[75]),"+f"(d[76]),"+f"(d[77]),"+f"(d[78]),"+f"(d[79]) : "r"(a[0]),"r"(a[1]),"r"(a[2]),"r"(a[3]),"l"(db),"r"(sc));
}
__device__ __forceinline__ void wg_ss8_10(float* d, uint64_t da, uint64_t db, int sc) {
  asm volatile("{.reg .pred p; setp.ne.b32 p, %6, 0; wgmma.mma_async.sync.aligned.m64n8k16.f32.bf16.bf16 {%0,%1,%2,%3}, %4, %5, p, 1, 1, 1, 0;}"
    : "+f"(d[0]),"+f"(d[1]),"+f"(d[2]),"+f"(d[3]) : "l"(da),"l"(db),"r"(sc));
}

constexpr uint32_t DB = 1024;
constexpr int WSLOT = 24576, NW = 6, ASLOT = 8192, ARING = 4 * ASLOT;
constexpr int OFF_A = NW * WSLOT;
constexpr int OFF_PB = OFF_A + 2 * ARING;
constexpr int OFF_CV = OFF_PB + 16384, OFF_ST = OFF_CV + 768, OFF_TS = OFF_ST + 256, OFF_MODR = OFF_TS + 512, OFF_BAR = OFF_MODR + 80, SMEM_BYTES = OFF_BAR + 1168;
constexpr int OFF_BX = OFF_PB, OFF_AX = OFF_BX + 12288, OFF_RT = OFF_AX + 2048, OFF_GB = OFF_RT + 512, OFF_CO = OFF_CV;
constexpr int OFF_UV = 5 * WSLOT, OFF_UVE = OFF_PB, OFF_SX = OFF_A + ARING + 3 * ASLOT, OFF_X1 = 2 * WSLOT + ASLOT, OFF_XCH = WSLOT;
constexpr int OFF_Q = 0, KV_V = 4096, KV_H = 8192, F_E = 16, F_O = 4176, OFF_TAP = 168576, OFF_MR = OFF_A + 3 * ASLOT;
constexpr uint64_t pk5(int a, int b, int c, int d, int e) { return (uint64_t)(a / 128) | (uint64_t)(b / 128) << 12 | (uint64_t)(c / 128) << 24 | (uint64_t)(d / 128) << 36 | (uint64_t)(e / 128) << 48; }
constexpr uint64_t T_KV = pk5(20480, 30720, 40960, 180224, 190464), T_F = pk5(51200, 59648, 200192, 147456, 155904), T_X = pk5(208512, 164352, 68096, 208512, 164352),
                   T_P = pk5(131072, OFF_PB, 114688, 131072, OFF_PB);
__host__ __device__ __forceinline__ uint32_t tab(uint64_t t, int c) { return ((uint32_t)(t >> (12 * c)) & 0xFFF) << 7; }
enum { B_KV = 0, B_FRAW = 5, B_Q = 10, B_XR = 16, B_MR = B_XR + 5, B_QTOK, B_ST1, B_MODR, B_S3 = B_MODR + 5, B_FIN, B_FL = 32, B_PFULL = B_FL + 5, B_PEMPTY = B_PFULL + 5, B_FRDY = B_PEMPTY + 5,
       B_EXT = B_FRDY + 5, B_QTD, B_LAG, B_GB, B_UVD, B_TURN, B_FULL = 60, B_RETRY = B_FULL + 33, B_XFREE = B_RETRY + 9, B_BX, B_UVB, B_UVE, B_SX, B_EMPTY = 109 };
static_assert(B_MODR + 5 <= B_FL && B_UVD < B_FULL && B_SX + 2 == B_EMPTY - 1, "barrier groups");
#define BAR(i) (base + OFF_BAR + 8 * (i))

constexpr int NE = 24;
struct Maps { CUtensorMap km, v, q, kh, tap, wm, w1s, w3s, xs, w1, w3, w1e, w3e, x1s, x1b, w2a, w2b, outa, outb; };
struct Ptrs { const bf16 *ssmk, *c, *ssmd; Scratch* g; uint64_t prog, cprog[2]; int boff, te, pe, th, zero; uint32_t cn, c0, fin, turn, mr2, m3, seq; float one; uint2 sched[NE]; uint32_t wdep[20], wt[5]; uint2 w2t[12]; int hid[3][9]; };

#define REGION_IDS int tid, lane, bid; \
  asm volatile("mov.u32 %0, %%tid.x;" : "=r"(tid)); asm volatile("mov.u32 %0, %%laneid;" : "=r"(lane)); asm volatile("mov.u32 %0, %%ctaid.x;" : "=r"(bid)); \
  const int i0 = tid & 127; (void)i0; (void)lane; (void)bid

__device__ __forceinline__ void ffn_role(int& h, int& j, int& r) {
  uint32_t b;
  asm volatile("mov.u32 %0, %%ctaid.x;" : "=r"(b));
  const uint32_t c = b >> 1, q = (c - 36) * 37 >> 8, e = c - 36 - 7 * q;
  h = b & 1;
  const uint32_t k = c < 4 ? 0 : c < 36 ? (c - 4) & 7 : e + 1, p = c < 4 ? c : c < 36 ? (c - 4) >> 3 : q, up = c - 4 >= 32;
  j = 2 * (k & 1) + up;
  r = 2 * (k & 6) + p;
}
__device__ __forceinline__ int fslice(int j, int e) { return e == 2 ? j ^ 1 : (~j & 2) + e; }
__device__ __forceinline__ int mod_ch(int p) { return p < 40 ? (p >> 3) * 128 + (p & 1) * 64 : 64 * (p < 50 ? p - 40 : p - 50); }
__device__ __forceinline__ int mod_col(int p) { return mod_ch(p) + 640 * (p < 40 ? 0x4210 >> (2 * (p & 6)) & 7 : p < 50 ? 3 : 5); }
__device__ __forceinline__ uint32_t mod_sum(uint2 v) { return pack_bf16(0.f, __uint_as_float(v.x) + __uint_as_float(v.y)); }

constexpr int NT = 3, LAG2 = 29, MG = 4;
__device__ __forceinline__ int w_block(int up, int m) { return m == 1 ? 2 + 3 * up : 3 * (m >> 1) + up; }
__host__ __device__ constexpr int w2_at(int v) { return 8192 * (v ? 0x0613030008ull >> v % 5 * 8 & 255 : 15); }
__host__ __device__ constexpr int w2_step(int v) { return 8192 * (v ? 0x32113 >> v % 5 * 4 & 15 : 1); }
__host__ __device__ constexpr int hid_at(int m, int g) { return 8192 * ((g ? 0x0D07110F1816ull : 0x0A19101A1412ull) >> m % 6 * 8 & 255); }
__host__ __device__ constexpr uint32_t w2_desc(int v) { return (DB + w2_at(v)) >> 4 | w2_step(v) << 12; }
__device__ __forceinline__ int next_slot(int s) { return s >= 4 * WSLOT ? 0 : s + WSLOT; }

template <int U> __device__ __forceinline__ void cstep(float* acc, const uint32_t* A, uint64_t db) {
  const uint32_t* a = A + 4 * U;
  const uint64_t d = db + 16 * U;
  if (U == 4) { wg_rs64_0(acc + 96, A, db + 192, 0); wg_rs48_0(acc + 96, A + 4, db + 208, 1); wg_rs32_0(acc + 96, A + 8, db + 224, 1); wg_rs16_0(acc + 96, A + 12, db + 240, 1); }
  if (U <= 4) wg_rs192_0(acc, a, d, U);
  if (U == 5) wg_rs176_0(acc, a, d, 1);
  if (U == 6) wg_rs160_0(acc, a, d, 1);
  if (U == 7) wg_rs144_0(acc, a, d, 1);
  if (U == 8) wg_rs128_0(acc, a, d, 1);
  if (U == 9) wg_rs112_0(acc, a, d, 1);
  if (U == 10) wg_rs96_0(acc, a, d, 1);
  if (U == 11) wg_rs80_0(acc, a, d, 1);
  if (U == 12) wg_rs64_0(acc, a, d, 1);
  if (U == 13) wg_rs48_0(acc, a, d, 1);
  if (U == 14) wg_rs32_0(acc, a, d, 1);
  if (U == 15) wg_rs16_0(acc, a, d, 1);
}
template <int U0, int U1> __device__ __forceinline__ void csteps(float* acc, const uint32_t* A, uint64_t db) {
  cstep<U0>(acc, A, db);
  if constexpr (U0 > U1) csteps<U0 - 1, U1>(acc, A, db);
}
template <int U0, int U1> __device__ __forceinline__ void cload(uint32_t* A, uint32_t fa) {
  asm volatile("{ld.shared.b32 %0, [%4+%5]; ld.shared.b32 %1, [%4+%5+128]; ld.shared.b32 %2, [%4+%5+16]; ld.shared.b32 %3, [%4+%5+144];}"
               : "=r"(A[4 * U0]), "=r"(A[4 * U0 + 1]), "=r"(A[4 * U0 + 2]), "=r"(A[4 * U0 + 3]) : "r"(fa), "n"(256 * U0) : "memory");
  if constexpr (U0 > U1) cload<U0 - 1, U1>(A, fa);
}

__device__ __forceinline__ uint2 c_load(const bf16* c) {
  REGION_IDS;
  return make_uint2(ldg32(c + 320 * (bid & 1) + 2 * i0), ldg32(c + 320 * (bid & 1) + 256 + 2 * lane));
}
__device__ __forceinline__ void silu_vector(uint2 c, uint32_t base) {
  REGION_IDS;
  sts32(base + OFF_CV + 4 * i0, pack_bf16(silu_f(bf_lo(c.x)), silu_f(bf_hi(c.x))));
  sts32(base + OFF_CV + 512 + 4 * lane, pack_bf16(silu_f(bf_lo(c.y)), silu_f(bf_hi(c.y))));
  fence_async_smem();
}

__device__ __forceinline__ void mod_poll(Scratch* G, uint32_t base, int c, int n, uint32_t epoch) {
  REGION_IDS;
  const int e = 4 * c + (lane & (4 * n - 1));
  uint2 m;
  int it = 0;
#pragma unroll 1
  do m = ld_relaxed64(&G->modc[bid][8 + e]); while (__any_sync(~0u, ((m.x ^ epoch) | (m.y ^ epoch)) & 1) && ++it < SPIN_LIMIT);
  sts32(base + OFF_MODR + 4 * e, __byte_perm(badd2(mod_sum(m), (lane & 1) * 0x3F800000u), 0, 0x3232));
  __syncwarp();
  if (elect()) { mbar_arrive(BAR(B_MODR + c)); if (n > 1) mbar_arrive(BAR(B_MODR + c + 1)); }
}
__device__ __forceinline__ void row_stats(Scratch* G, uint32_t base, uint32_t epoch) {
  REGION_IDS;
  mbar_wait_cluster(BAR(B_ST1));
  if (lane < 8) red_hint(G->hint[5][lane]);
  const uint2 x = lds64(base + OFF_ST + 8 * (lane & 15)), y = lds64(base + OFF_ST + 128 + 8 * (lane & 15));
  float m, sd;
  ln_final(__uint_as_float(x.x) + __uint_as_float(y.x), __uint_as_float(x.y) + __uint_as_float(y.y), m, sd);
  sd = rbf(rcpf(sd));
  const uint32_t mr = pack_bf16(sd, -rbf(m) * sd), tg = lane & 7 ? 0 : lane & 8 ? 1 : 0x8000;
  const uint32_t o = __byte_perm(__shfl_sync(~0u, mr, 2 * lane & 14), __shfl_sync(~0u, mr, (2 * lane & 14) + 1), (lane & 8) ? 0x7632 : 0x5410);
  if (lane < 16) st_relaxed32(&G->st1[lane >> 3][8 * bid + (lane & 7)], (o & ~tg) | ((epoch & 1) * tg));
  if (elect()) mbar_arrive(BAR(B_FIN));
}
template <int B, int NEXT> __device__ __forceinline__ void strip(Scratch* G, const CUtensorMap* map, uint32_t base, int c, uint32_t epoch, uint32_t& ph, uint32_t& pre, float4& s) {
  REGION_IDS;
  int h, j, r, it = 0;
  ffn_role(h, j, r);
  const uint32_t buf = base + OFF_SX + 4096 * B, a = buf + 32 * lane;
#pragma unroll 1
  while (__any_sync(~0u, pre != 64 * epoch) && ++it < SPIN_LIMIT) pre = ld_relaxed32(G->xsh[c][(r & 6) + (j >> 1)]);
#pragma unroll 1
  for (it = 0; it < SPIN_LIMIT; it++) {
    if (elect()) { mbar_expect_tx(BAR(B_SX + B), 4096); tma2d(buf, map, 128 * r + 64 * h, D_ * (epoch & 1) + 128 * c + 32 * j, BAR(B_SX + B)); }
    mbar_wait(BAR(B_SX + B), ph);
    ph ^= 1;
    if (__all_sync(~0u, min(min(lds32(a), lds32(a + 1024)), min(lds32(a + 2048), lds32(a + 3072))))) break;
  }
  pre = 0;
  if (c == NEXT - 1 || c == NEXT - 2) pre = ld_relaxed32(G->xsh[c + 1][(r & 6) + (j >> 1)]);
#pragma unroll 1
  for (uint32_t o = buf + 4 * lane; o < buf + 4096; o += 1024) {
    uint32_t x[8];
#pragma unroll
    for (int i = 0; i < 8; i++) x[i] = lds32(o + 128 * i);
#pragma unroll
    for (int i = 0; i < 8; i++) { const float lo = bf_lo(x[i]), hi = bf_hi(x[i]); s.x += lo; s.y = fmaf(lo, lo, s.y); s.z += hi; s.w = fmaf(hi, hi, s.w); }
  }
}
__device__ __forceinline__ void planes(uint32_t a, uint4& y) {
  uint4 z = lds128(a + 4096);
  y.x = badd2(y.x, z.x); y.y = badd2(y.y, z.y); y.z = badd2(y.z, z.z); y.w = badd2(y.w, z.w);
  z = lds128(a + 8192);
  const uint4 m = lds128(a + 12288);
  y.x = badd2(y.x, badd2(z.x, m.x)); y.y = badd2(y.y, badd2(z.y, m.y)); y.z = badd2(y.z, badd2(z.z, m.z)); y.w = badd2(y.w, badd2(z.w, m.w));
}
__device__ __forceinline__ void mr_poll(Scratch* G, uint32_t base, uint32_t epoch) {
  int it = 0;
#pragma unroll 1
  while (__any_sync(~0u, ld_relaxed32(G->hint[5][4 * (blockIdx.x >> 6) + (blockIdx.x >> 3 & 3)]) != epoch << 7) && ++it < SPIN_LIMIT);
  if (elect()) { mbar_expect_tx(BAR(B_MR), 8192); bulk_load(base + OFF_MR, G->st1, 8192, BAR(B_MR)); mbar_arrive(BAR(B_QTOK)); }
}

__global__ void __cluster_dims__(2, 1, 1) __launch_bounds__(512, 1) k_fused(const __grid_constant__ Ptrs P, const __grid_constant__ Maps maps) {
  Scratch* const G = P.g;
  extern __shared__ __align__(1024) uint8_t smem_raw[];
  const uint32_t t_start = clock();
  const uint32_t base = __shfl_sync(~0u, smem_u32(smem_raw), 0);
  uint32_t t_iss = 0;
  if (threadIdx.x < 32 && blockIdx.x < 128) {
    mbar_init<1>(BAR(0), 1);
    if (elect()) {
      const int c0 = 64 * (blockIdx.x & 1), c1 = 2 * (blockIdx.x & 126);
      mbar_expect_tx(BAR(B_KV), 12288);
      tma3d(base + tab(T_KV, 0), &maps.km, c0, c1, 0, BAR(B_KV));
      tma3d(base + tab(T_KV, 0) + KV_V, &maps.v, c0, c1, 0, BAR(B_KV));
      tma3d(base + tab(T_KV, 0) + KV_H, &maps.kh, c0, c1 - 1, 5, BAR(B_KV));
      tma3d(base + OFF_TAP, &maps.tap, 0, blockIdx.x & 1, 0, BAR(B_KV));
    }
    if (P.boff) mbar_wait(BAR(0));
  }
  if ((base & 0xFFFFFFu) != DB) __trap();
  const int wid = __shfl_sync(~0u, threadIdx.x >> 5, 0), wg = wid >> 2, w = wid & 3;
  if (blockIdx.x + P.boff >= 128) {
    REGION_IDS;
    constexpr int nu = 30;
    auto tile = [&](int n) { return 2 * n + (blockIdx.x >> 1 & 1); };
    auto fetch = [&](int n, int b) {
      if (elect()) {
        mbar_expect_tx(BAR(n), 40960);
#pragma unroll
        for (int k = 0; k < 5; k++) tma3d(base + 40960 * b + 8192 * k, &maps.wm, mod_col(tile(n)), 320 * (blockIdx.x & 1) + 64 * k, 0, BAR(n));
      }
    };
    if (P.boff) __syncthreads();
    if (wid == 12) {
      mbar_init<4>(BAR(0), 1);
#pragma unroll 1
      for (int n = 0; n < 4; n++) fetch(n, n);
      mbar_init<26>(BAR(4), 1);
      mbar_init<60>(BAR(32), 4);
    }
    const uint32_t par = ~ld_relaxed32(G->hint[7][0]) >> 7 & 1;
    silu_vector(c_load(P.c), base);
    __syncthreads();
    if (wid == 12) {
      wait_clock(t_start + P.th);
#pragma unroll 1
      for (int n = 4, b = 4; n < nu; n++) {
        if (n >= 5) mbar_wait(BAR(27 + n));
        fetch(n, b);
        b = b == 4 ? 0 : b + 1;
      }
    } else if (wg < 2) {
      uint32_t cv[40];
#pragma unroll
      for (int k = 0; k < 40; k++) cv[k] = lds32(base + OFF_CV + 16 * k + 4 * (lane & 3));
      const uint32_t a0 = base + 128 * ((lane & 7) + (lane >> 4) * 8) + (((2 * w + (lane >> 3 & 1)) ^ (lane & 7)) << 4);
#pragma unroll 1
      for (int n = wg; n < nu; n += 2) {
        float d[16] = {};
        mbar_wait(BAR(n));
#pragma unroll
        for (int k0 = 0; k0 < 20; k0 += 10) {
          uint32_t a[40];
#pragma unroll
          for (int k = 0; k < 10; k++) ldmatrix_x4_t(a + 4 * k, a0 + 40960 * (n % 5) + 2048 * (k0 + k));
#pragma unroll
          for (int k = 0; k < 10; k++)
            asm("mma.sync.aligned.m16n8k16.row.col.f32.bf16.bf16.f32 {%0,%1,%2,%3}, {%4,%5,%6,%7}, {%8,%9}, {%0,%1,%2,%3};"
                : "+f"(d[4 * (k & 3)]), "+f"(d[4 * (k & 3) + 1]), "+f"(d[4 * (k & 3) + 2]), "+f"(d[4 * (k & 3) + 3])
                : "r"(a[4 * k]), "r"(a[4 * k + 1]), "r"(a[4 * k + 2]), "r"(a[4 * k + 3]), "r"(cv[2 * (k0 + k)]), "r"(cv[2 * (k0 + k) + 1]));
        }
        arrive1(BAR(32 + n));
        if (!(lane & 3)) {
          sts32(base + 204800 + 256 * n + 64 * w + lane, __float_as_uint(d[0] + d[4] + (d[8] + d[12])));
          sts32(base + 204800 + 256 * n + 64 * w + lane + 32, __float_as_uint(d[2] + d[6] + (d[10] + d[14])));
        }
        arrive1(BAR(62 + n));
      }
    } else if (wg == 2) {
#pragma unroll 1
      for (int n = w; n < nu; n += 4) {
        const int t = tile(n), ch = mod_ch(t) + lane;
        uint32_t* q = (uint32_t*)(t < 40 ? &G->modc[ch & 127][8 + (t >> 1)] : &G->modv[t >= 50][ch]) + (bid & 1);
        mbar_wait(BAR(62 + n));
        const uint32_t x = (lds32(base + 204800 + 256 * n + 4 * lane) & ~1u) | par, y = (lds32(base + 204928 + 256 * n + 4 * lane) & ~1u) | par;
        publish(q, x);
        publish(q + (t < 40 ? 2048 : 64), y);
        if (t < 40 && (t & 6) == 6) {
          q = (uint32_t*)&G->modv[2][ch] + (bid & 1);
          publish(q, x);
          publish(q + 64, y);
        }
      }
    }
    return;
  }
  if (wid < 15) mbar_init<4>(BAR(4 * wid + (wid == 0)), wid < 8 ? 1 : 4);
  asm volatile("fence.mbarrier_init.release.cluster; bar.sync 0, 512;" ::: "memory");
  asm volatile("barrier.cluster.arrive.relaxed.aligned;" ::: "memory");
  if (wid == 4) {
    const int c0 = 64 * (blockIdx.x & 1), c1 = 2 * (blockIdx.x & 126);
    wait_clock(t_start + P.te);
    if (elect()) { tma3d(base + tab(T_KV, 1), &maps.km, 128 + c0, c1, 0, BAR(B_KV + 1)); tma3d(base + tab(T_KV, 1) + KV_H, &maps.kh, 128 + c0, c1 - 1, 5, BAR(B_KV + 1)); }
    wait_clock(t_start + P.te + P.pe);
    if (elect()) tma3d(base + tab(T_KV, 1) + KV_V, &maps.v, 128 + c0, c1, 0, BAR(B_KV + 1));
    wait_clock(t_start + P.te + 2 * P.pe);
    if (elect()) bulk_load(base + tab(T_F, 0) + F_E, P.ssmk + blockIdx.x * S_, 4096, BAR(B_FRAW));
    wait_clock(t_start + P.te + 3 * P.pe);
    if (elect()) tma3d(base + OFF_Q, &maps.q, c0, c1, 0, BAR(B_Q));
  }
#define LAUNCHES const uint32_t launches = ld_relaxed32(G->hint[7][blockIdx.x >> 4])
#define EPOCH ((__shfl_sync(~0u, launches, 0) >> 7) + 1)
  if (wg == 3) {
    asm volatile("setmaxnreg.dec.sync.aligned.u32 24;");
    if (w == 1) {
      {
        REGION_IDS;
        const int c1 = 2 * (bid & 126);
#pragma unroll 1
        for (int e = 4; e < NE; e++) {
          const uint2 x = P.sched[e];
          const uint32_t kind = x.x >> 16 & 15, ch = x.x >> 13 & 0x380, dst = base + (x.y & 0x3FFFF), b = BAR(x.y >> 18);
          wait_clock(t_start + (x.x & 0xFFFF));
          if (kind < 3 && elect()) tma3d(dst, &maps.km + kind, ch + 64 * (bid & 1), c1, 0, b);
          if (kind == 0 && elect()) tma3d(dst + KV_H, &maps.kh, ch + 64 * (bid & 1), c1 - 1, 5, b);
          if (kind == 3 && elect()) bulk_load(dst, P.ssmk + (ch + bid) * S_, 4096, b);
          if ((uint32_t)(e - 8) < 13 && elect()) prefetch_map(&maps.w1s + (e - 8));
        }
      }
      cluster_wait();
      int h, j, r;
      ffn_role(h, j, r);
      mbar_wait(BAR(B_QTD));
      mbar_wait(BAR(B_FL));
#pragma unroll 1
      for (int u = 0; u < 20; u++) {
        const uint32_t x = P.wdep[u], s = base + (x & ~8191u);
        if (u < 5) wait_clock(t_start + P.wt[u]);
        mbar_wait(BAR(opaque(x & 255)));
        if (elect()) {
          mbar_expect_tx(BAR(B_FULL + u), WSLOT + 4 * (x & 4096));
#pragma unroll
          for (int k = 0; k < 6; k++) tma3d(s + 4096 * w_block(k & 1, k >> 1), &maps.w1s + (k & 1), 0, 32 * u, 3 * (4 * h + j) + (k >> 1), BAR(B_FULL + u));
        }
      }
#pragma unroll 1
      for (int v = 0; v < 12; v++) {
        const int q = v * 11 >> 5, e = v - 3 * q, k32 = 24 * h + (q ? 6 * fslice(j, e) + 2 * q - 2 : 6 * j + 2 * e);
        const uint2 x = P.w2t[v];
        mbar_wait(BAR(x.y));
        if (elect()) {
          mbar_expect_tx(BAR(B_FULL + 20 + v), q ? WSLOT + 2 * ASLOT : WSLOT);
#pragma unroll
          for (int k = 0; k < 3; k++) tma5d(base - DB + 16 * ((x.x & 0xFFFF) + k * (x.x >> 16)), &maps.w2a + (q > 0), k < 2 ? 128 * j + 64 * k : 512 + 32 * (j & 2), k32, BAR(B_FULL + 20 + v));
        }
      }
    } else if (w == 0) {
      LAUNCHES;
      uint32_t epoch;
      {
        REGION_IDS;
        const unsigned* hp = G->hint[0][4 * (bid >> 6) + (bid >> 3 & 3)];
        uint32_t v = ld_relaxed32(hp + 256 * min(lane, 5));
        if (lane < 3) sts128(base + tab(T_X, lane) + 4096, 0, 0, 0, 0);
        if (lane && lane < B_Q + 5) mbar_expect_tx(BAR(lane), lane < B_FRAW ? 9728 : 4096);
        epoch = EPOCH;
        fence_async_smem();
        const uint32_t rdy = __ballot_sync(~0u, v == epoch << 6);
        uint32_t nx = 0, nm = 0;
#pragma unroll 1
        for (uint32_t seq = P.seq; seq; seq >>= 2) {
          int it = 0;
          if (seq & 1) {
            if (!(seq & 2)) mod_poll(G, base, nm, 1 + (seq == 13), epoch);
            nm++;
          } else if (seq & 2) {
            mr_poll(G, base, epoch);
          } else {
            if (!(rdy >> nx & 1)) {
#pragma unroll 1
              while (__any_sync(~0u, ld_relaxed32(hp + 256 * nx) != epoch << 6) && ++it < SPIN_LIMIT);
            }
            if (nx >= 3) mbar_wait(BAR(B_PFULL - 3 + nx));
            if (elect()) { mbar_expect_tx(BAR(B_XR + nx), 4096); bulk_load(base + tab(T_X, nx), G->xr + (128 * nx + bid) * 256, 4096, BAR(B_XR + nx)); }
            nx++;
          }
        }
      }
      REGION_IDS;
      int h, j, r;
      ffn_role(h, j, r);
      mbar_wait(BAR(B_PFULL + 3));
      {
        float4 s = {};
        uint32_t ph = 0, pre = 0;
#pragma unroll 1
        for (int c = 2; c < 4; c++) strip<1, 3>(G, &maps.x1s, base, c, epoch, ph, pre, s);
        __syncwarp();
        sts128(base + OFF_SX + 4096 + 16 * lane, __float_as_uint(s.x), __float_as_uint(s.y), __float_as_uint(s.z), __float_as_uint(s.w));
        arrive1(BAR(B_S3));
      }
      ffn_role(h, j, r);
      cluster_wait();
      mbar_wait(BAR(B_UVD));
      asm volatile("fence.acq_rel.gpu;" ::: "memory");
      if (lane < 8) red_hint(G->hint[7][lane]);
      unsigned x;
      int it = 0;
#pragma unroll 1
      do { asm volatile("ld.acquire.gpu.global.u32 %0, [%1];" : "=r"(x) : "l"(G->hint[7][bid >> 4]) : "memory"); } while (__any_sync(~0u, x != 128 * epoch) && ++it < SPIN_LIMIT);
      fence_async_all();
      const int ch = D_ * (epoch & 1);
      mbar_wait(BAR(B_EXT));
      mbar_wait(BAR(B_EMPTY + 18));
      if (elect()) {
        mbar_expect_tx(BAR(B_FULL + 32), 20480);
#pragma unroll
        for (int k = 0; k < 4; k++) tma2d(base + (k < 3 ? OFF_X1 + k * WSLOT : OFF_SX), &maps.x1b, 128 * r + 64 * h, ch + 128 * j + 32 * (k ^ (j & 1)), BAR(B_FULL + 32));
        tma2d(base + OFF_SX + 4096, &maps.x1b, 128 * r + 64 * h, ch + 512 + 32 * j, BAR(B_FULL + 32));
        mbar_expect_tx(BAR(B_FULL), 8192); mbar_expect_tx(BAR(B_FULL + 1), 8192); mbar_expect_tx(BAR(B_FULL + 2), 4096);
      }
      mbar_wait(BAR(B_EMPTY + 27));
      if (elect()) mbar_arrive_remote(mapa(BAR(B_XFREE), h ^ 1));
    } else {
      LAUNCHES;
      uint32_t epoch;
      {
        REGION_IDS;
        uint32_t dv;
        asm volatile("ld.global.nc.u16 %0, [%1];" : "=r"(dv) : "l"(P.ssmd + 128 * (lane & 7) % D_ + bid));
        if (lane < 5) sts128(base + tab(T_F, lane) + (w & 1) * (F_O - 16), 0, 0, 0, 0);
        epoch = EPOCH;
        __syncwarp();
#pragma unroll 1
        for (int c = 0; c < 5; c++) {
          const float d = i0 == 64 ? bf_lo(dv) : 0.f;
          dv = __shfl_down_sync(~0u, dv, 1);
          const uint32_t a = base + tab(T_F, c) + 16 * (i0 - 64);
          mbar_wait(BAR(B_FRAW + c));
#pragma unroll
          for (int k = 0; k < 4; k++) {
            uint4 x = lds128(a + F_E + 1024 * k);
            const uint32_t pv = lds32(a + F_E - 4 + 1024 * k);
            if (k == 0) { x.x = pack_bf16(bf_lo(x.x) + d, bf_hi(x.x)); sts32(a + F_E, x.x); }
            sts128(a + F_O + 1024 * k, __byte_perm(pv, x.x, 0x5432), __byte_perm(x.x, x.y, 0x5432), __byte_perm(x.y, x.z, 0x5432), __byte_perm(x.z, x.w, 0x5432));
          }
          __syncwarp();
          if (elect()) mbar_arrive2(BAR(B_FRDY + c));
          if (c == 0 && w == P.fin) row_stats(G, base, epoch);
        }
      }
      REGION_IDS;
      int h, j, r;
      ffn_role(h, j, r);
      cluster_wait();
      if (w == 2) {
        uint32_t rdy = 0, s = 0;
        mbar_wait(BAR(B_QTD));
        mbar_wait(BAR(B_FL + 2));
#pragma unroll 1
        for (int n = 0; n < 10; n++) {
          if (n == P.cn) {
            mbar_wait(BAR(B_PEMPTY + 3));
            if (elect()) {
              tma3d(base + OFF_UV, &maps.w1 + (r & 1), 0, 40 * (r & 14), 3 * (4 * h + j), BAR(B_UVB));
              tma3d(base + OFF_UV + 12288, &maps.w1 + (r & 1), 0, 40 * (r & 14) + 32, 3 * (4 * h + j), BAR(B_UVB));
            }
            {
              const uint2* mp = &G->modv[lane & 4 ? 0 : 2][40 * (r & 14) + (lane & 24) + 2 * (lane & 3)];
              uint4 v[3];
              int it = 0;
#pragma unroll 1
              do {
                v[0] = ld_relaxed128(mp); v[1] = ld_relaxed128(mp + 32); v[2] = ld_relaxed128(mp + 64 - (lane & 16));
              } while (__any_sync(~0u, ((v[0].x ^ epoch) | (v[0].y ^ epoch) | (v[0].z ^ epoch) | (v[0].w ^ epoch) | (v[1].x ^ epoch) | (v[1].y ^ epoch) | (v[1].z ^ epoch) | (v[1].w ^ epoch) |
                                        (v[2].x ^ epoch) | (v[2].y ^ epoch) | (v[2].z ^ epoch) | (v[2].w ^ epoch)) & 1) && ++it < SPIN_LIMIT);
#pragma unroll
              for (int i = 0; i < 3; i++)
                sts32(base + OFF_CO + 128 * i + 4 * lane, badd2(pack_bf16(__uint_as_float(v[i].x) + __uint_as_float(v[i].y), __uint_as_float(v[i].z) + __uint_as_float(v[i].w)), lane & 4 ? 0 : 0x3F803F80u));
            }
            fence_async_smem();
            __syncwarp();
            if (elect()) mbar_expect_tx(BAR(B_UVB), WSLOT);
          }
          mbar_wait(BAR(n < 2 ? B_FL + 3 + n : n == 2 ? B_PFULL + 4 : B_EMPTY + 2 * n - 5));
#pragma unroll 1
          for (int it = 0; !(rdy >> n & 1) && it < SPIN_LIMIT; it++) rdy = __ballot_sync(~0u, ld_relaxed32(G->xsh[lane < 10 ? lane >> 1 : 0][(r & 6) + (lane & 1)]) == 64 * epoch);
          if (elect()) {
            tma2d(base + OFF_A + s, &maps.xs, 128 * r + 64 * h, 64 * n, BAR(B_FULL + 2 * n));
            tma2d(base + OFF_A + ARING + s, &maps.xs, 128 * r + 64 - 64 * h, 64 * n, BAR(B_FULL + 2 * n));
          }
          s = s == 2 * ASLOT ? 0 : s + ASLOT;
        }
      } else {
        if (P.m3 < 5) mod_poll(G, base, P.m3, 1, epoch);
        float4 s = {};
        uint32_t ph = 0, pre = 0;
        mbar_wait(BAR(B_FL + 2));
        mbar_wait(BAR(B_PFULL + 3));
#pragma unroll 1
        for (int c = 0; c < 5; c = c == 1 ? 4 : c + 1) {
          if (c == 4) {
            ffn_role(h, j, r);
            mbar_wait(BAR(B_PEMPTY + 4));
            if (elect()) {
              mbar_expect_tx(BAR(B_UVE), 6144);
              tma3d(base + OFF_UVE, &maps.w1e + (r & 1), 0, 40 * (r & 14) + 64, 3 * (4 * h + j), BAR(B_UVE));
            }
          }
          strip<0, 1>(G, &maps.x1s, base, c, epoch, ph, pre, s);
        }
        mbar_wait(BAR(B_S3));
        const uint4 y = lds128(base + OFF_SX + 4096 + 16 * lane);
        const float s0 = s.x + __uint_as_float(y.x), q0 = s.y + __uint_as_float(y.y), s1 = s.z + __uint_as_float(y.z), q1 = s.w + __uint_as_float(y.w);
        ffn_role(h, j, r);
        asm volatile("{.reg .b128 t, x; .reg .b64 a, b; mov.b64 a, {%1,%2}; mov.b64 b, {%3,%4}; mov.b128 x, {a,b}; atom.relaxed.gpu.global.exch.b128 t, [%0], x;}"
                     ::"l"(&G->st2[2 * r + h][j][4 * lane]), "r"((__float_as_uint(s0) & ~1u) | (epoch & 1)), "f"(q0), "r"((__float_as_uint(s1) & ~1u) | (epoch & 1)), "f"(q1) : "memory");
        uint4* z = G->x1[~epoch & 1] + 1280 * bid + lane;
#pragma unroll 1
        for (int k = 0; k < 40; k++) st_relaxed128(z + 32 * k, 0, 0, 0, 0);
      }
    }
  } else if (wg == 2) {
    asm volatile("setmaxnreg.dec.sync.aligned.u32 40;");
    mbar_init<12>(BAR(B_FULL + 12 * w), 1);
    mbar_init<9>(BAR(B_EMPTY - 1 + 9 * w), 8);
    asm volatile("fence.mbarrier_init.release.cluster;" ::: "memory");
    LAUNCHES;
    const uint32_t epoch = EPOCH;
    cluster_wait();
#pragma unroll 1
    for (uint64_t prog = P.prog; prog; prog >>= 4) {
      REGION_IDS;
      const int s = (prog & 7) - 1;
      if (!(prog & 8)) {
        const uint32_t a = base + tab(T_KV, s) + 128 * (lane & 3) + ((w ^ (lane & 3)) << 4) + 4 * (lane & 16) + (lane & 12), keep = ~(lane & 1), bit = epoch & lane & 1;
        uint4* dst = G->xr + (128 * s + 64 * (bid & 1) + 8 * w + 2 * (lane & 16) + (lane >> 1 & 6)) * 256 + 255 - 4 * (bid >> 1) - (lane & 3);
        mbar_wait(BAR(B_KV));
        mbar_wait(BAR(B_KV + s));
        const uint4 wv = lds128(base + OFF_TAP + 512 * s + 64 * w + 16 * (lane & 16) + 4 * (lane & 12));
        uint32_t kk[11], r[8];
#pragma unroll
        for (int k = 0; k < 11; k++) kk[k] = k < 3 ? lds32((a ^ (64 * (k & 1))) + KV_H + 512 * k) : lds32((a ^ (64 * (~k & 1))) + 512 * (k - 3));
        if (elect()) red_hint(G->hint[s][4 * (bid & 1) + w]);
#pragma unroll
        for (int k = 0; k < 8; k++) r[k] = lds32((a ^ (64 * (k & 1))) + KV_V + 512 * k);
        const uint32_t w0 = __byte_perm(wv.x, wv.z, 0x5410), w1 = __byte_perm(wv.x, wv.z, 0x7632),
                       w2 = __byte_perm(wv.y, wv.w, 0x5410), w3 = __byte_perm(wv.y, wv.w, 0x7632);
#pragma unroll
        for (int k = 0; k < 8; k++) r[k] = bmul2(bfma2(kk[k + 3], w0, bfma2(kk[k + 2], w1, bfma2(kk[k + 1], w2, bmul2(kk[k], w3)))), r[k]);
        st_relaxed128(dst, (__byte_perm(r[7], r[6], 0x5410) & keep) | bit, __byte_perm(r[5], r[4], 0x5410), __byte_perm(r[3], r[2], 0x5410), __byte_perm(r[1], r[0], 0x5410));
        st_relaxed128(dst + 256, (__byte_perm(r[7], r[6], 0x7632) & keep) | bit, __byte_perm(r[5], r[4], 0x7632), __byte_perm(r[3], r[2], 0x7632), __byte_perm(r[1], r[0], 0x7632));
      } else if (s == 5) {
        mbar_wait(BAR(B_PFULL));
#pragma unroll
        for (int hf = 0; hf < 2; hf++) {
          const uint32_t a = base + tab(T_P, 0) + 16 * i0 + 2048 * hf;
          uint4 y = lds128(a);
          planes(a, y);
          sts128(a, y.x, y.y, y.z, y.w);
        }
      } else if (s >= 0) {
        const int tr = 4 * (lane & 1) + (lane >> 1 & 3);
        const uint32_t a = base + OFF_Q + 4096 * s + 128 * ((lane & 24) + tr) + ((w ^ tr) << 4);
        uint4* dst = G->qt + (128 * s + 64 * (bid & 1) + 8 * w + (lane >> 2)) * 256 + 4 * (bid >> 1) + (lane & 3);
        mbar_wait(BAR(B_Q + s));
#pragma unroll
        for (int k = 0; k < 2; k++) {
          uint32_t x[4];
          ldmatrix_x4_t(x, a ^ (64 * k));
          st_relaxed128(dst + 8192 * k, set_tag(x[0], ~lane & 1, epoch), x[1], x[2], x[3]);
        }
      } else if (w == 3) {
        row_stats(G, base, epoch);
      }
    }
    arrive1(BAR(B_QTD));
    {
      REGION_IDS;
      const uint32_t tag = opaque(~lane & 1);
      const uint32_t io = 16 * i0;
      uint4* gp = (uint4*)((char*)(G->xs + 256 * blockIdx.x) + io);
      constexpr int QO = -D_ * 256;
      const uint32_t sa = base + io;
      uint4 q[2];
      if (w == 0 && P.mr2) mr_poll(G, base, epoch);
      mbar_wait(BAR(B_QTOK));
      q[0] = ld_relaxed128(gp + QO);
      q[1] = ld_relaxed128(gp + QO + 128);
#pragma unroll 1
      for (int it = 0; it < SPIN_LIMIT; it++) {
        mbar_wait(BAR(B_MR), it & 1);
        const uint32_t x = lds32(sa + 16 * i0 + OFF_MR), y = lds32(sa + 16 * i0 + OFF_MR + 4096);
        sts32(sa + 16 * i0 + OFF_MR, x & 0xFFFF7FFFu);
        if (bar_all(3, !(((x >> 15 ^ epoch) | (y ^ epoch)) & 1))) break;
        if (w == 0 && elect()) { fence_async_smem(); mbar_expect_tx(BAR(B_MR), 8192); bulk_load(base + OFF_MR, G->st1, 8192, BAR(B_MR)); }
      }
#pragma unroll 1
      for (int c = 0; c < 5; c++) {
        mbar_wait(BAR(B_MODR + c));
        uint4 co = lds128(base + OFF_MODR + 16 * c);
        co.x = bmul2(co.x, co.z); co.y = bmul2(co.y, co.z);
        mbar_wait(BAR(B_PFULL + c));
        const uint32_t pb = io + (base + tab(T_P, c));
        gp = (uint4*)((char*)(G->xs + 256 * blockIdx.x + 32768 * c) + io);
#pragma unroll
        for (int hf = 0; hf < 2; hf++) {
#pragma unroll 1
          for (int it = 0; __any_sync(~0u, set_tag(q[hf].x, tag, epoch) != q[hf].x) && it < SPIN_LIMIT; it++) {
            q[hf] = ld_relaxed128(gp + QO + 128 * hf);
          }
          uint4 y = lds128(pb + 2048 * hf);
          if (c) planes(pb + 2048 * hf, y);
          const uint4 z = lds128(sa + OFF_MR + 2048 * hf), m = lds128(sa + OFF_MR + 2048 * hf + 4096);
          y.x = bfma2(bfma2(bfma2(q[hf].x, z.x, m.x), co.y, co.x), y.x, q[hf].x);
          if (hf) {
            __syncwarp();
            asm volatile("{.reg .pred p; elect.sync _|p, 0xffffffff; @p red.relaxed.gpu.global.add.u32 [%0], 1; @p mbarrier.arrive.shared::cta.b64 _, [%1];}"
                         ::"l"(G->xsh[c][2 * w + (blockIdx.x >> 6)]), "r"(BAR(B_PEMPTY + c)), "r"(y.x) : "memory");
          }
          y.y = bfma2(bfma2(bfma2(q[hf].y, z.y, m.y), co.y, co.x), y.y, q[hf].y);
          y.z = bfma2(bfma2(bfma2(q[hf].z, z.z, m.z), co.y, co.x), y.z, q[hf].z);
          y.w = bfma2(bfma2(bfma2(q[hf].w, z.w, m.w), co.y, co.x), y.w, q[hf].w);
          st_relaxed128(gp + 128 * hf, set_tag(bmul2(y.x, co.w), tag, epoch), bmul2(y.y, co.w), bmul2(y.z, co.w), bmul2(y.w, co.w));
          asm volatile("{.reg .pred p; .reg .b32 t; setp.ne.u32 p, %5, 0; max.u32 t, %1, 1; @!p st.relaxed.gpu.global.v4.u32 [%0+%6], {t,%2,%3,%4}; @p st.relaxed.gpu.global.v4.u32 [%0+%7], {t,%2,%3,%4};}"
                       ::"l"(gp + 128 * hf), "r"(y.x), "r"(y.y), "r"(y.z), "r"(y.w), "r"(epoch & 1), "n"(D_ * 4096), "n"(D_ * 8192) : "memory");
          if (c < 4) q[hf] = ld_relaxed128(gp + QO + 32768 + 128 * hf);
        }
      }
    }
    int h, j, r;
    ffn_role(h, j, r);
    {
      REGION_IDS;
      mbar_wait(BAR(B_UVB));
      float d[12] = {};
      fence_regs(d);
      wg_fence();
#pragma unroll
      for (int k = 0; k < 15; k++) {
        if (k == 12) { wg_commit(); mbar_wait(BAR(B_UVE)); wg_fence(); }
        wg_ss8_10(d + 4 * (k % 3), mkdesc(DB + (k < 12 ? OFF_UV + 12288 * (k / 6) + 4096 * (k % 3) + 2048 * (k / 3 & 1) : OFF_UVE + 2048 * (k % 3)), 16, 1024, 1),
                  mkdesc(DB + OFF_CO + 64 * (k / 3), 32, 128, 0), 1);
      }
      wg_commit();
      const int row = (r & 14) + (lane >> 2 & 1);
      uint32_t* dst = &G->uv[4 * h + j][32 * row + 4 * ((2 * w ^ row) & 6) + (lane & 3)];
      const uint32_t tag = !(lane & 3);
      wg_wait<0>();
      fence_regs(d);
      if (elect()) { red_hint(G->hint[8][4 * h + j]); mbar_arrive(BAR(B_UVD)); }
      uint32_t x[6];
#pragma unroll
      for (int k = 0; k < 6; k++) asm volatile("movmatrix.sync.aligned.m8n8.trans.b16 %0, %1;" : "=r"(x[k]) : "r"(pack_bf16(d[2 * k], d[2 * k + 1])));
      if (lane < 8) {
#pragma unroll
        for (int k = 0; k < 6; k++) st_relaxed32(dst + 512 * w_block(r & 1, k >> 1) + ((4 * k ^ lane) & 4), set_tag(x[k], tag, epoch));
      }
    }
    {
      REGION_IDS;
      if (w == 0) {
        int it = 0;
#pragma unroll 1
        while (__any_sync(~0u, ld_relaxed32(G->hint[8][4 * h + j]) != 64 * epoch) && ++it < SPIN_LIMIT);
        if (elect()) { mbar_expect_tx(BAR(B_BX), 12288); bulk_load(base + OFF_BX, G->uv[4 * h + j], 12288, BAR(B_BX)); }
      }
      const uint32_t* sp = &G->st2[2 * r + (h ^ (w >> 1))][0][2 * (i0 & 63)];
      uint2 x[4];
      int it = 0;
#pragma unroll 1
      do {
#pragma unroll
        for (int k = 0; k < 4; k++) x[k] = ld_relaxed64(sp + 128 * k);
      } while (__any_sync(~0u, ((x[0].x ^ epoch) | (x[1].x ^ epoch) | (x[2].x ^ epoch) | (x[3].x ^ epoch)) & 1) && ++it < SPIN_LIMIT);
      float m, sd;
      ln_final((__uint_as_float(x[0].x) + __uint_as_float(x[1].x)) + (__uint_as_float(x[2].x) + __uint_as_float(x[3].x)),
               (__uint_as_float(x[0].y) + __uint_as_float(x[1].y)) + (__uint_as_float(x[2].y) + __uint_as_float(x[3].y)), m, sd);
      const uint32_t e = pack_bf16(-m, sd);
      sts128(base + OFF_AX + 16 * i0, e, e, e, e);
      sts32(base + OFF_RT + 4 * i0, __float_as_uint(rcpf(sd)));
      fence_async_smem();
#pragma unroll 1
      for (it = 0; it < SPIN_LIMIT; it++) {
        mbar_wait(BAR(B_BX), it & 1);
        uint32_t y = 0;
#pragma unroll
        for (int k = 0; k < 6; k++) y |= lds32(base + OFF_BX + 16 * i0 + 2048 * k) ^ epoch;
        if (bar_all(3, !(y & 1))) break;
        if (w == 0 && elect()) { mbar_expect_tx(BAR(B_BX), 12288); bulk_load(base + OFF_BX, G->uv[4 * h + j], 12288, BAR(B_BX)); }
      }
      arrive1(BAR(B_EXT));
      {
        uint2 g0, g1;
        int it = 0;
#pragma unroll 1
        do {
          g0 = ld_relaxed64(&G->modv[1][128 * j + i0]);
          g1 = ld_relaxed64(&G->modv[1][512 + 32 * j + lane]);
        } while (__any_sync(~0u, ((g0.x ^ epoch) | (g0.y ^ epoch) | (g1.x ^ epoch) | (g1.y ^ epoch)) & 1) && ++it < SPIN_LIMIT);
        const uint32_t ga = base + OFF_GB + 80 * (lane >> 1 & 3) + 2 * (lane & 1) + (lane >> 3) * 4;
        asm volatile("st.shared.u16 [%0], %1;" ::"r"(ga + 16 * (w ^ (j & 1))), "h"((uint16_t)(mod_sum(g0) >> 16)) : "memory");
        asm volatile("st.shared.u16 [%0], %1;" ::"r"(ga + 64), "h"((uint16_t)(mod_sum(g1) >> 16)) : "memory");
        arrive1(BAR(B_GB));
      }
      const int id = 16 * r + 4 * h + fslice(j, w);
      const unsigned* fp = &G->hhf[8 * id + 64 * (lane & 1)];
#pragma unroll 1
      for (int q = w == 3 ? 3 : 0; q < 3; q++) {
        const int m = 3 * q + w;
        const uint4* src = G->hh + id * 1536 + 512 * q;
        it = 0;
#pragma unroll 1
        while (__any_sync(~0u, ld_relaxed32(fp + q) != 4 * epoch) && ++it < SPIN_LIMIT);
        mbar_wait(BAR(P.hid[2][m]));
        if (elect()) {
          bulk_load(base + OFF_A + h * ARING + P.hid[h][m], src, ASLOT, BAR(B_FULL + 23 + m));
          bulk_load(base + OFF_A + ARING - h * ARING + P.hid[h ^ 1][m], src + 8 * 1536, ASLOT, BAR(B_FULL + 23 + m));
        }
      }
    }
  } else {
    asm volatile("setmaxnreg.inc.sync.aligned.u32 224;");
    LAUNCHES;
    uint32_t par = EPOCH & 1;
    cluster_wait();
    {
      float acc[128];
      uint32_t A[64];
#pragma unroll
      for (int i = 0; i < 64; i++) A[i] = 0;
      int c = wg;
#pragma unroll 1
      for (uint64_t prog = P.cprog[wg]; prog; prog >>= 8) {
        REGION_IDS;
        const int s = prog & 7;
        if (s < 5) {
          const uint32_t a = base + tab(T_KV, s) + 128 * (lane & 3) + ((w ^ (lane & 3)) << 4) + 4 * (lane & 16) + (lane & 12), keep = ~(lane & 1), bit = par & lane;
          uint4* dst = G->xr + (128 * s + 64 * (bid & 1) + 8 * w + 2 * (lane & 16) + (lane >> 1 & 6)) * 256 + 255 - 4 * (bid >> 1) - (lane & 3);
          mbar_wait(BAR(B_KV));
          mbar_wait(BAR(B_KV + s));
          const uint4 wv = lds128(base + OFF_TAP + 512 * s + 64 * w + 16 * (lane & 16) + 4 * (lane & 12));
          uint32_t kk[11], r[8];
#pragma unroll
          for (int k = 0; k < 11; k++) kk[k] = k < 3 ? lds32((a ^ (64 * (k & 1))) + KV_H + 512 * k) : lds32((a ^ (64 * (~k & 1))) + 512 * (k - 3));
          if (elect()) red_hint(G->hint[s][4 * (bid & 1) + w]);
#pragma unroll
          for (int k = 0; k < 8; k++) r[k] = lds32((a ^ (64 * (k & 1))) + KV_V + 512 * k);
          const uint32_t w0 = __byte_perm(wv.x, wv.z, 0x5410), w1 = __byte_perm(wv.x, wv.z, 0x7632),
                         w2 = __byte_perm(wv.y, wv.w, 0x5410), w3 = __byte_perm(wv.y, wv.w, 0x7632);
#pragma unroll
          for (int k = 0; k < 8; k++) r[k] = bmul2(bfma2(kk[k + 3], w0, bfma2(kk[k + 2], w1, bfma2(kk[k + 1], w2, bmul2(kk[k], w3)))), r[k]);
          st_relaxed128(dst, (__byte_perm(r[7], r[6], 0x5410) & keep) | bit, __byte_perm(r[5], r[4], 0x5410), __byte_perm(r[3], r[2], 0x5410), __byte_perm(r[1], r[0], 0x5410));
          st_relaxed128(dst + 256, (__byte_perm(r[7], r[6], 0x7632) & keep) | bit, __byte_perm(r[5], r[4], 0x7632), __byte_perm(r[3], r[2], 0x7632), __byte_perm(r[1], r[0], 0x7632));
        }
        if (prog & 8) {
          float s0 = 0.f, s1 = 0.f, q0 = 0.f, q1 = 0.f;
          const uint32_t a = OFF_Q + 1024 * w + 128 * (lane & 7) + (((lane >> 3) ^ (lane & 7)) << 4);
          const uint32_t ra = mapa(base + OFF_ST + 128 * (bid & 1) + 64 * (lane & 1) + 16 * w + 8 * (lane >> 2), lane >> 1 & 1), rb = mapa(BAR(B_ST1), lane >> 1 & 1);
          if (w == 3 && elect()) mbar_expect_tx(BAR(B_ST1), 256);
#pragma unroll 1
          for (int k = 0; k < 5; k++) {
            mbar_wait(BAR(B_Q + k));
            const uint32_t o = opaque(base + 4096 * k);
            const uint4 x = lds128(o + a), y = lds128(o + (a ^ 64));
            const uint32_t e[8] = {x.x, x.y, x.z, x.w, y.x, y.y, y.z, y.w};
#pragma unroll
            for (int i = 0; i < 8; i++) { const float lo = bf_lo(e[i]), hi = bf_hi(e[i]); s0 += lo; s1 += hi; q0 = fmaf(lo, lo, q0); q1 = fmaf(hi, hi, q1); }
          }
          s0 += s1; q0 += q1;
          s0 += __shfl_xor_sync(~0u, s0, 8); q0 += __shfl_xor_sync(~0u, q0, 8);
          s0 += __shfl_xor_sync(~0u, s0, 16); q0 += __shfl_xor_sync(~0u, q0, 16);
          if (lane < 8) asm volatile("st.async.shared::cluster.mbarrier::complete_tx::bytes.v2.b32 [%0], {%1,%2}, [%3];" ::"r"(ra), "r"(__float_as_uint(s0)), "r"(__float_as_uint(q0)), "r"(rb) : "memory");
        }
        if (prog & 32) {
          const int L = 16 * w + (lane >> 2) + 2 * (lane & 3) - 7;
          const uint32_t fo = base + ((L & 1) ? F_O + 2 * (L + 1) : F_E + 2 * L);
          mbar_wait(BAR(B_FRDY + c));
          cload<0, 0>(A, fo + tab(T_F, c));
          cload<15, 1>(A, fo + tab(T_F, c));
          arrive1(BAR(B_FL + c));
        }
        if (!(prog & 64)) continue;
        uint32_t xo;
        if (P.turn >> c & 1) mbar_wait(BAR(B_TURN - 3 + c));
        if (c == 0) mbar_wait(BAR(P.c0));
#pragma unroll 1
        for (int it = 0; it < SPIN_LIMIT; it++) {
          xo = tab(T_X, opaque(c));
          mbar_wait(BAR(B_XR + c), it & 1);
          const uint32_t tag = lds32(base + xo + 32 * i0);
          wg_fence();
          csteps<0, 0>(acc, A, mkdesc(DB + xo, 16, 128, 0));
          csteps<15, 6>(acc, A, mkdesc(DB + xo, 16, 128, 0));
          wg_commit();
          if (bar_all(1 + wg, !((tag ^ par) & 1))) break;
          wg_wait<0>();
          if (w == 0 && elect()) { mbar_expect_tx(BAR(B_XR + c), 4096); bulk_load(base + xo, G->xr + (128 * c + bid) * 256, 4096, BAR(B_XR + c)); }
        }
        wg_fence();
        csteps<5, 1>(acc, A, mkdesc(DB + tab(T_X, opaque(c)), 16, 128, 0));
        wg_commit();
        if (c >= 2 && c < 4 && elect()) mbar_arrive(BAR(B_TURN - 2 + c));
        if (c >= 3) mbar_wait(BAR(B_PEMPTY + c - 3));
        wg_wait<0>();
        fence_regs(acc);
        const uint32_t pb = base + tab(T_P, c) + 4096 * w;
#pragma unroll
        for (int k = 0; k < 8; k++) {
          uint32_t p[4];
#pragma unroll
          for (int e = 0; e < 4; e++) { const int i = 4 * k + e; p[e] = i < 31 ? pack_bf16(acc[4 * i] + acc[4 * i + 6], acc[4 * i + 1] + acc[4 * i + 7]) : pack_bf16(acc[124], acc[125]); }
          if (k == 0 && (lane & 3) < w) p[0] = 0;
          stmatrix_x4_t(k == 0 ? pb + 16 * ((255 - lane + 2 * w) & 255) : pb + 16 * (255 - lane + 2 * w) - 512 * k, p[0], p[1], p[2], p[3]);
        }
        arrive1(BAR(B_PFULL + c));
        c += 2;
      }
    }
    uint32_t ck;
    { REGION_IDS; ck = base + OFF_A + wg * ARING + lane * 128 + (((2 * w) ^ (lane & 7)) << 4); }
    const uint32_t abd = DB + OFF_A + wg * ARING;
    auto a_tile = [&](int as, int n, bool first) {
#pragma unroll 1
      for (int it = 0; __any_sync(~0u, ((lds32(ck + as) ^ par) | (lds32(ck + as + (first ? 4096 : 256)) ^ par)) & 1) && it < SPIN_LIMIT; it++) {
        int h, j, r;
        ffn_role(h, j, r);
        if (elect()) {
          const uint32_t dst = base + OFF_A + wg * ARING + as;
          mbar_expect_tx(BAR(B_RETRY + wid), ASLOT);
          if (first) tma2d(dst, &maps.xs, 128 * r + 64 * (h ^ wg), 64 * n, BAR(B_RETRY + wid));
          else bulk_load(dst, G->hh + ((2 * r + (h ^ wg)) * 8 + 4 * h + fslice(j, n % 3)) * 1536 + (n / 3) * 512, ASLOT, BAR(B_RETRY + wid));
        }
        mbar_wait(BAR(B_RETRY + wid), par >> 1);
        par ^= 2;
      }
    };
    float acc[192];
    int ws = 0, as = 0;
#pragma unroll 1
    for (int u = 0; u < 20 - NT; u++) {
      mbar_wait(BAR(B_FULL + u));
      if (!(u & 1)) a_tile(as, u >> 1, true);
      wg_fence();
#pragma unroll
      for (int k = 0; k < 4; k++) wg_ss192_11(acc + 96 * (k & 1), mkdesc(abd + as + k / 2 * 2048, 16, 1024, 1), mkdesc(DB + ws + 12288 * (k & 1) + k / 2 * 2048, 4096, 1024, 1), u + k / 2);
      wg_commit();
      wg_wait<1>();
      if (elect()) mbar_arrive(BAR(B_EMPTY + u - 1));
      ws = next_slot(ws);
      as = as == 5 * ASLOT / 2 ? 0 : as + ASLOT / 2;
    }
    auto tail = [&](int v, int i) {
      const int u = 20 - NT + i / 2;
      if (i < 2 * NT) wg_ss192_11(acc + 96 * v, mkdesc(opaque(abd) + u % 6 * 4096 + (i & 1) * 2048, 16, 1024, 1), mkdesc(DB + u % 5 * WSLOT + (i & 1) * 2048 + 12288 * v, 4096, 1024, 1), 1);
      if (i == 2 * NT) wg_ss192_01(acc + 96 * v, mkdesc(DB + OFF_AX + 1024 * opaque(wg), 0, 128, 0), mkdesc(DB + OFF_BX + 6144 * v, 2048, 1024, 1), 1);
    };
#pragma unroll
    for (int u = 20 - NT; u <= 20; u++) {
      mbar_wait(BAR(u < 20 ? B_FULL + u : B_EXT));
      if (u == 16 || u == 18) a_tile(u % 6 * 4096, u >> 1, true);
      wg_fence();
      tail(0, 2 * (u + NT - 20));
      tail(0, 2 * (u + NT - 20) + 1);
      wg_commit();
      if (u == 20 - NT) { wg_wait<1>(); if (elect()) mbar_arrive(BAR(B_EMPTY + u - 1)); }
    }
    float o[80];
    uint32_t fr[3][16], bo;
    {
      int h, j, r;
      ffn_role(h, j, r);
      REGION_IDS;
      const float r0 = 0.5f * __uint_as_float(lds32(base + OFF_RT + 256 * wg + 64 * w + (lane & 28))), r1 = 0.5f * __uint_as_float(lds32(base + OFF_RT + 256 * wg + 64 * w + 32 + (lane & 28)));
      const int id = (2 * r + (h ^ wg)) * 8 + 4 * h + j;
      uint4* const hdst = G->hh + id * 1536 + 128 * w + (lane ^ lane >> 3);
      const uint32_t keep = ~(~lane & 1), bit = par & ~keep;
      bo = 1024 + ((j & 1) << 23);
      auto own = [&](int i) { wg_rs160_1(o, fr[i >> 2] + 4 * (i & 3), mkdesc(DB + (5 + i / 4) % 6 * WSLOT + (i & 3) * 2048, 8192, bo, 1), i); };
      auto gate = [&](float* g, int d) {
#pragma unroll
        for (int e = 0; e < 4; e++) { g[e] *= e < 2 ? r0 : r1; g[e + d] *= g[e]; asm("tanh.approx.f32 %0, %0;" : "+f"(g[e])); }
      };
      auto mix = [&](uint32_t* x, const float* g, int d) {
        x[0] = pack_bf16(fmaf(g[d], g[0], g[d]), fmaf(g[d + 1], g[1], g[d + 1]));
        x[1] = pack_bf16(fmaf(g[d + 2], g[2], g[d + 2]), fmaf(g[d + 3], g[3], g[d + 3]));
      };
      auto hint = [&](int v) { asm volatile("{.reg .pred p; setp.eq.u32 p, %1, 0; @p red.relaxed.gpu.global.add.u32 [%0], 1;}" ::"l"(&G->hhf[id * 8 + v]), "r"(lane) : "memory"); };
      auto put = [&](int v, int k) {
        uint32_t* x = fr[v] + 2 * k;
        const uint32_t t0 = (x[k / 2] & keep) | bit, t1 = (x[5 + k / 2] & keep) | bit;
        if (!v) { x[k / 2] = t0; x[5 + k / 2] = t1; }
        st_relaxed128(hdst + 512 * v + 8 * k, k ? x[0] : t0, k ? t0 : x[2], x[4], x[6]);
        st_relaxed128(hdst + 512 * v + 8 * k + 64, x[1], x[3], k ? x[5] : t1, k ? t1 : x[7]);
      };
      auto move = [&](uint32_t* x) {
#pragma unroll
        for (int k = 0; k < 16; k++) asm volatile("mul.rn.f32 %0, %0, %1;" : "+r"(x[k]) : "f"(P.one));
      };
      wg_fence();
      tail(1, 0);
      tail(1, 1);
      wg_commit();
      wg_wait<1>();
#pragma unroll
      for (int k = 0; k < 96; k++) asm volatile("" : "+f"(acc[k])::"memory");
      if (elect()) mbar_arrive(BAR(B_EMPTY + 18));
      gate(acc + 28, 32);
#pragma unroll
      for (int k = 7; k >= 0; k--) {
        if (k >= 8 - 2 * NT) split(P.zero, k);
        if (k > 8 - 2 * NT) tail(1, 9 - k);
        if (k == 9 - 2 * NT) wg_commit();
        if (k) gate(acc + 4 * k - 4, 32);
        mix(fr[0] + 2 * k, acc + 4 * k, 32);
        if (k == 1) hint(0);
        if (!(k & 3)) put(0, k);
      }
      move(fr[0]);
      split(P.zero, 14);
      wg_wait<0>();
#pragma unroll
      for (int k = 96; k < 192; k++) asm volatile("" : "+f"(acc[k])::"memory");
      if (elect()) mbar_arrive(BAR(B_EMPTY + 19));
#pragma unroll
      for (int k = 7; k >= 0; k--) gate(acc + 64 + 4 * k, 96);
      mbar_wait(BAR(B_FULL + 20));
      mbar_wait(BAR(B_FULL + 21));
#pragma unroll
      for (int k = 7; k >= 0; k--) mix(fr[1] + 2 * k, acc + 64 + 4 * k, 96);
#pragma unroll
      for (int k = 0; k < 4; k++) pin4(P.zero, fr[1] + 4 * k);
      wg_fence();
      own(0);
      own(1);
      split(P.zero, 15);
      put(1, 4);
      hint(1);
      own(2);
      put(1, 0);
      own(3);
      wg_commit();
      gate(acc + 124, 32);
#pragma unroll
      for (int k = 7; k >= 0; k--) {
        if (k & 1 || k == 6) split(P.zero, 16 + k);
        if (!(k & 1)) own(7 - k / 2);
        if (k == 4 || k == 0) wg_commit();
        if (k == 4) { wg_wait<1>(); if (elect()) mbar_arrive(BAR(B_EMPTY + 20)); }
        if (k) gate(acc + 92 + 4 * k, 32);
        mix(fr[2] + 2 * k, acc + 96 + 4 * k, 32);
        if (k == 1) hint(2);
        if (!(k & 3)) put(2, k);
      }
      mbar_wait(BAR(B_FULL + 22));
      wg_fence();
#pragma unroll
      for (int i = 8; i < 12; i++) own(i);
      wg_commit();
      wg_wait<1>();
      if (elect()) mbar_arrive(BAR(B_EMPTY + 21));
      ck = base + OFF_A + wg * ARING + 2048 * w + 516 * (lane >> 3) + 144 * (lane >> 2 & 1) + 32 * (lane & 3);
    }
    uint32_t x1[40];
    if (!wg) {
      REGION_IDS;
      const uint32_t xa = base + (lane >> 4) * 1024 + (lane & 7) * 128 + (((2 * w + ((lane >> 3) & 1)) ^ (lane & 7)) << 4);
      mbar_wait(BAR(B_FULL + 32));
#pragma unroll
      for (int k = 0; k < 10; k++) ldmatrix_x4_t(x1 + 4 * k, xa + (k < 6 ? OFF_X1 + k / 2 * WSLOT + (k & 1) * 2048 : OFF_SX + 2048 * (k - 6)));
    }
#pragma unroll 1
    for (int u = 23; u < (wg ? 32 : LAG2); u++) {
      as = P.hid[wg][u - 23];
      const uint64_t wd = mkdesc(0, 0, bo, 1) | P.w2t[u - 20].x;
      mbar_wait(BAR(B_FULL + u));
      a_tile(as, u - 23, false);
      wg_fence();
#pragma unroll
      for (int kk = 0; kk < 4; kk++) wg_ss160_01(o, mkdesc(abd + as + kk / 2 * 512 + (kk & 1) * 32, 16, 1024, 2), wd + kk * 128, 1);
      wg_commit();
      if (u == 31 && elect()) mbar_arrive(BAR(B_LAG));
      wg_wait<1>();
      if (elect()) mbar_arrive(BAR(B_EMPTY + u - 1));
    }
    int h, j, r;
    ffn_role(h, j, r);
    REGION_IDS;
    const uint32_t xb = base + OFF_XCH + 5120 * w;
    if (wg) {
      const uint32_t rdst = mapa(xb + 16 * lane, h ^ 1), rbar = mapa(BAR(B_FULL), h ^ 1);
      mbar_wait(BAR(B_XFREE));
      wg_wait<0>();
      fence_regs(o);
#pragma unroll
      for (int k = 0; k < 10; k++)
        asm volatile("st.async.shared::cluster.mbarrier::complete_tx::bytes.v4.b32 [%0], {%1,%2,%3,%4}, [%5];" ::"r"(rdst + 512 * k), "r"(pack_bf16(o[8 * k], o[8 * k + 1])),
                     "r"(pack_bf16(o[8 * k + 2], o[8 * k + 3])), "r"(pack_bf16(o[8 * k + 4], o[8 * k + 5])), "r"(pack_bf16(o[8 * k + 6], o[8 * k + 7])), "r"(rbar + 8 * (k / 4)) : "memory");
    } else {
      uint32_t gr[40];
      const float r0 = __uint_as_float(lds32(base + OFF_RT + 64 * w + (lane & 28))), r1 = __uint_as_float(lds32(base + OFF_RT + 64 * w + 32 + (lane & 28)));
      const uint32_t p0 = pack_bf16(r0, r0), p1 = pack_bf16(r1, r1), q0 = pack_bf16(r0 - bf_lo(p0), r0 - bf_lo(p0)), q1 = pack_bf16(r1 - bf_lo(p1), r1 - bf_lo(p1));
      mbar_wait(BAR(B_GB));
#pragma unroll
      for (int k = 0; k < 5; k++) {
        const uint4 g = lds128(base + OFF_GB + 80 * (lane & 3) + 16 * k);
        gr[8 * k] = g.x; gr[8 * k + 2] = g.y; gr[8 * k + 4] = g.z; gr[8 * k + 6] = g.w;
      }
      auto scale = [&](int k) {
#pragma unroll
        for (int e = 4 * k; e < 4 * k + 4; e += 2) { gr[e + 1] = bfma2(gr[e], p1, bmul2(gr[e], q1)); gr[e] = bfma2(gr[e], p0, bmul2(gr[e], q0)); }
      };
#pragma unroll
      for (int k = max(127 - 4 * LAG2, 0); k < 10; k++) scale(k);
      wg_wait<0>();
      if (elect()) mbar_arrive(BAR(B_EMPTY + LAG2 - 1));
#pragma unroll 1
      for (int u = LAG2; u < 32; u++) {
        mbar_wait(BAR(B_FULL + u));
        a_tile(P.hid[0][u - 23], u - 23, false);
      }
      auto da = [&](int i) { return mkdesc(DB + hid_at(i / 4 + LAG2 - 23, 0) + (i & 2) * 256 + (i & 1) * 32, 16, 1024, 2); };
      auto db = [&](int i, int b) { return mkdesc(DB + w2_at(i / 4 + LAG2 - 20) + b * w2_step(i / 4 + LAG2 - 20) + (i & 3) * 2048, w2_step(i / 4 + LAG2 - 20), bo, 1); };
      const int row = 128 * r + 64 * h + 16 * w;
      auto merge = [&](int e) {
        if (e % 4 == 0) mbar_wait_cluster(BAR(B_FULL + e / 4), 1);
        const uint4 p = lds128(xb + 16 * lane + 512 * e);
        x1[4 * e] = bfma2(gr[4 * e], p.x, x1[4 * e]); x1[4 * e + 1] = bfma2(gr[4 * e + 1], p.y, x1[4 * e + 1]);
        x1[4 * e + 2] = bfma2(gr[4 * e + 2], p.z, x1[4 * e + 2]); x1[4 * e + 3] = bfma2(gr[4 * e + 3], p.w, x1[4 * e + 3]);
      };
      auto out = [&](int k) {
        const float* v = o + 8 * k;
        uint32_t y[4];
#pragma unroll
        for (int e = 0; e < 4; e++) y[e] = bfma2(gr[4 * k + e], pack_bf16(v[2 * e], v[2 * e + 1]), x1[4 * k + e]);
        stmatrix_x4(k < 8 ? xb + 2048 * (k >> 2) + (lane & 15) * 128 + (((2 * (k & 3) + (lane >> 4)) ^ (lane & 7) ^ 4 * (j & 1)) << 4)
                          : xb + 4096 + (lane & 15) * 64 + (((2 * (k & 1) + (lane >> 4)) ^ (lane >> 1 & 3)) << 4), y[0], y[1], y[2], y[3]);
        if ((k & 3) == 3 || k == 9) {
          fence_async_smem();
          __syncwarp();
          if (lane == 0) tma2d_store(k < 8 ? &maps.outa : &maps.outb, k < 8 ? 128 * j + 64 * (k >> 2) : 512 + 32 * j, row, xb + 2048 * (k >> 2));
        }
      };
      constexpr int ND = 128 - 4 * LAG2;
      mbar_wait(BAR(B_LAG));
      wg_fence();
#pragma unroll
      for (int i = 0; i < ND; i++) {
        wg_ss160_01(o, da(i), db(i, 0), 1);
        if (i >= 1 && i <= 10) { scale(i - 1); split(P.zero, 32 + i); }
      }
      wg_commit();
#pragma unroll
      for (int e = 0; e < MG; e++) merge(e);
      __syncwarp();
      wg_wait<0>();
      fence_regs(o);
#pragma unroll
      for (int k = 0; k < 10; k++) {
        if (k >= MG && k % 4 == 0) {
#pragma unroll
          for (int e = k; e < min(k + 4, 10); e++) merge(e);
          __syncwarp();
        }
        out(k);
      }
      if (lane == 0) { bulk_commit(); bulk_wait_read(); }
    }
  }
}

typedef CUresult (*EncFn)(CUtensorMap*, CUtensorMapDataType, cuuint32_t, void*, const cuuint64_t*, const cuuint64_t*, const cuuint32_t*,
                          const cuuint32_t*, CUtensorMapInterleave, CUtensorMapSwizzle, CUtensorMapL2promotion, CUtensorMapFloatOOBfill);
static int enc_err = 0;
static void enc(EncFn fn, CUtensorMap* m, const void* p, int rank, const cuuint64_t* gd, const cuuint64_t* gs, const cuuint32_t* bd, CUtensorMapSwizzle sw) {
  cuuint32_t es[5] = {1, 1, 1, 1, 1};
  enc_err = 2 * enc_err + (fn(m, CU_TENSOR_MAP_DATA_TYPE_BFLOAT16, rank, (void*)p, gd, gs, bd, es, CU_TENSOR_MAP_INTERLEAVE_NONE, sw,
                              CU_TENSOR_MAP_L2_PROMOTION_L2_128B, CU_TENSOR_MAP_FLOAT_OOB_FILL_NONE) != CUDA_SUCCESS);
}

extern "C" void kernel_launch(void* const* d_in, const int* in_sizes, int n_in, void* d_out, int out_size) {
  const bf16 *q = (const bf16*)d_in[0], *k = (const bf16*)d_in[1], *v = (const bf16*)d_in[2], *shift = (const bf16*)d_in[3],
             *ssmk = (const bf16*)d_in[4], *ssmd = (const bf16*)d_in[5], *w1 = (const bf16*)d_in[7], *w3 = (const bf16*)d_in[8],
             *w2 = (const bf16*)d_in[9], *c = (const bf16*)d_in[10], *wmod = (const bf16*)d_in[11];
  EncFn fn = nullptr;
  cudaDriverEntryPointQueryResult qr;
  cudaGetDriverEntryPoint("cuTensorMapEncodeTiled", (void**)&fn, cudaEnableDefault, &qr);
  Scratch* pg;
  cudaGetSymbolAddress((void**)&pg, g_s);
  Maps maps;
  enc_err = 0;
  const CUtensorMapSwizzle S128 = CU_TENSOR_MAP_SWIZZLE_128B;
  { cuuint64_t gd[3] = {D_, S_ / 8, 8}, gs[2] = {D_ * 16, D_ * 2}; cuuint32_t b[3] = {64, 4, 8};
    enc(fn, &maps.km, k, 3, gd, gs, b, S128);
    enc(fn, &maps.v, v, 3, gd, gs, b, S128);
    enc(fn, &maps.q, q, 3, gd, gs, b, S128);
    b[2] = 3;
    enc(fn, &maps.kh, k, 3, gd, gs, b, S128); }
  { cuuint64_t gd[3] = {256, 2, 5}, gs[2] = {512, 1024}; cuuint32_t b[3] = {256, 1, 5};
    enc(fn, &maps.tap, shift, 3, gd, gs, b, CU_TENSOR_MAP_SWIZZLE_NONE); }
  { cuuint64_t gd[3] = {6 * D_, D_, 1}, gs[2] = {6 * D_ * 2, 6 * D_ * 2 * D_}; cuuint32_t b[3] = {64, 64, 1};
    enc(fn, &maps.wm, wmod, 3, gd, gs, b, S128); }
  { cuuint64_t gd[3] = {64, D_, F_ / 64}, gs[2] = {F_ * 2, 128}; cuuint32_t b[3] = {64, 32, 3};
    enc(fn, &maps.w1, w1, 3, gd, gs, b, S128);
    enc(fn, &maps.w3, w3, 3, gd, gs, b, S128);
    b[1] = 16;
    enc(fn, &maps.w1e, w1, 3, gd, gs, b, S128);
    enc(fn, &maps.w3e, w3, 3, gd, gs, b, S128);
    b[1] = 32; b[2] = 1;
    enc(fn, &maps.w1s, w1, 3, gd, gs, b, S128);
    enc(fn, &maps.w3s, w3, 3, gd, gs, b, S128); }
  { cuuint64_t gd[2] = {S_, D_}, gs[1] = {S_ * 2}; cuuint32_t b1[2] = {64, 64}, b2[2] = {64, 32};
    enc(fn, &maps.xs, pg->xs, 2, gd, gs, b1, S128);
    gd[1] = 2 * D_;
    enc(fn, &maps.x1b, pg->x1, 2, gd, gs, b2, S128);
    enc(fn, &maps.x1s, pg->x1, 2, gd, gs, b2, CU_TENSOR_MAP_SWIZZLE_NONE); }
  { cuuint64_t gd[5] = {D_, 2, 4, 4, 48}, gs[4] = {D_ * 2, D_ * 4, D_ * 16, D_ * 64}; cuuint32_t b[5] = {64, 2, 4, 4, 2};
    enc(fn, &maps.w2a, w2, 5, gd, gs, b, S128);
    gs[1] = D_ * 16; gs[2] = D_ * 4;
    enc(fn, &maps.w2b, w2, 5, gd, gs, b, S128); }
  { cuuint64_t gd[2] = {D_, S_}, gs[1] = {D_ * 2}; cuuint32_t b1[2] = {64, 16}, b2[2] = {32, 16};
    enc(fn, &maps.outa, d_out, 2, gd, gs, b1, S128);
    enc(fn, &maps.outb, d_out, 2, gd, gs, b2, CU_TENSOR_MAP_SWIZZLE_64B); }
  if (enc_err) return;
  cudaFuncSetAttribute(k_fused, cudaFuncAttributeMaxDynamicSharedMemorySize, SMEM_BYTES);
  cudaLaunchConfig_t cfg = {132, 512, SMEM_BYTES};
  cudaLaunchAttribute at = {cudaLaunchAttributeClusterDimension};
  at.val.clusterDim.x = 2; at.val.clusterDim.y = at.val.clusterDim.z = 1;
  cfg.attrs = &at; cfg.numAttrs = 1;
  int nc = 0;
  cudaOccupancyMaxActiveClusters(&nc, k_fused, &cfg);
  Ptrs P = {ssmk, c, ssmd, pg, 0x4E8DCBA9ull, {0x676760, 0x64620F01}, 0, 700, 420, 5500, 0, 6, B_KV, 0, 0, 1, 1, 0x57010, 1.f};
  const char* sched = "k10v14f04q04q14q24q34q44k24v24f14k34v34f24k44v44f34f44n02n02n02n02n02n02";
  int t = 700, pace = 420;
  for (int e = 0; e < NE; e++) {
    const char x = sched[3 * e];
    const int r = sched[3 * e + 1] - '0', kind = x == 'k' ? 0 : x == 'v' ? 1 : x == 'q' ? 2 : x == 'f' ? 3 : 4;
    t += (sched[3 * e + 2] - '0') * pace / 4;
    P.sched[e] = make_uint2(t | kind << 16 | r << 20, (kind < 2 ? tab(T_KV, r) + kind * KV_V : kind == 2 ? OFF_Q + 4096 * r : tab(T_F, r) + F_E) | (r + (kind < 2 ? B_KV : kind == 2 ? B_Q : B_FRAW)) << 18);
  }
  for (int u = 0; u < 5; u++) P.wt[u] = 11500 + 400 * u;
  const int dep[5] = {B_FL + 1, B_FL + 2, B_PFULL + 2, B_FL + 1, B_PEMPTY + 2};
  for (int u = 0; u < 20; u++) P.wdep[u] = u % 5 * WSLOT | (~u & 1) << 12 | (u < 5 ? dep[u] : B_EMPTY + u - 5);
  for (int v = 0; v < 12; v++) P.w2t[v] = make_uint2(w2_desc(v), v ? B_EMPTY + (v > 5 ? 15 + v : v > 3 ? 14 + v : v > 1 ? 16 : 15) : B_UVD);
  for (int m = 0; m < 9; m++) { P.hid[0][m] = hid_at(m, 0) - OFF_A; P.hid[1][m] = hid_at(m, 1) - OFF_A - ARING; P.hid[2][m] = B_EMPTY + 19 + (m > 2 ? m : m / 2); }
  if (nc < 66) { P.boff = 128; k_fused<<<4, 512, SMEM_BYTES, cudaStreamPerThread>>>(P, maps); P.boff = 0; }
  k_fused<<<nc < 66 ? 128 : 132, 512, SMEM_BYTES, cudaStreamPerThread>>>(P, maps);
}
```

```cpp
#include <cuda_runtime.h>
#include <cuda.h>
#include <cuda_bf16.h>
#include <stdint.h>
#include <stdlib.h>

typedef __nv_bfloat16 bf16;
constexpr int S_ = 2048, D_ = 640, F_ = 1536;

struct Scratch {
  uint32_t st1[2][1024];
  uint32_t st2[32][4][128];
  uint2 modc[128][32];
  uint2 modv[3][D_];
  uint32_t uv[8][3072];
  unsigned hint[9][8][32];
  unsigned xsh[5][8][32], hhf[256 * 8];
  uint4 xr[D_ * 256];
  uint4 qt[D_ * 256];
  uint4 xs[D_ * 256];
  uint4 x1[2][D_ * 256];
  uint4 hh[32 * 8 * 1536];
};
__device__ __align__(1024) Scratch g_s;

__device__ __forceinline__ uint32_t smem_u32(const void* p) { return (uint32_t)__cvta_generic_to_shared(p); }
__device__ __forceinline__ void mbar_expect_tx(uint32_t b, uint32_t n) { asm volatile("mbarrier.arrive.expect_tx.shared::cta.b64 _, [%0], %1;" ::"r"(b), "r"(n) : "memory"); }
__device__ __forceinline__ void mbar_arrive(uint32_t b) { asm volatile("mbarrier.arrive.shared::cta.b64 _, [%0];" ::"r"(b) : "memory"); }
__device__ __forceinline__ void mbar_arrive2(uint32_t b) { asm volatile("mbarrier.arrive.shared::cta.b64 _, [%0], 2;" ::"r"(b) : "memory"); }
__device__ __forceinline__ uint32_t mapa(uint32_t a, uint32_t cta) { uint32_t r; asm volatile("mapa.shared::cluster.u32 %0, %1, %2;" : "=r"(r) : "r"(a), "r"(cta)); return r; }
__device__ __forceinline__ void mbar_arrive_remote(uint32_t rb) { asm volatile("mbarrier.arrive.shared::cluster.b64 _, [%0];" ::"r"(rb) : "memory"); }
constexpr int SPIN_LIMIT = 1 << 16;
template <int N> __device__ __forceinline__ void mbar_init(uint32_t b, uint32_t count) {
#pragma unroll
  for (int i = 0; i < N; i++) asm volatile("mbarrier.init.shared::cta.b64 [%0], %1;" ::"r"(b + 8 * i), "r"(count) : "memory");
}
__device__ __forceinline__ bool elect() { uint32_t p; asm volatile("{.reg .pred q; elect.sync _|q, 0xffffffff; selp.u32 %0, 1, 0, q;}" : "=r"(p)); return p; }
__device__ __forceinline__ void arrive1(uint32_t b) { __syncwarp(); if (elect()) mbar_arrive(b); }
__device__ __forceinline__ bool mbar_test(uint32_t b) {
  uint32_t ok;
  asm volatile("{.reg .pred p; mbarrier.test_wait.parity.shared::cta.b64 p, [%1], 0; selp.u32 %0,1,0,p;}" : "=r"(ok) : "r"(b) : "memory");
  return ok;
}
#define WAIT_LOOP(sem) "{.reg .pred p; mov.u32 %0, 0; W: mbarrier.try_wait.parity" sem ".shared::cta.b64 p, [%1], %2; @p bra.uni D; add.u32 %0, %0, 1; setp.lt.u32 p, %0, %3; @p bra.uni W; D:}"
__device__ __forceinline__ void mbar_wait(uint32_t b, uint32_t ph = 0) {
  int it;
  asm volatile(WAIT_LOOP("") : "=&r"(it) : "r"(b), "r"(ph), "n"(SPIN_LIMIT) : "memory");
}
__device__ __forceinline__ void mbar_wait_cluster(uint32_t b, uint32_t ph = 0) {
  int it;
  asm volatile(WAIT_LOOP(".acquire.cluster") : "=&r"(it) : "r"(b), "r"(ph), "n"(SPIN_LIMIT) : "memory");
}
__device__ __forceinline__ void wait_clock(uint32_t t) {
  asm volatile("{.reg .pred p; .reg .s32 d; W: mov.u32 d, %%clock; sub.s32 d, d, %0; setp.lt.s32 p, d, 0; @p bra.uni W;}" ::"r"(t) : "memory");
}
__device__ __forceinline__ void tma2d(uint32_t dst, const CUtensorMap* m, int c0, int c1, uint32_t bar) {
  asm volatile("cp.async.bulk.tensor.2d.shared::cluster.global.mbarrier::complete_tx::bytes [%0], [%1, {%3,%4}], [%2];" ::"r"(dst), "l"(m), "r"(bar), "r"(c0), "r"(c1) : "memory");
}
__device__ __forceinline__ void tma3d(uint32_t dst, const CUtensorMap* m, int c0, int c1, int c2, uint32_t bar) {
  asm volatile("cp.async.bulk.tensor.3d.shared::cluster.global.mbarrier::complete_tx::bytes [%0], [%1, {%3,%4,%5}], [%2];" ::"r"(dst), "l"(m), "r"(bar), "r"(c0), "r"(c1), "r"(c2) : "memory");
}
__device__ __forceinline__ void tma5d(uint32_t dst, const CUtensorMap* m, int c0, int c4, uint32_t bar) {
  asm volatile("cp.async.bulk.tensor.5d.shared::cluster.global.mbarrier::complete_tx::bytes [%0], [%1, {%4,%3,%3,%3,%5}], [%2];" ::"r"(dst), "l"(m), "r"(bar), "r"(0), "r"(c0), "r"(c4) : "memory");
}
__device__ __forceinline__ void tma2d_store(const CUtensorMap* m, int c0, int c1, uint32_t src) {
  asm volatile("cp.async.bulk.tensor.2d.global.shared::cta.bulk_group [%0, {%2,%3}], [%1];" ::"l"(m), "r"(src), "r"(c0), "r"(c1) : "memory");
}
__device__ __forceinline__ void bulk_load(uint32_t dst, const void* src, uint32_t bytes, uint32_t bar) {
  asm volatile("cp.async.bulk.shared::cluster.global.mbarrier::complete_tx::bytes [%0], [%1], %2, [%3];" ::"r"(dst), "l"(src), "r"(bytes), "r"(bar) : "memory");
}
__device__ __forceinline__ void prefetch_map(const CUtensorMap* m) { asm volatile("prefetch.tensormap [%0];" ::"l"(m) : "memory"); }
__device__ __forceinline__ void bulk_commit() { asm volatile("cp.async.bulk.commit_group;" ::: "memory"); }
__device__ __forceinline__ void bulk_wait_read() { asm volatile("cp.async.bulk.wait_group.read 0;" ::: "memory"); }
__device__ __forceinline__ void fence_async_smem() { asm volatile("fence.proxy.async.shared::cta;" ::: "memory"); }
__device__ __forceinline__ void fence_async_all() { asm volatile("fence.proxy.async.global;" ::: "memory"); }
__device__ __forceinline__ void named_bar(int id, int n) { asm volatile("bar.sync %0, %1;" ::"r"(id), "r"(n) : "memory"); }
__device__ __forceinline__ bool bar_all(int id, bool v) {
  uint32_t r;
  asm volatile("{.reg .pred p, q; setp.ne.u32 p, %2, 0; bar.red.and.pred q, %1, 128, p; selp.u32 %0, 1, 0, q;}" : "=r"(r) : "r"(id), "r"((uint32_t)v) : "memory");
  return __all_sync(~0u, r);
}
__device__ __forceinline__ void cluster_wait() { asm volatile("barrier.cluster.wait.aligned;" ::: "memory"); }
__device__ __forceinline__ void wg_fence() { asm volatile("wgmma.fence.sync.aligned;" ::: "memory"); }
__device__ __forceinline__ void wg_commit() { asm volatile("wgmma.commit_group.sync.aligned;" ::: "memory"); }
template <int N> __device__ __forceinline__ void wg_wait() { asm volatile("wgmma.wait_group.sync.aligned %0;" ::"n"(N) : "memory"); }
template <int N> __device__ __forceinline__ void fence_regs(float (&a)[N]) {
#pragma unroll
  for (int i = 0; i < N; i++) asm volatile("" : "+f"(a[i])::"memory");
}
template <int N> __device__ __forceinline__ void fence_n(float* a) {
#pragma unroll
  for (int i = 0; i < N; i++) asm volatile("" : "+f"(a[i])::"memory");
}
__device__ __forceinline__ uint64_t mkdesc(uint32_t addr, uint32_t lbo, uint32_t sbo, uint32_t swz) {
  uint32_t lo = (addr >> 4) | ((lbo >> 4) << 16), hi = (sbo >> 4) | (swz << 30);
  return ((uint64_t)hi << 32) | lo;
}
__device__ __forceinline__ void stmatrix_x4(uint32_t a, uint32_t r0, uint32_t r1, uint32_t r2, uint32_t r3) {
  asm volatile("stmatrix.sync.aligned.m8n8.x4.shared.b16 [%0], {%1,%2,%3,%4};" ::"r"(a), "r"(r0), "r"(r1), "r"(r2), "r"(r3) : "memory");
}
__device__ __forceinline__ void stmatrix_x4_t(uint32_t a, uint32_t r0, uint32_t r1, uint32_t r2, uint32_t r3) {
  asm volatile("stmatrix.sync.aligned.m8n8.x4.trans.shared.b16 [%0], {%1,%2,%3,%4};" ::"r"(a), "r"(r0), "r"(r1), "r"(r2), "r"(r3) : "memory");
}
__device__ __forceinline__ void ldmatrix_x4_t(uint32_t* r, uint32_t a) {
  asm volatile("ldmatrix.sync.aligned.m8n8.x4.trans.shared.b16 {%0,%1,%2,%3}, [%4];" : "=r"(r[0]), "=r"(r[1]), "=r"(r[2]), "=r"(r[3]) : "r"(a) : "memory");
}
__device__ __forceinline__ uint32_t lds32(uint32_t a) { uint32_t v; asm volatile("ld.shared.b32 %0, [%1];" : "=r"(v) : "r"(a) : "memory"); return v; }
__device__ __forceinline__ uint2 lds64(uint32_t a) { uint2 v; asm volatile("ld.shared.v2.b32 {%0,%1}, [%2];" : "=r"(v.x), "=r"(v.y) : "r"(a) : "memory"); return v; }
__device__ __forceinline__ uint4 lds128(uint32_t a) { uint4 v; asm volatile("ld.shared.v4.b32 {%0,%1,%2,%3}, [%4];" : "=r"(v.x), "=r"(v.y), "=r"(v.z), "=r"(v.w) : "r"(a) : "memory"); return v; }
__device__ __forceinline__ void sts32(uint32_t a, uint32_t v) { asm volatile("st.shared.b32 [%0], %1;" ::"r"(a), "r"(v) : "memory"); }
__device__ __forceinline__ void sts64(uint32_t a, uint32_t x, uint32_t y) { asm volatile("st.shared.v2.b32 [%0], {%1,%2};" ::"r"(a), "r"(x), "r"(y) : "memory"); }
__device__ __forceinline__ void sts128(uint32_t a, uint32_t x, uint32_t y, uint32_t z, uint32_t w) { asm volatile("st.shared.v4.b32 [%0], {%1,%2,%3,%4};" ::"r"(a), "r"(x), "r"(y), "r"(z), "r"(w) : "memory"); }
__device__ __forceinline__ uint4 ld_relaxed128(const void* p) { uint4 v; asm volatile("ld.relaxed.gpu.global.v4.u32 {%0,%1,%2,%3}, [%4];" : "=r"(v.x), "=r"(v.y), "=r"(v.z), "=r"(v.w) : "l"(p) : "memory"); return v; }
__device__ __forceinline__ uint2 ld_relaxed64(const void* p) { uint2 v; asm volatile("ld.relaxed.gpu.global.v2.u32 {%0,%1}, [%2];" : "=r"(v.x), "=r"(v.y) : "l"(p) : "memory"); return v; }
__device__ __forceinline__ uint32_t ld_relaxed32(const void* p) { uint32_t v; asm volatile("ld.relaxed.gpu.global.u32 %0, [%1];" : "=r"(v) : "l"(p) : "memory"); return v; }
__device__ __forceinline__ void st_relaxed128(void* p, uint32_t x, uint32_t y, uint32_t z, uint32_t w) { asm volatile("st.relaxed.gpu.global.v4.u32 [%0], {%1,%2,%3,%4};" ::"l"(p), "r"(x), "r"(y), "r"(z), "r"(w) : "memory"); }
__device__ __forceinline__ void st_relaxed32(void* p, uint32_t x) { asm volatile("st.relaxed.gpu.global.u32 [%0], %1;" ::"l"(p), "r"(x) : "memory"); }
__device__ __forceinline__ void red_hint(unsigned* p) { asm volatile("red.relaxed.gpu.global.add.u32 [%0], 1;" ::"l"(p) : "memory"); }
__device__ __forceinline__ void publish(uint32_t* p, uint32_t x) { asm volatile("{.reg .b32 t; atom.relaxed.gpu.global.exch.b32 t, [%0], %1;}" ::"l"(p), "r"(x) : "memory"); }
__device__ __forceinline__ uint32_t ldg32(const void* p) { uint32_t v; asm volatile("ld.global.nc.L1::no_allocate.b32 %0, [%1];" : "=r"(v) : "l"(p)); return v; }
__device__ __forceinline__ uint32_t pack_bf16(float lo, float hi) { uint32_t r; asm("cvt.rn.bf16x2.f32 %0, %1, %2;" : "=r"(r) : "f"(hi), "f"(lo)); return r; }
__device__ __forceinline__ float bf_lo(uint32_t v) { return __uint_as_float(v << 16); }
__device__ __forceinline__ float bf_hi(uint32_t v) { return __uint_as_float(v & 0xFFFF0000u); }
__device__ __forceinline__ uint32_t bmul2(uint32_t a, uint32_t b) { uint32_t r; asm("mul.rn.bf16x2 %0, %1, %2;" : "=r"(r) : "r"(a), "r"(b)); return r; }
__device__ __forceinline__ uint32_t badd2(uint32_t a, uint32_t b) { uint32_t r; asm("add.rn.bf16x2 %0, %1, %2;" : "=r"(r) : "r"(a), "r"(b)); return r; }
__device__ __forceinline__ uint32_t bfma2(uint32_t a, uint32_t b, uint32_t c) { uint32_t r; asm("fma.rn.bf16x2 %0, %1, %2, %3;" : "=r"(r) : "r"(a), "r"(b), "r"(c)); return r; }
__device__ __forceinline__ uint32_t set_tag(uint32_t x, uint32_t mask, uint32_t e) { uint32_t r; asm("lop3.b32 %0, %1, %2, %3, 0xB8;" : "=r"(r) : "r"(x), "r"(mask), "r"(e)); return r; }
__device__ __forceinline__ uint32_t opaque(uint32_t x) { asm volatile("" : "+r"(x)); return x; }
__device__ __forceinline__ float rbf(float x) { return __bfloat162float(__float2bfloat16(x)); }
__device__ __forceinline__ float silu_f(float x) {
  float e, r;
  asm("ex2.approx.ftz.f32 %0, %1;" : "=f"(e) : "f"(x * -1.4426950408889634f));
  asm("rcp.approx.ftz.f32 %0, %1;" : "=f"(r) : "f"(1.f + e));
  return x * r;
}
__device__ __forceinline__ float silu2(float x) {
  float t;
  asm("tanh.approx.f32 %0, %1;" : "=f"(t) : "f"(x));
  return fmaf(x, t, x);
}
__device__ __forceinline__ void pin(int off, uint32_t x) { asm volatile("{.reg .pred p; setp.lt.s32 p, %0, 0; @p st.shared.b32 [%0], %1;}" ::"r"(off), "r"(x) : "memory"); }
__device__ __forceinline__ void pin4(int off, const uint32_t* x) { asm volatile("{.reg .pred p; setp.lt.s32 p, %0, 0; @p st.shared.v4.b32 [%0], {%1,%2,%3,%4};}" ::"r"(off), "r"(x[0]), "r"(x[1]), "r"(x[2]), "r"(x[3]) : "memory"); }
__device__ __forceinline__ void split(int x, int n) { asm volatile("{.reg .pred p; setp.eq.s32 p, %0, %1; @p trap;}" ::"r"(x), "r"(~n) : "memory"); }
__device__ __forceinline__ void ln_final(float s, float q, float& m, float& sd) {
  m = s * (1.f / D_);
  asm("sqrt.approx.f32 %0, %1;" : "=f"(sd) : "f"(rbf(rbf(fmaxf(fmaf(-m, m, q * (1.f / D_)), 0.f)) + 1e-5f)));
  sd = rbf(sd);
}
__device__ __forceinline__ float rcpf(float x) { float r; asm("rcp.approx.f32 %0, %1;" : "=f"(r) : "f"(x)); return r; }

__device__ __forceinline__ void wg_rs16_0(float* d, const uint32_t* a, uint64_t db, int sc) {
  asm volatile("{.reg .pred p; setp.ne.b32 p, %13, 0; wgmma.mma_async.sync.aligned.m64n16k16.f32.bf16.bf16 {%0,%1,%2,%3,%4,%5,%6,%7}, {%8,%9,%10,%11}, %12, p, 1, 1, 0;}"
    : "+f"(d[0]),"+f"(d[1]),"+f"(d[2]),"+f"(d[3]),"+f"(d[4]),"+f"(d[5]),"+f"(d[6]),"+f"(d[7]) : "r"(a[0]),"r"(a[1]),"r"(a[2]),"r"(a[3]),"l"(db),"r"(sc));
}
__device__ __forceinline__ void wg_rs32_0(float* d, const uint32_t* a, uint64_t db, int sc) {
  asm volatile("{.reg .pred p; setp.ne.b32 p, %21, 0; wgmma.mma_async.sync.aligned.m64n32k16.f32.bf16.bf16 {%0,%1,%2,%3,%4,%5,%6,%7,%8,%9,%10,%11,%12,%13,%14,%15}, {%16,%17,%18,%19}, %20, p, 1, 1, 0;}"
    : "+f"(d[0]),"+f"(d[1]),"+f"(d[2]),"+f"(d[3]),"+f"(d[4]),"+f"(d[5]),"+f"(d[6]),"+f"(d[7]),"+f"(d[8]),"+f"(d[9]),"+f"(d[10]),"+f"(d[11]),"+f"(d[12]),"+f"(d[13]),"+f"(d[14]),"+f"(d[15]) : "r"(a[0]),"r"(a[1]),"r"(a[2]),"r"(a[3]),"l"(db),"r"(sc));
}
__device__ __forceinline__ void wg_rs48_0(float* d, const uint32_t* a, uint64_t db, int sc) {
  asm volatile("{.reg .pred p; setp.ne.b32 p, %29, 0; wgmma.mma_async.sync.aligned.m64n48k16.f32.bf16.bf16 {%0,%1,%2,%3,%4,%5,%6,%7,%8,%9,%10,%11,%12,%13,%14,%15,%16,%17,%18,%19,%20,%21,%22,%23}, {%24,%25,%26,%27}, %28, p, 1, 1, 0;}"
    : "+f"(d[0]),"+f"(d[1]),"+f"(d[2]),"+f"(d[3]),"+f"(d[4]),"+f"(d[5]),"+f"(d[6]),"+f"(d[7]),"+f"(d[8]),"+f"(d[9]),"+f"(d[10]),"+f"(d[11]),"+f"(d[12]),"+f"(d[13]),"+f"(d[14]),"+f"(d[15]),"+f"(d[16]),"+f"(d[17]),"+f"(d[18]),"+f"(d[19]),"+f"(d[20]),"+f"(d[21]),"+f"(d[22]),"+f"(d[23]) : "r"(a[0]),"r"(a[1]),"r"(a[2]),"r"(a[3]),"l"(db),"r"(sc));
}
__device__ __forceinline__ void wg_rs64_0(float* d, const uint32_t* a, uint64_t db, int sc) {
  asm volatile("{.reg .pred p; setp.ne.b32 p, %37, 0; wgmma.mma_async.sync.aligned.m64n64k16.f32.bf16.bf16 {%0,%1,%2,%3,%4,%5,%6,%7,%8,%9,%10,%11,%12,%13,%14,%15,%16,%17,%18,%19,%20,%21,%22,%23,%24,%25,%26,%27,%28,%29,%30,%31}, {%32,%33,%34,%35}, %36, p, 1, 1, 0;}"
    : "+f"(d[0]),"+f"(d[1]),"+f"(d[2]),"+f"(d[3]),"+f"(d[4]),"+f"(d[5]),"+f"(d[6]),"+f"(d[7]),"+f"(d[8]),"+f"(d[9]),"+f"(d[10]),"+f"(d[11]),"+f"(d[12]),"+f"(d[13]),"+f"(d[14]),"+f"(d[15]),"+f"(d[16]),"+f"(d[17]),"+f"(d[18]),"+f"(d[19]),"+f"(d[20]),"+f"(d[21]),"+f"(d[22]),"+f"(d[23]),"+f"(d[24]),"+f"(d[25]),"+f"(d[26]),"+f"(d[27]),"+f"(d[28]),"+f"(d[29]),"+f"(d[30]),"+f"(d[31]) : "r"(a[0]),"r"(a[1]),"r"(a[2]),"r"(a[3]),"l"(db),"r"(sc));
}
__device__ __forceinline__ void wg_rs80_0(float* d, const uint32_t* a, uint64_t db, int sc) {
  asm volatile("{.reg .pred p; setp.ne.b32 p, %45, 0; wgmma.mma_async.sync.aligned.m64n80k16.f32.bf16.bf16 {%0,%1,%2,%3,%4,%5,%6,%7,%8,%9,%10,%11,%12,%13,%14,%15,%16,%17,%18,%19,%20,%21,%22,%23,%24,%25,%26,%27,%28,%29,%30,%31,%32,%33,%34,%35,%36,%37,%38,%39}, {%40,%41,%42,%43}, %44, p, 1, 1, 0;}"
    : "+f"(d[0]),"+f"(d[1]),"+f"(d[2]),"+f"(d[3]),"+f"(d[4]),"+f"(d[5]),"+f"(d[6]),"+f"(d[7]),"+f"(d[8]),"+f"(d[9]),"+f"(d[10]),"+f"(d[11]),"+f"(d[12]),"+f"(d[13]),"+f"(d[14]),"+f"(d[15]),"+f"(d[16]),"+f"(d[17]),"+f"(d[18]),"+f"(d[19]),"+f"(d[20]),"+f"(d[21]),"+f"(d[22]),"+f"(d[23]),"+f"(d[24]),"+f"(d[25]),"+f"(d[26]),"+f"(d[27]),"+f"(d[28]),"+f"(d[29]),"+f"(d[30]),"+f"(d[31]),"+f"(d[32]),"+f"(d[33]),"+f"(d[34]),"+f"(d[35]),"+f"(d[36]),"+f"(d[37]),"+f"(d[38]),"+f"(d[39]) : "r"(a[0]),"r"(a[1]),"r"(a[2]),"r"(a[3]),"l"(db),"r"(sc));
}
__device__ __forceinline__ void wg_rs96_0(float* d, const uint32_t* a, uint64_t db, int sc) {
  asm volatile("{.reg .pred p; setp.ne.b32 p, %53, 0; wgmma.mma_async.sync.aligned.m64n96k16.f32.bf16.bf16 {%0,%1,%2,%3,%4,%5,%6,%7,%8,%9,%10,%11,%12,%13,%14,%15,%16,%17,%18,%19,%20,%21,%22,%23,%24,%25,%26,%27,%28,%29,%30,%31,%32,%33,%34,%35,%36,%37,%38,%39,%40,%41,%42,%43,%44,%45,%46,%47}, {%48,%49,%50,%51}, %52, p, 1, 1, 0;}"
    : "+f"(d[0]),"+f"(d[1]),"+f"(d[2]),"+f"(d[3]),"+f"(d[4]),"+f"(d[5]),"+f"(d[6]),"+f"(d[7]),"+f"(d[8]),"+f"(d[9]),"+f"(d[10]),"+f"(d[11]),"+f"(d[12]),"+f"(d[13]),"+f"(d[14]),"+f"(d[15]),"+f"(d[16]),"+f"(d[17]),"+f"(d[18]),"+f"(d[19]),"+f"(d[20]),"+f"(d[21]),"+f"(d[22]),"+f"(d[23]),"+f"(d[24]),"+f"(d[25]),"+f"(d[26]),"+f"(d[27]),"+f"(d[28]),"+f"(d[29]),"+f"(d[30]),"+f"(d[31]),"+f"(d[32]),"+f"(d[33]),"+f"(d[34]),"+f"(d[35]),"+f"(d[36]),"+f"(d[37]),"+f"(d[38]),"+f"(d[39]),"+f"(d[40]),"+f"(d[41]),"+f"(d[42]),"+f"(d[43]),"+f"(d[44]),"+f"(d[45]),"+f"(d[46]),"+f"(d[47]) : "r"(a[0]),"r"(a[1]),"r"(a[2]),"r"(a[3]),"l"(db),"r"(sc));
}
__device__ __forceinline__ void wg_rs112_0(float* d, const uint32_t* a, uint64_t db, int sc) {
  asm volatile("{.reg .pred p; setp.ne.b32 p, %61, 0; wgmma.mma_async.sync.aligned.m64n112k16.f32.bf16.bf16 {%0,%1,%2,%3,%4,%5,%6,%7,%8,%9,%10,%11,%12,%13,%14,%15,%16,%17,%18,%19,%20,%21,%22,%23,%24,%25,%26,%27,%28,%29,%30,%31,%32,%33,%34,%35,%36,%37,%38,%39,%40,%41,%42,%43,%44,%45,%46,%47,%48,%49,%50,%51,%52,%53,%54,%55}, {%56,%57,%58,%59}, %60, p, 1, 1, 0;}"
    : "+f"(d[0]),"+f"(d[1]),"+f"(d[2]),"+f"(d[3]),"+f"(d[4]),"+f"(d[5]),"+f"(d[6]),"+f"(d[7]),"+f"(d[8]),"+f"(d[9]),"+f"(d[10]),"+f"(d[11]),"+f"(d[12]),"+f"(d[13]),"+f"(d[14]),"+f"(d[15]),"+f"(d[16]),"+f"(d[17]),"+f"(d[18]),"+f"(d[19]),"+f"(d[20]),"+f"(d[21]),"+f"(d[22]),"+f"(d[23]),"+f"(d[24]),"+f"(d[25]),"+f"(d[26]),"+f"(d[27]),"+f"(d[28]),"+f"(d[29]),"+f"(d[30]),"+f"(d[31]),"+f"(d[32]),"+f"(d[33]),"+f"(d[34]),"+f"(d[35]),"+f"(d[36]),"+f"(d[37]),"+f"(d[38]),"+f"(d[39]),"+f"(d[40]),"+f"(d[41]),"+f"(d[42]),"+f"(d[43]),"+f"(d[44]),"+f"(d[45]),"+f"(d[46]),"+f"(d[47]),"+f"(d[48]),"+f"(d[49]),"+f"(d[50]),"+f"(d[51]),"+f"(d[52]),"+f"(d[53]),"+f"(d[54]),"+f"(d[55]) : "r"(a[0]),"r"(a[1]),"r"(a[2]),"r"(a[3]),"l"(db),"r"(sc));
}
__device__ __forceinline__ void wg_rs128_0(float* d, const uint32_t* a, uint64_t db, int sc) {
  asm volatile("{.reg .pred p; setp.ne.b32 p, %69, 0; wgmma.mma_async.sync.aligned.m64n128k16.f32.bf16.bf16 {%0,%1,%2,%3,%4,%5,%6,%7,%8,%9,%10,%11,%12,%13,%14,%15,%16,%17,%18,%19,%20,%21,%22,%23,%24,%25,%26,%27,%28,%29,%30,%31,%32,%33,%34,%35,%36,%37,%38,%39,%40,%41,%42,%43,%44,%45,%46,%47,%48,%49,%50,%51,%52,%53,%54,%55,%56,%57,%58,%59,%60,%61,%62,%63}, {%64,%65,%66,%67}, %68, p, 1, 1, 0;}"
    : "+f"(d[0]),"+f"(d[1]),"+f"(d[2]),"+f"(d[3]),"+f"(d[4]),"+f"(d[5]),"+f"(d[6]),"+f"(d[7]),"+f"(d[8]),"+f"(d[9]),"+f"(d[10]),"+f"(d[11]),"+f"(d[12]),"+f"(d[13]),"+f"(d[14]),"+f"(d[15]),"+f"(d[16]),"+f"(d[17]),"+f"(d[18]),"+f"(d[19]),"+f"(d[20]),"+f"(d[21]),"+f"(d[22]),"+f"(d[23]),"+f"(d[24]),"+f"(d[25]),"+f"(d[26]),"+f"(d[27]),"+f"(d[28]),"+f"(d[29]),"+f"(d[30]),"+f"(d[31]),"+f"(d[32]),"+f"(d[33]),"+f"(d[34]),"+f"(d[35]),"+f"(d[36]),"+f"(d[37]),"+f"(d[38]),"+f"(d[39]),"+f"(d[40]),"+f"(d[41]),"+f"(d[42]),"+f"(d[43]),"+f"(d[44]),"+f"(d[45]),"+f"(d[46]),"+f"(d[47]),"+f"(d[48]),"+f"(d[49]),"+f"(d[50]),"+f"(d[51]),"+f"(d[52]),"+f"(d[53]),"+f"(d[54]),"+f"(d[55]),"+f"(d[56]),"+f"(d[57]),"+f"(d[58]),"+f"(d[59]),"+f"(d[60]),"+f"(d[61]),"+f"(d[62]),"+f"(d[63]) : "r"(a[0]),"r"(a[1]),"r"(a[2]),"r"(a[3]),"l"(db),"r"(sc));
}
__device__ __forceinline__ void wg_rs144_0(float* d, const uint32_t* a, uint64_t db, int sc) {
  asm volatile("{.reg .pred p; setp.ne.b32 p, %77, 0; wgmma.mma_async.sync.aligned.m64n144k16.f32.bf16.bf16 {%0,%1,%2,%3,%4,%5,%6,%7,%8,%9,%10,%11,%12,%13,%14,%15,%16,%17,%18,%19,%20,%21,%22,%23,%24,%25,%26,%27,%28,%29,%30,%31,%32,%33,%34,%35,%36,%37,%38,%39,%40,%41,%42,%43,%44,%45,%46,%47,%48,%49,%50,%51,%52,%53,%54,%55,%56,%57,%58,%59,%60,%61,%62,%63,%64,%65,%66,%67,%68,%69,%70,%71}, {%72,%73,%74,%75}, %76, p, 1, 1, 0;}"
    : "+f"(d[0]),"+f"(d[1]),"+f"(d[2]),"+f"(d[3]),"+f"(d[4]),"+f"(d[5]),"+f"(d[6]),"+f"(d[7]),"+f"(d[8]),"+f"(d[9]),"+f"(d[10]),"+f"(d[11]),"+f"(d[12]),"+f"(d[13]),"+f"(d[14]),"+f"(d[15]),"+f"(d[16]),"+f"(d[17]),"+f"(d[18]),"+f"(d[19]),"+f"(d[20]),"+f"(d[21]),"+f"(d[22]),"+f"(d[23]),"+f"(d[24]),"+f"(d[25]),"+f"(d[26]),"+f"(d[27]),"+f"(d[28]),"+f"(d[29]),"+f"(d[30]),"+f"(d[31]),"+f"(d[32]),"+f"(d[33]),"+f"(d[34]),"+f"(d[35]),"+f"(d[36]),"+f"(d[37]),"+f"(d[38]),"+f"(d[39]),"+f"(d[40]),"+f"(d[41]),"+f"(d[42]),"+f"(d[43]),"+f"(d[44]),"+f"(d[45]),"+f"(d[46]),"+f"(d[47]),"+f"(d[48]),"+f"(d[49]),"+f"(d[50]),"+f"(d[51]),"+f"(d[52]),"+f"(d[53]),"+f"(d[54]),"+f"(d[55]),"+f"(d[56]),"+f"(d[57]),"+f"(d[58]),"+f"(d[59]),"+f"(d[60]),"+f"(d[61]),"+f"(d[62]),"+f"(d[63]),"+f"(d[64]),"+f"(d[65]),"+f"(d[66]),"+f"(d[67]),"+f"(d[68]),"+f"(d[69]),"+f"(d[70]),"+f"(d[71]) : "r"(a[0]),"r"(a[1]),"r"(a[2]),"r"(a[3]),"l"(db),"r"(sc));
}
__device__ __forceinline__ void wg_rs160_0(float* d, const uint32_t* a, uint64_t db, int sc) {
  asm volatile("{.reg .pred p; setp.ne.b32 p, %85, 0; wgmma.mma_async.sync.aligned.m64n160k16.f32.bf16.bf16 {%0,%1,%2,%3,%4,%5,%6,%7,%8,%9,%10,%11,%12,%13,%14,%15,%16,%17,%18,%19,%20,%21,%22,%23,%24,%25,%26,%27,%28,%29,%30,%31,%32,%33,%34,%35,%36,%37,%38,%39,%40,%41,%42,%43,%44,%45,%46,%47,%48,%49,%50,%51,%52,%53,%54,%55,%56,%57,%58,%59,%60,%61,%62,%63,%64,%65,%66,%67,%68,%69,%70,%71,%72,%73,%74,%75,%76,%77,%78,%79}, {%80,%81,%82,%83}, %84, p, 1, 1, 0;}"
    : "+f"(d[0]),"+f"(d[1]),"+f"(d[2]),"+f"(d[3]),"+f"(d[4]),"+f"(d[5]),"+f"(d[6]),"+f"(d[7]),"+f"(d[8]),"+f"(d[9]),"+f"(d[10]),"+f"(d[11]),"+f"(d[12]),"+f"(d[13]),"+f"(d[14]),"+f"(d[15]),"+f"(d[16]),"+f"(d[17]),"+f"(d[18]),"+f"(d[19]),"+f"(d[20]),"+f"(d[21]),"+f"(d[22]),"+f"(d[23]),"+f"(d[24]),"+f"(d[25]),"+f"(d[26]),"+f"(d[27]),"+f"(d[28]),"+f"(d[29]),"+f"(d[30]),"+f"(d[31]),"+f"(d[32]),"+f"(d[33]),"+f"(d[34]),"+f"(d[35]),"+f"(d[36]),"+f"(d[37]),"+f"(d[38]),"+f"(d[39]),"+f"(d[40]),"+f"(d[41]),"+f"(d[42]),"+f"(d[43]),"+f"(d[44]),"+f"(d[45]),"+f"(d[46]),"+f"(d[47]),"+f"(d[48]),"+f"(d[49]),"+f"(d[50]),"+f"(d[51]),"+f"(d[52]),"+f"(d[53]),"+f"(d[54]),"+f"(d[55]),"+f"(d[56]),"+f"(d[57]),"+f"(d[58]),"+f"(d[59]),"+f"(d[60]),"+f"(d[61]),"+f"(d[62]),"+f"(d[63]),"+f"(d[64]),"+f"(d[65]),"+f"(d[66]),"+f"(d[67]),"+f"(d[68]),"+f"(d[69]),"+f"(d[70]),"+f"(d[71]),"+f"(d[72]),"+f"(d[73]),"+f"(d[74]),"+f"(d[75]),"+f"(d[76]),"+f"(d[77]),"+f"(d[78]),"+f"(d[79]) : "r"(a[0]),"r"(a[1]),"r"(a[2]),"r"(a[3]),"l"(db),"r"(sc));
}
__device__ __forceinline__ void wg_rs176_0(float* d, const uint32_t* a, uint64_t db, int sc) {
  asm volatile("{.reg .pred p; setp.ne.b32 p, %93, 0; wgmma.mma_async.sync.aligned.m64n176k16.f32.bf16.bf16 {%0,%1,%2,%3,%4,%5,%6,%7,%8,%9,%10,%11,%12,%13,%14,%15,%16,%17,%18,%19,%20,%21,%22,%23,%24,%25,%26,%27,%28,%29,%30,%31,%32,%33,%34,%35,%36,%37,%38,%39,%40,%41,%42,%43,%44,%45,%46,%47,%48,%49,%50,%51,%52,%53,%54,%55,%56,%57,%58,%59,%60,%61,%62,%63,%64,%65,%66,%67,%68,%69,%70,%71,%72,%73,%74,%75,%76,%77,%78,%79,%80,%81,%82,%83,%84,%85,%86,%87}, {%88,%89,%90,%91}, %92, p, 1, 1, 0;}"
    : "+f"(d[0]),"+f"(d[1]),"+f"(d[2]),"+f"(d[3]),"+f"(d[4]),"+f"(d[5]),"+f"(d[6]),"+f"(d[7]),"+f"(d[8]),"+f"(d[9]),"+f"(d[10]),"+f"(d[11]),"+f"(d[12]),"+f"(d[13]),"+f"(d[14]),"+f"(d[15]),"+f"(d[16]),"+f"(d[17]),"+f"(d[18]),"+f"(d[19]),"+f"(d[20]),"+f"(d[21]),"+f"(d[22]),"+f"(d[23]),"+f"(d[24]),"+f"(d[25]),"+f"(d[26]),"+f"(d[27]),"+f"(d[28]),"+f"(d[29]),"+f"(d[30]),"+f"(d[31]),"+f"(d[32]),"+f"(d[33]),"+f"(d[34]),"+f"(d[35]),"+f"(d[36]),"+f"(d[37]),"+f"(d[38]),"+f"(d[39]),"+f"(d[40]),"+f"(d[41]),"+f"(d[42]),"+f"(d[43]),"+f"(d[44]),"+f"(d[45]),"+f"(d[46]),"+f"(d[47]),"+f"(d[48]),"+f"(d[49]),"+f"(d[50]),"+f"(d[51]),"+f"(d[52]),"+f"(d[53]),"+f"(d[54]),"+f"(d[55]),"+f"(d[56]),"+f"(d[57]),"+f"(d[58]),"+f"(d[59]),"+f"(d[60]),"+f"(d[61]),"+f"(d[62]),"+f"(d[63]),"+f"(d[64]),"+f"(d[65]),"+f"(d[66]),"+f"(d[67]),"+f"(d[68]),"+f"(d[69]),"+f"(d[70]),"+f"(d[71]),"+f"(d[72]),"+f"(d[73]),"+f"(d[74]),"+f"(d[75]),"+f"(d[76]),"+f"(d[77]),"+f"(d[78]),"+f"(d[79]),"+f"(d[80]),"+f"(d[81]),"+f"(d[82]),"+f"(d[83]),"+f"(d[84]),"+f"(d[85]),"+f"(d[86]),"+f"(d[87]) : "r"(a[0]),"r"(a[1]),"r"(a[2]),"r"(a[3]),"l"(db),"r"(sc));
}
__device__ __forceinline__ void wg_rs192_0(float* d, const uint32_t* a, uint64_t db, int sc) {
  asm volatile("{.reg .pred p; setp.ne.b32 p, %101, 0; wgmma.mma_async.sync.aligned.m64n192k16.f32.bf16.bf16 {%0,%1,%2,%3,%4,%5,%6,%7,%8,%9,%10,%11,%12,%13,%14,%15,%16,%17,%18,%19,%20,%21,%22,%23,%24,%25,%26,%27,%28,%29,%30,%31,%32,%33,%34,%35,%36,%37,%38,%39,%40,%41,%42,%43,%44,%45,%46,%47,%48,%49,%50,%51,%52,%53,%54,%55,%56,%57,%58,%59,%60,%61,%62,%63,%64,%65,%66,%67,%68,%69,%70,%71,%72,%73,%74,%75,%76,%77,%78,%79,%80,%81,%82,%83,%84,%85,%86,%87,%88,%89,%90,%91,%92,%93,%94,%95}, {%96,%97,%98,%99}, %100, p, 1, 1, 0;}"
    : "+f"(d[0]),"+f"(d[1]),"+f"(d[2]),"+f"(d[3]),"+f"(d[4]),"+f"(d[5]),"+f"(d[6]),"+f"(d[7]),"+f"(d[8]),"+f"(d[9]),"+f"(d[10]),"+f"(d[11]),"+f"(d[12]),"+f"(d[13]),"+f"(d[14]),"+f"(d[15]),"+f"(d[16]),"+f"(d[17]),"+f"(d[18]),"+f"(d[19]),"+f"(d[20]),"+f"(d[21]),"+f"(d[22]),"+f"(d[23]),"+f"(d[24]),"+f"(d[25]),"+f"(d[26]),"+f"(d[27]),"+f"(d[28]),"+f"(d[29]),"+f"(d[30]),"+f"(d[31]),"+f"(d[32]),"+f"(d[33]),"+f"(d[34]),"+f"(d[35]),"+f"(d[36]),"+f"(d[37]),"+f"(d[38]),"+f"(d[39]),"+f"(d[40]),"+f"(d[41]),"+f"(d[42]),"+f"(d[43]),"+f"(d[44]),"+f"(d[45]),"+f"(d[46]),"+f"(d[47]),"+f"(d[48]),"+f"(d[49]),"+f"(d[50]),"+f"(d[51]),"+f"(d[52]),"+f"(d[53]),"+f"(d[54]),"+f"(d[55]),"+f"(d[56]),"+f"(d[57]),"+f"(d[58]),"+f"(d[59]),"+f"(d[60]),"+f"(d[61]),"+f"(d[62]),"+f"(d[63]),"+f"(d[64]),"+f"(d[65]),"+f"(d[66]),"+f"(d[67]),"+f"(d[68]),"+f"(d[69]),"+f"(d[70]),"+f"(d[71]),"+f"(d[72]),"+f"(d[73]),"+f"(d[74]),"+f"(d[75]),"+f"(d[76]),"+f"(d[77]),"+f"(d[78]),"+f"(d[79]),"+f"(d[80]),"+f"(d[81]),"+f"(d[82]),"+f"(d[83]),"+f"(d[84]),"+f"(d[85]),"+f"(d[86]),"+f"(d[87]),"+f"(d[88]),"+f"(d[89]),"+f"(d[90]),"+f"(d[91]),"+f"(d[92]),"+f"(d[93]),"+f"(d[94]),"+f"(d[95]) : "r"(a[0]),"r"(a[1]),"r"(a[2]),"r"(a[3]),"l"(db),"r"(sc));
}
__device__ __forceinline__ void wg_ss192_11(float* d, uint64_t da, uint64_t db, int sc) {
  asm volatile("{.reg .pred p; setp.ne.b32 p, %98, 0; wgmma.mma_async.sync.aligned.m64n192k16.f32.bf16.bf16 {%0,%1,%2,%3,%4,%5,%6,%7,%8,%9,%10,%11,%12,%13,%14,%15,%16,%17,%18,%19,%20,%21,%22,%23,%24,%25,%26,%27,%28,%29,%30,%31,%32,%33,%34,%35,%36,%37,%38,%39,%40,%41,%42,%43,%44,%45,%46,%47,%48,%49,%50,%51,%52,%53,%54,%55,%56,%57,%58,%59,%60,%61,%62,%63,%64,%65,%66,%67,%68,%69,%70,%71,%72,%73,%74,%75,%76,%77,%78,%79,%80,%81,%82,%83,%84,%85,%86,%87,%88,%89,%90,%91,%92,%93,%94,%95}, %96, %97, p, 1, 1, 1, 1;}"
    : "+f"(d[0]),"+f"(d[1]),"+f"(d[2]),"+f"(d[3]),"+f"(d[4]),"+f"(d[5]),"+f"(d[6]),"+f"(d[7]),"+f"(d[8]),"+f"(d[9]),"+f"(d[10]),"+f"(d[11]),"+f"(d[12]),"+f"(d[13]),"+f"(d[14]),"+f"(d[15]),"+f"(d[16]),"+f"(d[17]),"+f"(d[18]),"+f"(d[19]),"+f"(d[20]),"+f"(d[21]),"+f"(d[22]),"+f"(d[23]),"+f"(d[24]),"+f"(d[25]),"+f"(d[26]),"+f"(d[27]),"+f"(d[28]),"+f"(d[29]),"+f"(d[30]),"+f"(d[31]),"+f"(d[32]),"+f"(d[33]),"+f"(d[34]),"+f"(d[35]),"+f"(d[36]),"+f"(d[37]),"+f"(d[38]),"+f"(d[39]),"+f"(d[40]),"+f"(d[41]),"+f"(d[42]),"+f"(d[43]),"+f"(d[44]),"+f"(d[45]),"+f"(d[46]),"+f"(d[47]),"+f"(d[48]),"+f"(d[49]),"+f"(d[50]),"+f"(d[51]),"+f"(d[52]),"+f"(d[53]),"+f"(d[54]),"+f"(d[55]),"+f"(d[56]),"+f"(d[57]),"+f"(d[58]),"+f"(d[59]),"+f"(d[60]),"+f"(d[61]),"+f"(d[62]),"+f"(d[63]),"+f"(d[64]),"+f"(d[65]),"+f"(d[66]),"+f"(d[67]),"+f"(d[68]),"+f"(d[69]),"+f"(d[70]),"+f"(d[71]),"+f"(d[72]),"+f"(d[73]),"+f"(d[74]),"+f"(d[75]),"+f"(d[76]),"+f"(d[77]),"+f"(d[78]),"+f"(d[79]),"+f"(d[80]),"+f"(d[81]),"+f"(d[82]),"+f"(d[83]),"+f"(d[84]),"+f"(d[85]),"+f"(d[86]),"+f"(d[87]),"+f"(d[88]),"+f"(d[89]),"+f"(d[90]),"+f"(d[91]),"+f"(d[92]),"+f"(d[93]),"+f"(d[94]),"+f"(d[95]) : "l"(da),"l"(db),"r"(sc));
}
__device__ __forceinline__ void wg_ss192_01(float* d, uint64_t da, uint64_t db, int sc) {
  asm volatile("{.reg .pred p; setp.ne.b32 p, %98, 0; wgmma.mma_async.sync.aligned.m64n192k16.f32.bf16.bf16 {%0,%1,%2,%3,%4,%5,%6,%7,%8,%9,%10,%11,%12,%13,%14,%15,%16,%17,%18,%19,%20,%21,%22,%23,%24,%25,%26,%27,%28,%29,%30,%31,%32,%33,%34,%35,%36,%37,%38,%39,%40,%41,%42,%43,%44,%45,%46,%47,%48,%49,%50,%51,%52,%53,%54,%55,%56,%57,%58,%59,%60,%61,%62,%63,%64,%65,%66,%67,%68,%69,%70,%71,%72,%73,%74,%75,%76,%77,%78,%79,%80,%81,%82,%83,%84,%85,%86,%87,%88,%89,%90,%91,%92,%93,%94,%95}, %96, %97, p, 1, 1, 0, 1;}"
    : "+f"(d[0]),"+f"(d[1]),"+f"(d[2]),"+f"(d[3]),"+f"(d[4]),"+f"(d[5]),"+f"(d[6]),"+f"(d[7]),"+f"(d[8]),"+f"(d[9]),"+f"(d[10]),"+f"(d[11]),"+f"(d[12]),"+f"(d[13]),"+f"(d[14]),"+f"(d[15]),"+f"(d[16]),"+f"(d[17]),"+f"(d[18]),"+f"(d[19]),"+f"(d[20]),"+f"(d[21]),"+f"(d[22]),"+f"(d[23]),"+f"(d[24]),"+f"(d[25]),"+f"(d[26]),"+f"(d[27]),"+f"(d[28]),"+f"(d[29]),"+f"(d[30]),"+f"(d[31]),"+f"(d[32]),"+f"(d[33]),"+f"(d[34]),"+f"(d[35]),"+f"(d[36]),"+f"(d[37]),"+f"(d[38]),"+f"(d[39]),"+f"(d[40]),"+f"(d[41]),"+f"(d[42]),"+f"(d[43]),"+f"(d[44]),"+f"(d[45]),"+f"(d[46]),"+f"(d[47]),"+f"(d[48]),"+f"(d[49]),"+f"(d[50]),"+f"(d[51]),"+f"(d[52]),"+f"(d[53]),"+f"(d[54]),"+f"(d[55]),"+f"(d[56]),"+f"(d[57]),"+f"(d[58]),"+f"(d[59]),"+f"(d[60]),"+f"(d[61]),"+f"(d[62]),"+f"(d[63]),"+f"(d[64]),"+f"(d[65]),"+f"(d[66]),"+f"(d[67]),"+f"(d[68]),"+f"(d[69]),"+f"(d[70]),"+f"(d[71]),"+f"(d[72]),"+f"(d[73]),"+f"(d[74]),"+f"(d[75]),"+f"(d[76]),"+f"(d[77]),"+f"(d[78]),"+f"(d[79]),"+f"(d[80]),"+f"(d[81]),"+f"(d[82]),"+f"(d[83]),"+f"(d[84]),"+f"(d[85]),"+f"(d[86]),"+f"(d[87]),"+f"(d[88]),"+f"(d[89]),"+f"(d[90]),"+f"(d[91]),"+f"(d[92]),"+f"(d[93]),"+f"(d[94]),"+f"(d[95]) : "l"(da),"l"(db),"r"(sc));
}
__device__ __forceinline__ void wg_ss160_01(float* d, uint64_t da, uint64_t db, int sc) {
  asm volatile("{.reg .pred p; setp.ne.b32 p, %82, 0; wgmma.mma_async.sync.aligned.m64n160k16.f32.bf16.bf16 {%0,%1,%2,%3,%4,%5,%6,%7,%8,%9,%10,%11,%12,%13,%14,%15,%16,%17,%18,%19,%20,%21,%22,%23,%24,%25,%26,%27,%28,%29,%30,%31,%32,%33,%34,%35,%36,%37,%38,%39,%40,%41,%42,%43,%44,%45,%46,%47,%48,%49,%50,%51,%52,%53,%54,%55,%56,%57,%58,%59,%60,%61,%62,%63,%64,%65,%66,%67,%68,%69,%70,%71,%72,%73,%74,%75,%76,%77,%78,%79}, %80, %81, p, 1, 1, 0, 1;}"
    : "+f"(d[0]),"+f"(d[1]),"+f"(d[2]),"+f"(d[3]),"+f"(d[4]),"+f"(d[5]),"+f"(d[6]),"+f"(d[7]),"+f"(d[8]),"+f"(d[9]),"+f"(d[10]),"+f"(d[11]),"+f"(d[12]),"+f"(d[13]),"+f"(d[14]),"+f"(d[15]),"+f"(d[16]),"+f"(d[17]),"+f"(d[18]),"+f"(d[19]),"+f"(d[20]),"+f"(d[21]),"+f"(d[22]),"+f"(d[23]),"+f"(d[24]),"+f"(d[25]),"+f"(d[26]),"+f"(d[27]),"+f"(d[28]),"+f"(d[29]),"+f"(d[30]),"+f"(d[31]),"+f"(d[32]),"+f"(d[33]),"+f"(d[34]),"+f"(d[35]),"+f"(d[36]),"+f"(d[37]),"+f"(d[38]),"+f"(d[39]),"+f"(d[40]),"+f"(d[41]),"+f"(d[42]),"+f"(d[43]),"+f"(d[44]),"+f"(d[45]),"+f"(d[46]),"+f"(d[47]),"+f"(d[48]),"+f"(d[49]),"+f"(d[50]),"+f"(d[51]),"+f"(d[52]),"+f"(d[53]),"+f"(d[54]),"+f"(d[55]),"+f"(d[56]),"+f"(d[57]),"+f"(d[58]),"+f"(d[59]),"+f"(d[60]),"+f"(d[61]),"+f"(d[62]),"+f"(d[63]),"+f"(d[64]),"+f"(d[65]),"+f"(d[66]),"+f"(d[67]),"+f"(d[68]),"+f"(d[69]),"+f"(d[70]),"+f"(d[71]),"+f"(d[72]),"+f"(d[73]),"+f"(d[74]),"+f"(d[75]),"+f"(d[76]),"+f"(d[77]),"+f"(d[78]),"+f"(d[79]) : "l"(da),"l"(db),"r"(sc));
}
__device__ __forceinline__ void wg_ss96_01(float* d, uint64_t da, uint64_t db, int sc) {
  asm volatile("{.reg .pred p; setp.ne.b32 p, %50, 0; wgmma.mma_async.sync.aligned.m64n96k16.f32.bf16.bf16 {%0,%1,%2,%3,%4,%5,%6,%7,%8,%9,%10,%11,%12,%13,%14,%15,%16,%17,%18,%19,%20,%21,%22,%23,%24,%25,%26,%27,%28,%29,%30,%31,%32,%33,%34,%35,%36,%37,%38,%39,%40,%41,%42,%43,%44,%45,%46,%47}, %48, %49, p, 1, 1, 0, 1;}"
    : "+f"(d[0]),"+f"(d[1]),"+f"(d[2]),"+f"(d[3]),"+f"(d[4]),"+f"(d[5]),"+f"(d[6]),"+f"(d[7]),"+f"(d[8]),"+f"(d[9]),"+f"(d[10]),"+f"(d[11]),"+f"(d[12]),"+f"(d[13]),"+f"(d[14]),"+f"(d[15]),"+f"(d[16]),"+f"(d[17]),"+f"(d[18]),"+f"(d[19]),"+f"(d[20]),"+f"(d[21]),"+f"(d[22]),"+f"(d[23]),"+f"(d[24]),"+f"(d[25]),"+f"(d[26]),"+f"(d[27]),"+f"(d[28]),"+f"(d[29]),"+f"(d[30]),"+f"(d[31]),"+f"(d[32]),"+f"(d[33]),"+f"(d[34]),"+f"(d[35]),"+f"(d[36]),"+f"(d[37]),"+f"(d[38]),"+f"(d[39]),"+f"(d[40]),"+f"(d[41]),"+f"(d[42]),"+f"(d[43]),"+f"(d[44]),"+f"(d[45]),"+f"(d[46]),"+f"(d[47]) : "l"(da),"l"(db),"r"(sc));
}
__device__ __forceinline__ void wg_ss64_01(float* d, uint64_t da, uint64_t db, int sc) {
  asm volatile("{.reg .pred p; setp.ne.b32 p, %34, 0; wgmma.mma_async.sync.aligned.m64n64k16.f32.bf16.bf16 {%0,%1,%2,%3,%4,%5,%6,%7,%8,%9,%10,%11,%12,%13,%14,%15,%16,%17,%18,%19,%20,%21,%22,%23,%24,%25,%26,%27,%28,%29,%30,%31}, %32, %33, p, 1, 1, 0, 1;}"
    : "+f"(d[0]),"+f"(d[1]),"+f"(d[2]),"+f"(d[3]),"+f"(d[4]),"+f"(d[5]),"+f"(d[6]),"+f"(d[7]),"+f"(d[8]),"+f"(d[9]),"+f"(d[10]),"+f"(d[11]),"+f"(d[12]),"+f"(d[13]),"+f"(d[14]),"+f"(d[15]),"+f"(d[16]),"+f"(d[17]),"+f"(d[18]),"+f"(d[19]),"+f"(d[20]),"+f"(d[21]),"+f"(d[22]),"+f"(d[23]),"+f"(d[24]),"+f"(d[25]),"+f"(d[26]),"+f"(d[27]),"+f"(d[28]),"+f"(d[29]),"+f"(d[30]),"+f"(d[31]) : "l"(da),"l"(db),"r"(sc));
}
__device__ __forceinline__ void wg_rs160_1(float* d, const uint32_t* a, uint64_t db, int sc) {
  asm volatile("{.reg .pred p; setp.ne.b32 p, %85, 0; wgmma.mma_async.sync.aligned.m64n160k16.f32.bf16.bf16 {%0,%1,%2,%3,%4,%5,%6,%7,%8,%9,%10,%11,%12,%13,%14,%15,%16,%17,%18,%19,%20,%21,%22,%23,%24,%25,%26,%27,%28,%29,%30,%31,%32,%33,%34,%35,%36,%37,%38,%39,%40,%41,%42,%43,%44,%45,%46,%47,%48,%49,%50,%51,%52,%53,%54,%55,%56,%57,%58,%59,%60,%61,%62,%63,%64,%65,%66,%67,%68,%69,%70,%71,%72,%73,%74,%75,%76,%77,%78,%79}, {%80,%81,%82,%83}, %84, p, 1, 1, 1;}"
    : "+f"(d[0]),"+f"(d[1]),"+f"(d[2]),"+f"(d[3]),"+f"(d[4]),"+f"(d[5]),"+f"(d[6]),"+f"(d[7]),"+f"(d[8]),"+f"(d[9]),"+f"(d[10]),"+f"(d[11]),"+f"(d[12]),"+f"(d[13]),"+f"(d[14]),"+f"(d[15]),"+f"(d[16]),"+f"(d[17]),"+f"(d[18]),"+f"(d[19]),"+f"(d[20]),"+f"(d[21]),"+f"(d[22]),"+f"(d[23]),"+f"(d[24]),"+f"(d[25]),"+f"(d[26]),"+f"(d[27]),"+f"(d[28]),"+f"(d[29]),"+f"(d[30]),"+f"(d[31]),"+f"(d[32]),"+f"(d[33]),"+f"(d[34]),"+f"(d[35]),"+f"(d[36]),"+f"(d[37]),"+f"(d[38]),"+f"(d[39]),"+f"(d[40]),"+f"(d[41]),"+f"(d[42]),"+f"(d[43]),"+f"(d[44]),"+f"(d[45]),"+f"(d[46]),"+f"(d[47]),"+f"(d[48]),"+f"(d[49]),"+f"(d[50]),"+f"(d[51]),"+f"(d[52]),"+f"(d[53]),"+f"(d[54]),"+f"(d[55]),"+f"(d[56]),"+f"(d[57]),"+f"(d[58]),"+f"(d[59]),"+f"(d[60]),"+f"(d[61]),"+f"(d[62]),"+f"(d[63]),"+f"(d[64]),"+f"(d[65]),"+f"(d[66]),"+f"(d[67]),"+f"(d[68]),"+f"(d[69]),"+f"(d[70]),"+f"(d[71]),"+f"(d[72]),"+f"(d[73]),"+f"(d[74]),"+f"(d[75]),"+f"(d[76]),"+f"(d[77]),"+f"(d[78]),"+f"(d[79]) : "r"(a[0]),"r"(a[1]),"r"(a[2]),"r"(a[3]),"l"(db),"r"(sc));
}
__device__ __forceinline__ void wg_ss8_10(float* d, uint64_t da, uint64_t db, int sc) {
  asm volatile("{.reg .pred p; setp.ne.b32 p, %6, 0; wgmma.mma_async.sync.aligned.m64n8k16.f32.bf16.bf16 {%0,%1,%2,%3}, %4, %5, p, 1, 1, 1, 0;}"
    : "+f"(d[0]),"+f"(d[1]),"+f"(d[2]),"+f"(d[3]) : "l"(da),"l"(db),"r"(sc));
}

constexpr uint32_t DB = 1024;
constexpr int WSLOT = 24576, NW = 6, ASLOT = 8192, ARING = 4 * ASLOT;
constexpr int OFF_A = NW * WSLOT;
constexpr int OFF_PB = OFF_A + 2 * ARING;
constexpr int OFF_CV = OFF_PB + 16384, OFF_ST = OFF_CV + 768, OFF_TS = OFF_ST + 256, OFF_MODR = OFF_TS + 512, OFF_BAR = OFF_MODR + 80, SMEM_BYTES = OFF_BAR + 1168;
constexpr int OFF_BX = OFF_PB, OFF_AX = OFF_BX + 12288, OFF_RT = OFF_AX + 2048, OFF_GB = OFF_RT + 512, OFF_CO = OFF_CV;
constexpr int OFF_UV = 5 * WSLOT, OFF_UVE = OFF_PB, OFF_SX = OFF_A + ARING + 3 * ASLOT, OFF_X1 = 2 * WSLOT + ASLOT, OFF_XCH = WSLOT;
constexpr int OFF_Q = 0, KV_V = 4096, KV_H = 8192, F_E = 16, F_O = 4176, OFF_TAP = 168576, OFF_MR = OFF_A + 3 * ASLOT;
constexpr uint64_t pk5(int a, int b, int c, int d, int e) { return (uint64_t)(a / 128) | (uint64_t)(b / 128) << 12 | (uint64_t)(c / 128) << 24 | (uint64_t)(d / 128) << 36 | (uint64_t)(e / 128) << 48; }
constexpr uint64_t T_KV = pk5(20480, 30720, 40960, 180224, 190464), T_F = pk5(51200, 59648, 200192, 147456, 155904), T_X = pk5(208512, 164352, 68096, 208512, 164352),
                   T_P = pk5(131072, OFF_PB, 114688, 131072, OFF_PB);
__host__ __device__ __forceinline__ uint32_t tab(uint64_t t, int c) { return ((uint32_t)(t >> (12 * c)) & 0xFFF) << 7; }
enum { B_KV = 0, B_FRAW = 5, B_Q = 10, B_XR = 16, B_MR = B_XR + 5, B_QTOK, B_ST1, B_MODR, B_S3 = B_MODR + 5, B_FIN, B_FL = 32, B_PFULL = B_FL + 5, B_PEMPTY = B_PFULL + 5, B_FRDY = B_PEMPTY + 5,
       B_EXT = B_FRDY + 5, B_QTD, B_LAG, B_GB, B_UVD, B_TURN, B_FULL = 60, B_RETRY = B_FULL + 33, B_XFREE = B_RETRY + 9, B_BX, B_UVB, B_UVE, B_SX, B_EMPTY = 109 };
static_assert(B_MODR + 5 <= B_FL && B_UVD < B_FULL && B_SX + 2 == B_EMPTY - 1, "barrier groups");
#define BAR(i) (base + OFF_BAR + 8 * (i))

constexpr int NE = 18;
struct Maps { CUtensorMap km, v, q, kh, tap, wm, w1s, w3s, xs, w1, w3, w1e, w3e, x1s, x1b, w2a, w2b, outa, outb; };
struct Ptrs { const bf16 *ssmk, *c, *ssmd; Scratch* g; uint64_t prog, cprog[2]; int boff, te, pe, th, zero; uint32_t xd, aw, cn, c0, fin, turn, mr2, m3, seq; float one; uint2 sched[NE]; uint32_t wdep[20], wt[5]; uint2 w2t[12]; int hid[3][9]; };

#define REGION_IDS int tid, lane, bid; \
  asm volatile("mov.u32 %0, %%tid.x;" : "=r"(tid)); asm volatile("mov.u32 %0, %%laneid;" : "=r"(lane)); asm volatile("mov.u32 %0, %%ctaid.x;" : "=r"(bid)); \
  const int i0 = tid & 127; (void)i0; (void)lane; (void)bid

__device__ __forceinline__ void ffn_role(int& h, int& j, int& r) {
  uint32_t b;
  asm volatile("mov.u32 %0, %%ctaid.x;" : "=r"(b));
  const uint32_t c = b >> 1, q = (c - 36) * 37 >> 8, e = c - 36 - 7 * q;
  h = b & 1;
  const uint32_t k = c < 4 ? 0 : c < 36 ? (c - 4) & 7 : e + 1, p = c < 4 ? c : c < 36 ? (c - 4) >> 3 : q, up = c - 4 >= 32;
  j = 2 * (k & 1) + up;
  r = 2 * (k & 6) + p;
}
__device__ __forceinline__ int fslice(int j, int e) { return e == 2 ? j ^ 1 : (~j & 2) + e; }
__device__ __forceinline__ int mod_ch(int p) { return p < 40 ? (p >> 3) * 128 + (p & 1) * 64 : 64 * (p < 50 ? p - 40 : p - 50); }
__device__ __forceinline__ int mod_col(int p) { return mod_ch(p) + 640 * (p < 40 ? 0x4210 >> (2 * (p & 6)) & 7 : p < 50 ? 3 : 5); }
__device__ __forceinline__ uint32_t mod_sum(uint2 v) { return pack_bf16(0.f, __uint_as_float(v.x) + __uint_as_float(v.y)); }

constexpr int NT = 3, LAG2 = 29, MG = 4;
__device__ __forceinline__ int w_block(int up, int m) { return m == 1 ? 2 + 3 * up : 3 * (m >> 1) + up; }
__host__ __device__ constexpr int w2_at(int v) { return 8192 * (v ? 0x0613030008ull >> v % 5 * 8 & 255 : 15); }
__host__ __device__ constexpr int w2_step(int v) { return 8192 * (v ? 0x32113 >> v % 5 * 4 & 15 : 1); }
__host__ __device__ constexpr int hid_at(int m, int g) { return 8192 * ((g ? 0x0D07110F1816ull : 0x0A19101A1412ull) >> m % 6 * 8 & 255); }
__host__ __device__ constexpr uint32_t w2_desc(int v) { return (DB + w2_at(v)) >> 4 | w2_step(v) << 12; }
__device__ __forceinline__ int next_slot(int s) { return s >= 4 * WSLOT ? 0 : s + WSLOT; }

template <int U> __device__ __forceinline__ void cstep(float* acc, const uint32_t* A, uint64_t db) {
  const uint32_t* a = A + 4 * U;
  const uint64_t d = db + 16 * U;
  if (U == 4) { wg_rs64_0(acc + 96, A, db + 192, 0); wg_rs48_0(acc + 96, A + 4, db + 208, 1); wg_rs32_0(acc + 96, A + 8, db + 224, 1); wg_rs16_0(acc + 96, A + 12, db + 240, 1); }
  if (U <= 4) wg_rs192_0(acc, a, d, U);
  if (U == 5) wg_rs176_0(acc, a, d, 1);
  if (U == 6) wg_rs160_0(acc, a, d, 1);
  if (U == 7) wg_rs144_0(acc, a, d, 1);
  if (U == 8) wg_rs128_0(acc, a, d, 1);
  if (U == 9) wg_rs112_0(acc, a, d, 1);
  if (U == 10) wg_rs96_0(acc, a, d, 1);
  if (U == 11) wg_rs80_0(acc, a, d, 1);
  if (U == 12) wg_rs64_0(acc, a, d, 1);
  if (U == 13) wg_rs48_0(acc, a, d, 1);
  if (U == 14) wg_rs32_0(acc, a, d, 1);
  if (U == 15) wg_rs16_0(acc, a, d, 1);
}
template <int U0, int U1> __device__ __forceinline__ void csteps(float* acc, const uint32_t* A, uint64_t db) {
  cstep<U0>(acc, A, db);
  if constexpr (U0 > U1) csteps<U0 - 1, U1>(acc, A, db);
}
template <int U0, int U1> __device__ __forceinline__ void cload(uint32_t* A, uint32_t fa) {
  asm volatile("{ld.shared.b32 %0, [%4+%5]; ld.shared.b32 %1, [%4+%5+128]; ld.shared.b32 %2, [%4+%5+16]; ld.shared.b32 %3, [%4+%5+144];}"
               : "=r"(A[4 * U0]), "=r"(A[4 * U0 + 1]), "=r"(A[4 * U0 + 2]), "=r"(A[4 * U0 + 3]) : "r"(fa), "n"(256 * U0) : "memory");
  if constexpr (U0 > U1) cload<U0 - 1, U1>(A, fa);
}

__device__ __forceinline__ uint2 c_load(const bf16* c) {
  REGION_IDS;
  return make_uint2(ldg32(c + 320 * (bid & 1) + 2 * i0), ldg32(c + 320 * (bid & 1) + 256 + 2 * lane));
}
__device__ __forceinline__ void silu_vector(uint2 c, uint32_t base) {
  REGION_IDS;
  sts32(base + OFF_CV + 4 * i0, pack_bf16(silu_f(bf_lo(c.x)), silu_f(bf_hi(c.x))));
  sts32(base + OFF_CV + 512 + 4 * lane, pack_bf16(silu_f(bf_lo(c.y)), silu_f(bf_hi(c.y))));
  fence_async_smem();
}

__device__ __forceinline__ void mod_poll(Scratch* G, uint32_t base, int c, int n, uint32_t epoch) {
  REGION_IDS;
  const int e = 4 * c + (lane & (4 * n - 1));
  uint2 m;
  int it = 0;
#pragma unroll 1
  do m = ld_relaxed64(&G->modc[bid][8 + e]); while (__any_sync(~0u, ((m.x ^ epoch) | (m.y ^ epoch)) & 1) && ++it < SPIN_LIMIT);
  sts32(base + OFF_MODR + 4 * e, __byte_perm(badd2(mod_sum(m), (lane & 1) * 0x3F800000u), 0, 0x3232));
  __syncwarp();
  if (elect()) { mbar_arrive(BAR(B_MODR + c)); if (n > 1) mbar_arrive(BAR(B_MODR + c + 1)); }
}
__device__ __forceinline__ void row_stats(Scratch* G, uint32_t base, uint32_t epoch) {
  REGION_IDS;
  mbar_wait_cluster(BAR(B_ST1));
  if (lane < 8) red_hint(G->hint[5][lane]);
  const uint2 x = lds64(base + OFF_ST + 8 * (lane & 15)), y = lds64(base + OFF_ST + 128 + 8 * (lane & 15));
  float m, sd;
  ln_final(__uint_as_float(x.x) + __uint_as_float(y.x), __uint_as_float(x.y) + __uint_as_float(y.y), m, sd);
  sd = rbf(rcpf(sd));
  const uint32_t mr = pack_bf16(sd, -rbf(m) * sd), tg = lane & 7 ? 0 : lane & 8 ? 1 : 0x8000;
  const uint32_t o = __byte_perm(__shfl_sync(~0u, mr, 2 * lane & 14), __shfl_sync(~0u, mr, (2 * lane & 14) + 1), (lane & 8) ? 0x7632 : 0x5410);
  if (lane < 16) st_relaxed32(&G->st1[lane >> 3][8 * bid + (lane & 7)], (o & ~tg) | ((epoch & 1) * tg));
  if (elect()) mbar_arrive(BAR(B_FIN));
}
template <int B, int NEXT> __device__ __forceinline__ void strip(Scratch* G, const CUtensorMap* map, uint32_t base, int c, uint32_t epoch, uint32_t& ph, uint32_t& pre, float4& s) {
  REGION_IDS;
  int h, j, r, it = 0;
  ffn_role(h, j, r);
  const uint32_t buf = base + OFF_SX + 4096 * B, a = buf + 32 * lane;
#pragma unroll 1
  while (__any_sync(~0u, pre != 64 * epoch) && ++it < SPIN_LIMIT) pre = ld_relaxed32(G->xsh[c][(r & 6) + (j >> 1)]);
#pragma unroll 1
  for (it = 0; it < SPIN_LIMIT; it++) {
    if (elect()) { mbar_expect_tx(BAR(B_SX + B), 4096); tma2d(buf, map, 128 * r + 64 * h, D_ * (epoch & 1) + 128 * c + 32 * j, BAR(B_SX + B)); }
    mbar_wait(BAR(B_SX + B), ph);
    ph ^= 1;
    if (__all_sync(~0u, min(min(lds32(a), lds32(a + 1024)), min(lds32(a + 2048), lds32(a + 3072))))) break;
  }
  pre = 0;
  if (c == NEXT - 1 || c == NEXT - 2) pre = ld_relaxed32(G->xsh[c + 1][(r & 6) + (j >> 1)]);
#pragma unroll 1
  for (uint32_t o = buf + 4 * lane; o < buf + 4096; o += 1024) {
    uint32_t x[8];
#pragma unroll
    for (int i = 0; i < 8; i++) x[i] = lds32(o + 128 * i);
#pragma unroll
    for (int i = 0; i < 8; i++) { const float lo = bf_lo(x[i]), hi = bf_hi(x[i]); s.x += lo; s.y = fmaf(lo, lo, s.y); s.z += hi; s.w = fmaf(hi, hi, s.w); }
  }
}
__device__ __forceinline__ void planes(uint32_t a, uint4& y) {
  uint4 z = lds128(a + 4096);
  y.x = badd2(y.x, z.x); y.y = badd2(y.y, z.y); y.z = badd2(y.z, z.z); y.w = badd2(y.w, z.w);
  z = lds128(a + 8192);
  const uint4 m = lds128(a + 12288);
  y.x = badd2(y.x, badd2(z.x, m.x)); y.y = badd2(y.y, badd2(z.y, m.y)); y.z = badd2(y.z, badd2(z.z, m.z)); y.w = badd2(y.w, badd2(z.w, m.w));
}
__device__ __forceinline__ void mr_poll(Scratch* G, uint32_t base, uint32_t epoch) {
  int it = 0;
#pragma unroll 1
  while (__any_sync(~0u, ld_relaxed32(G->hint[5][4 * (blockIdx.x >> 6) + (blockIdx.x >> 3 & 3)]) != epoch << 7) && ++it < SPIN_LIMIT);
  if (elect()) { mbar_expect_tx(BAR(B_MR), 8192); bulk_load(base + OFF_MR, G->st1, 8192, BAR(B_MR)); mbar_arrive(BAR(B_QTOK)); }
}

__global__ void __cluster_dims__(2, 1, 1) __launch_bounds__(512, 1) k_fused(const __grid_constant__ Ptrs P, const __grid_constant__ Maps maps) {
  Scratch* const G = P.g;
  extern __shared__ __align__(1024) uint8_t smem_raw[];
  const uint32_t t_start = clock();
  const uint32_t base = __shfl_sync(~0u, smem_u32(smem_raw), 0);
  uint32_t t_iss = 0;
  if (threadIdx.x < 32 && blockIdx.x < 128) {
    mbar_init<1>(BAR(0), 1);
    if (elect()) {
      const int c0 = 64 * (blockIdx.x & 1), c1 = 2 * (blockIdx.x & 126);
      mbar_expect_tx(BAR(B_KV), 12288);
      tma3d(base + tab(T_KV, 0), &maps.km, c0, c1, 0, BAR(B_KV));
      tma3d(base + tab(T_KV, 0) + KV_V, &maps.v, c0, c1, 0, BAR(B_KV));
      tma3d(base + tab(T_KV, 0) + KV_H, &maps.kh, c0, c1 - 1, 5, BAR(B_KV));
      tma3d(base + OFF_TAP, &maps.tap, 0, blockIdx.x & 1, 0, BAR(B_KV));
    }
    if (P.boff) mbar_wait(BAR(0));
  }
  if ((base & 0xFFFFFFu) != DB) __trap();
  const int wid = __shfl_sync(~0u, threadIdx.x >> 5, 0), wg = wid >> 2, w = wid & 3;
  if (blockIdx.x + P.boff >= 128) {
    REGION_IDS;
    constexpr int nu = 30;
    auto tile = [&](int n) { return 2 * n + (blockIdx.x >> 1 & 1); };
    auto fetch = [&](int n, int b) {
      if (elect()) {
        mbar_expect_tx(BAR(n), 40960);
#pragma unroll
        for (int k = 0; k < 5; k++) tma3d(base + 40960 * b + 8192 * k, &maps.wm, mod_col(tile(n)), 320 * (blockIdx.x & 1) + 64 * k, 0, BAR(n));
      }
    };
    if (P.boff) __syncthreads();
    if (wid == 12) {
      mbar_init<4>(BAR(0), 1);
#pragma unroll 1
      for (int n = 0; n < 4; n++) fetch(n, n);
      mbar_init<26>(BAR(4), 1);
      mbar_init<60>(BAR(32), 4);
    }
    const uint32_t par = ~ld_relaxed32(G->hint[7][0]) >> 7 & 1;
    silu_vector(c_load(P.c), base);
    __syncthreads();
    if (wid == 12) {
      wait_clock(t_start + P.th);
#pragma unroll 1
      for (int n = 4, b = 4; n < nu; n++) {
        if (n >= 5) mbar_wait(BAR(27 + n));
        fetch(n, b);
        b = b == 4 ? 0 : b + 1;
      }
    } else if (wg < 2) {
      uint32_t cv[40];
#pragma unroll
      for (int k = 0; k < 40; k++) cv[k] = lds32(base + OFF_CV + 16 * k + 4 * (lane & 3));
      const uint32_t a0 = base + 128 * ((lane & 7) + (lane >> 4) * 8) + (((2 * w + (lane >> 3 & 1)) ^ (lane & 7)) << 4);
#pragma unroll 1
      for (int n = wg; n < nu; n += 2) {
        float d[16] = {};
        mbar_wait(BAR(n));
#pragma unroll
        for (int k0 = 0; k0 < 20; k0 += 10) {
          uint32_t a[40];
#pragma unroll
          for (int k = 0; k < 10; k++) ldmatrix_x4_t(a + 4 * k, a0 + 40960 * (n % 5) + 2048 * (k0 + k));
#pragma unroll
          for (int k = 0; k < 10; k++)
            asm("mma.sync.aligned.m16n8k16.row.col.f32.bf16.bf16.f32 {%0,%1,%2,%3}, {%4,%5,%6,%7}, {%8,%9}, {%0,%1,%2,%3};"
                : "+f"(d[4 * (k & 3)]), "+f"(d[4 * (k & 3) + 1]), "+f"(d[4 * (k & 3) + 2]), "+f"(d[4 * (k & 3) + 3])
                : "r"(a[4 * k]), "r"(a[4 * k + 1]), "r"(a[4 * k + 2]), "r"(a[4 * k + 3]), "r"(cv[2 * (k0 + k)]), "r"(cv[2 * (k0 + k) + 1]));
        }
        arrive1(BAR(32 + n));
        if (!(lane & 3)) {
          sts32(base + 204800 + 256 * n + 64 * w + lane, __float_as_uint(d[0] + d[4] + (d[8] + d[12])));
          sts32(base + 204800 + 256 * n + 64 * w + lane + 32, __float_as_uint(d[2] + d[6] + (d[10] + d[14])));
        }
        arrive1(BAR(62 + n));
      }
    } else if (wg == 2) {
#pragma unroll 1
      for (int n = w; n < nu; n += 4) {
        const int t = tile(n), ch = mod_ch(t) + lane;
        uint32_t* q = (uint32_t*)(t < 40 ? &G->modc[ch & 127][8 + (t >> 1)] : &G->modv[t >= 50][ch]) + (bid & 1);
        mbar_wait(BAR(62 + n));
        const uint32_t x = (lds32(base + 204800 + 256 * n + 4 * lane) & ~1u) | par, y = (lds32(base + 204928 + 256 * n + 4 * lane) & ~1u) | par;
        publish(q, x);
        publish(q + (t < 40 ? 2048 : 64), y);
        if (t < 40 && (t & 6) == 6) {
          q = (uint32_t*)&G->modv[2][ch] + (bid & 1);
          publish(q, x);
          publish(q + 64, y);
        }
      }
    }
    return;
  }
  if (wid < 15) mbar_init<4>(BAR(4 * wid + (wid == 0)), wid < 8 ? 1 : 4);
  asm volatile("fence.mbarrier_init.release.cluster; bar.sync 0, 512;" ::: "memory");
  asm volatile("barrier.cluster.arrive.relaxed.aligned;" ::: "memory");
  if (wid == 4) {
    const int c0 = 64 * (blockIdx.x & 1), c1 = 2 * (blockIdx.x & 126);
    wait_clock(t_start + P.te);
    if (elect()) { tma3d(base + tab(T_KV, 1), &maps.km, 128 + c0, c1, 0, BAR(B_KV + 1)); tma3d(base + tab(T_KV, 1) + KV_H, &maps.kh, 128 + c0, c1 - 1, 5, BAR(B_KV + 1)); }
    wait_clock(t_start + P.te + P.pe);
    if (elect()) tma3d(base + tab(T_KV, 1) + KV_V, &maps.v, 128 + c0, c1, 0, BAR(B_KV + 1));
    wait_clock(t_start + P.te + 2 * P.pe);
    if (elect()) bulk_load(base + tab(T_F, 0) + F_E, P.ssmk + blockIdx.x * S_, 4096, BAR(B_FRAW));
    wait_clock(t_start + P.te + 3 * P.pe);
    if (elect()) tma3d(base + OFF_Q, &maps.q, c0, c1, 0, BAR(B_Q));
  }
#define LAUNCHES const uint32_t launches = ld_relaxed32(G->hint[7][blockIdx.x >> 4])
#define EPOCH ((__shfl_sync(~0u, launches, 0) >> 7) + 1)
  if (wg == 3) {
    asm volatile("setmaxnreg.dec.sync.aligned.u32 24;");
    if (w == 1) {
      {
        LAUNCHES;
        REGION_IDS;
        const int c1 = 2 * (bid & 126);
#pragma unroll 1
        for (int e = 4; e < NE; e++) {
          const uint2 x = P.sched[e];
          const uint32_t kind = x.x >> 16 & 15, ch = x.x >> 13 & 0x380, dst = base + (x.y & 0x3FFFF), b = BAR(x.y >> 18);
          wait_clock(t_start + (x.x & 0xFFFF));
          if (kind < 3 && elect()) tma3d(dst, &maps.km + kind, ch + 64 * (bid & 1), c1, 0, b);
          if (kind == 0 && elect()) tma3d(dst + KV_H, &maps.kh, ch + 64 * (bid & 1), c1 - 1, 5, b);
          if (kind == 3 && elect()) bulk_load(dst, P.ssmk + (ch + bid) * S_, 4096, b);
        }
        if (P.mr2 == 2) mr_poll(G, base, EPOCH);
      }
      cluster_wait();
      int h, j, r;
      ffn_role(h, j, r);
      mbar_wait(BAR(B_QTD));
      mbar_wait(BAR(B_FL));
#pragma unroll 1
      for (int u = 0; u < 20; u++) {
        const uint32_t x = P.wdep[u], s = base + (x & ~8191u);
        if (u < 5) wait_clock(t_start + P.wt[u]);
        mbar_wait(BAR(opaque(x & 255)));
        if (elect()) {
          mbar_expect_tx(BAR(B_FULL + u), WSLOT + 4 * (x & 4096));
#pragma unroll
          for (int k = 0; k < 6; k++) tma3d(s + 4096 * w_block(k & 1, k >> 1), &maps.w1s + (k & 1), 0, 32 * u, 3 * (4 * h + j) + (k >> 1), BAR(B_FULL + u));
        }
      }
#pragma unroll 1
      for (int v = 0; v < 12; v++) {
        const int q = v * 11 >> 5, e = v - 3 * q, k32 = 24 * h + (q ? 6 * fslice(j, e) + 2 * q - 2 : 6 * j + 2 * e);
        const uint2 x = P.w2t[v];
        mbar_wait(BAR(x.y));
        if (elect()) {
          mbar_expect_tx(BAR(B_FULL + 20 + v), q ? WSLOT + 2 * ASLOT : WSLOT);
#pragma unroll
          for (int k = 0; k < 3; k++) tma5d(base - DB + 16 * ((x.x & 0xFFFF) + k * (x.x >> 16)), &maps.w2a + (q > 0), k < 2 ? 128 * j + 64 * k : 512 + 32 * (j & 2), k32, BAR(B_FULL + 20 + v));
        }
      }
    } else if (w == 0) {
      LAUNCHES;
      uint32_t epoch;
      {
        REGION_IDS;
        const unsigned* hp = G->hint[0][4 * (bid >> 6) + (bid >> 3 & 3)];
        uint32_t v = ld_relaxed32(hp + 256 * min(lane, 5));
        if (lane < 3) sts128(base + tab(T_X, lane) + 4096, 0, 0, 0, 0);
        if (lane && lane < B_Q + 5) mbar_expect_tx(BAR(lane), lane < B_FRAW ? 9728 : 4096);
        epoch = EPOCH;
        fence_async_smem();
        const uint32_t rdy = __ballot_sync(~0u, v == epoch << 6);
        uint32_t nx = 0, nm = 0;
#pragma unroll 1
        for (uint32_t seq = P.seq; seq; seq >>= 2) {
          int it = 0;
          if (seq & 1) {
            if (!(seq & 2)) mod_poll(G, base, nm, 1 + (seq == 13), epoch);
            nm++;
          } else if (seq & 2) {
            mr_poll(G, base, epoch);
          } else {
            if (!(rdy >> nx & 1)) {
#pragma unroll 1
              while (__any_sync(~0u, ld_relaxed32(hp + 256 * nx) != epoch << 6) && ++it < SPIN_LIMIT);
            }
            wait_clock(clock() + P.xd);
            if (nx >= 3) mbar_wait(BAR(B_PFULL - 3 + nx));
            if (elect()) { mbar_expect_tx(BAR(B_XR + nx), 4096); bulk_load(base + tab(T_X, nx), G->xr + (128 * nx + bid) * 256, 4096, BAR(B_XR + nx)); }
            nx++;
          }
        }
      }
      REGION_IDS;
      int h, j, r;
      ffn_role(h, j, r);
      mbar_wait(BAR(B_PFULL + 3));
      {
        float4 s = {};
        uint32_t ph = 0, pre = 0;
#pragma unroll 1
        for (int c = 2; c < 4; c++) strip<1, 3>(G, &maps.x1s, base, c, epoch, ph, pre, s);
        __syncwarp();
        sts128(base + OFF_SX + 4096 + 16 * lane, __float_as_uint(s.x), __float_as_uint(s.y), __float_as_uint(s.z), __float_as_uint(s.w));
        arrive1(BAR(B_S3));
      }
      ffn_role(h, j, r);
      cluster_wait();
      mbar_wait(BAR(B_UVD));
      asm volatile("fence.acq_rel.gpu;" ::: "memory");
      if (lane < 8) red_hint(G->hint[7][lane]);
      unsigned x;
      int it = 0;
#pragma unroll 1
      do { asm volatile("ld.acquire.gpu.global.u32 %0, [%1];" : "=r"(x) : "l"(G->hint[7][bid >> 4]) : "memory"); } while (__any_sync(~0u, x != 128 * epoch) && ++it < SPIN_LIMIT);
      fence_async_all();
      const int ch = D_ * (epoch & 1);
      mbar_wait(BAR(B_EXT));
      mbar_wait(BAR(B_EMPTY + 18));
      if (elect()) {
        mbar_expect_tx(BAR(B_FULL + 32), 20480);
#pragma unroll
        for (int k = 0; k < 4; k++) tma2d(base + (k < 3 ? OFF_X1 + k * WSLOT : OFF_SX), &maps.x1b, 128 * r + 64 * h, ch + 128 * j + 32 * (k ^ (j & 1)), BAR(B_FULL + 32));
        tma2d(base + OFF_SX + 4096, &maps.x1b, 128 * r + 64 * h, ch + 512 + 32 * j, BAR(B_FULL + 32));
        mbar_expect_tx(BAR(B_FULL), 8192); mbar_expect_tx(BAR(B_FULL + 1), 8192); mbar_expect_tx(BAR(B_FULL + 2), 4096);
      }
      mbar_wait(BAR(B_EMPTY + 27));
      if (elect()) mbar_arrive_remote(mapa(BAR(B_XFREE), h ^ 1));
    } else {
      LAUNCHES;
      uint32_t epoch;
      {
        REGION_IDS;
        uint32_t dv;
        asm volatile("ld.global.nc.u16 %0, [%1];" : "=r"(dv) : "l"(P.ssmd + 128 * (lane & 7) % D_ + bid));
        if (lane < 5) sts128(base + tab(T_F, lane) + (w & 1) * (F_O - 16), 0, 0, 0, 0);
        epoch = EPOCH;
        __syncwarp();
#pragma unroll 1
        for (int c = 0; c < 5; c++) {
          const float d = i0 == 64 ? bf_lo(dv) : 0.f;
          dv = __shfl_down_sync(~0u, dv, 1);
          const uint32_t a = base + tab(T_F, c) + 16 * (i0 - 64);
          mbar_wait(BAR(B_FRAW + c));
#pragma unroll
          for (int k = 0; k < 4; k++) {
            uint4 x = lds128(a + F_E + 1024 * k);
            const uint32_t pv = lds32(a + F_E - 4 + 1024 * k);
            if (k == 0) { x.x = pack_bf16(bf_lo(x.x) + d, bf_hi(x.x)); sts32(a + F_E, x.x); }
            sts128(a + F_O + 1024 * k, __byte_perm(pv, x.x, 0x5432), __byte_perm(x.x, x.y, 0x5432), __byte_perm(x.y, x.z, 0x5432), __byte_perm(x.z, x.w, 0x5432));
          }
          __syncwarp();
          if (elect()) mbar_arrive2(BAR(B_FRDY + c));
          if (c == 0 && w == P.fin) row_stats(G, base, epoch);
        }
      }
      REGION_IDS;
      int h, j, r;
      ffn_role(h, j, r);
      cluster_wait();
      if (w == 2) {
        uint32_t rdy = 0, s = 0;
        mbar_wait(BAR(B_QTD));
        mbar_wait(BAR(B_FL + 2));
#pragma unroll 1
        for (int n = 0; n < 10; n++) {
          if (n == P.cn) {
            mbar_wait(BAR(B_PEMPTY + 3));
            if (elect()) {
              tma3d(base + OFF_UV, &maps.w1 + (r & 1), 0, 40 * (r & 14), 3 * (4 * h + j), BAR(B_UVB));
              tma3d(base + OFF_UV + 12288, &maps.w1 + (r & 1), 0, 40 * (r & 14) + 32, 3 * (4 * h + j), BAR(B_UVB));
            }
            {
              const uint2* mp = &G->modv[lane & 4 ? 0 : 2][40 * (r & 14) + (lane & 24) + 2 * (lane & 3)];
              uint4 v[3];
              int it = 0;
#pragma unroll 1
              do {
                v[0] = ld_relaxed128(mp); v[1] = ld_relaxed128(mp + 32); v[2] = ld_relaxed128(mp + 64 - (lane & 16));
              } while (__any_sync(~0u, ((v[0].x ^ epoch) | (v[0].y ^ epoch) | (v[0].z ^ epoch) | (v[0].w ^ epoch) | (v[1].x ^ epoch) | (v[1].y ^ epoch) | (v[1].z ^ epoch) | (v[1].w ^ epoch) |
                                        (v[2].x ^ epoch) | (v[2].y ^ epoch) | (v[2].z ^ epoch) | (v[2].w ^ epoch)) & 1) && ++it < SPIN_LIMIT);
#pragma unroll
              for (int i = 0; i < 3; i++)
                sts32(base + OFF_CO + 128 * i + 4 * lane, badd2(pack_bf16(__uint_as_float(v[i].x) + __uint_as_float(v[i].y), __uint_as_float(v[i].z) + __uint_as_float(v[i].w)), lane & 4 ? 0 : 0x3F803F80u));
            }
            fence_async_smem();
            __syncwarp();
            if (elect()) mbar_expect_tx(BAR(B_UVB), WSLOT);
          }
          mbar_wait(BAR(n < 2 ? B_FL + 3 + n : n == 2 ? B_PFULL + 4 : B_EMPTY + 2 * n - 5));
#pragma unroll 1
          for (int it = 0; !(rdy >> n & 1) && it < SPIN_LIMIT; it++) rdy = __ballot_sync(~0u, ld_relaxed32(G->xsh[min(lane >> 1, n ? 4 : P.aw)][(r & 6) + (lane & 1)]) == 64 * epoch) & (n ? ~0u : (4u << 2 * P.aw) - 1);
          if (elect()) {
            tma2d(base + OFF_A + s, &maps.xs, 128 * r + 64 * h, 64 * n, BAR(B_FULL + 2 * n));
            tma2d(base + OFF_A + ARING + s, &maps.xs, 128 * r + 64 - 64 * h, 64 * n, BAR(B_FULL + 2 * n));
          }
          s = s == 2 * ASLOT ? 0 : s + ASLOT;
        }
      } else {
        if (P.m3 < 5) mod_poll(G, base, P.m3, 1, epoch);
        float4 s = {};
        uint32_t ph = 0, pre = 0;
        mbar_wait(BAR(B_FL + 2));
        mbar_wait(BAR(B_PFULL + 3));
#pragma unroll 1
        for (int c = 0; c < 5; c = c == 1 ? 4 : c + 1) {
          if (c == 4) {
            ffn_role(h, j, r);
            mbar_wait(BAR(B_PEMPTY + 4));
            if (elect()) {
              mbar_expect_tx(BAR(B_UVE), 6144);
              tma3d(base + OFF_UVE, &maps.w1e + (r & 1), 0, 40 * (r & 14) + 64, 3 * (4 * h + j), BAR(B_UVE));
            }
          }
          strip<0, 1>(G, &maps.x1s, base, c, epoch, ph, pre, s);
        }
        mbar_wait(BAR(B_S3));
        const uint4 y = lds128(base + OFF_SX + 4096 + 16 * lane);
        const float s0 = s.x + __uint_as_float(y.x), q0 = s.y + __uint_as_float(y.y), s1 = s.z + __uint_as_float(y.z), q1 = s.w + __uint_as_float(y.w);
        ffn_role(h, j, r);
        asm volatile("{.reg .b128 t, x; .reg .b64 a, b; mov.b64 a, {%1,%2}; mov.b64 b, {%3,%4}; mov.b128 x, {a,b}; atom.relaxed.gpu.global.exch.b128 t, [%0], x;}"
                     ::"l"(&G->st2[2 * r + h][j][4 * lane]), "r"((__float_as_uint(s0) & ~1u) | (epoch & 1)), "f"(q0), "r"((__float_as_uint(s1) & ~1u) | (epoch & 1)), "f"(q1) : "memory");
        uint4* z = G->x1[~epoch & 1] + 1280 * bid + lane;
#pragma unroll 1
        for (int k = 0; k < 40; k++) st_relaxed128(z + 32 * k, 0, 0, 0, 0);
      }
    }
  } else if (wg == 2) {
    asm volatile("setmaxnreg.dec.sync.aligned.u32 40;");
    mbar_init<12>(BAR(B_FULL + 12 * w), 1);
    mbar_init<9>(BAR(B_EMPTY - 1 + 9 * w), 8);
    asm volatile("fence.mbarrier_init.release.cluster;" ::: "memory");
    LAUNCHES;
    const uint32_t epoch = EPOCH;
    cluster_wait();
#pragma unroll 1
    for (uint64_t prog = P.prog; prog; prog >>= 4) {
      REGION_IDS;
      const int s = (prog & 7) - 1;
      if (!(prog & 8)) {
        const uint32_t a = base + tab(T_KV, s) + 128 * (lane & 3) + ((w ^ (lane & 3)) << 4) + 4 * (lane & 16) + (lane & 12), keep = ~(lane & 1), bit = epoch & lane & 1;
        uint4* dst = G->xr + (128 * s + 64 * (bid & 1) + 8 * w + 2 * (lane & 16) + (lane >> 1 & 6)) * 256 + 255 - 4 * (bid >> 1) - (lane & 3);
        mbar_wait(BAR(B_KV));
        mbar_wait(BAR(B_KV + s));
        const uint4 wv = lds128(base + OFF_TAP + 512 * s + 64 * w + 16 * (lane & 16) + 4 * (lane & 12));
        uint32_t kk[11], r[8];
#pragma unroll
        for (int k = 0; k < 11; k++) kk[k] = k < 3 ? lds32((a ^ (64 * (k & 1))) + KV_H + 512 * k) : lds32((a ^ (64 * (~k & 1))) + 512 * (k - 3));
        if (elect()) red_hint(G->hint[s][4 * (bid & 1) + w]);
#pragma unroll
        for (int k = 0; k < 8; k++) r[k] = lds32((a ^ (64 * (k & 1))) + KV_V + 512 * k);
        const uint32_t w0 = __byte_perm(wv.x, wv.z, 0x5410), w1 = __byte_perm(wv.x, wv.z, 0x7632),
                       w2 = __byte_perm(wv.y, wv.w, 0x5410), w3 = __byte_perm(wv.y, wv.w, 0x7632);
#pragma unroll
        for (int k = 0; k < 8; k++) r[k] = bmul2(bfma2(kk[k + 3], w0, bfma2(kk[k + 2], w1, bfma2(kk[k + 1], w2, bmul2(kk[k], w3)))), r[k]);
        st_relaxed128(dst, (__byte_perm(r[7], r[6], 0x5410) & keep) | bit, __byte_perm(r[5], r[4], 0x5410), __byte_perm(r[3], r[2], 0x5410), __byte_perm(r[1], r[0], 0x5410));
        st_relaxed128(dst + 256, (__byte_perm(r[7], r[6], 0x7632) & keep) | bit, __byte_perm(r[5], r[4], 0x7632), __byte_perm(r[3], r[2], 0x7632), __byte_perm(r[1], r[0], 0x7632));
      } else if (s == 5) {
        mbar_wait(BAR(B_PFULL));
#pragma unroll
        for (int hf = 0; hf < 2; hf++) {
          const uint32_t a = base + tab(T_P, 0) + 16 * i0 + 2048 * hf;
          uint4 y = lds128(a);
          planes(a, y);
          sts128(a, y.x, y.y, y.z, y.w);
        }
      } else if (s >= 0) {
        const int tr = 4 * (lane & 1) + (lane >> 1 & 3);
        const uint32_t a = base + OFF_Q + 4096 * s + 128 * ((lane & 24) + tr) + ((w ^ tr) << 4);
        uint4* dst = G->qt + (128 * s + 64 * (bid & 1) + 8 * w + (lane >> 2)) * 256 + 4 * (bid >> 1) + (lane & 3);
        mbar_wait(BAR(B_Q + s));
#pragma unroll
        for (int k = 0; k < 2; k++) {
          uint32_t x[4];
          ldmatrix_x4_t(x, a ^ (64 * k));
          st_relaxed128(dst + 8192 * k, set_tag(x[0], ~lane & 1, epoch), x[1], x[2], x[3]);
        }
      } else if (w == 3) {
        row_stats(G, base, epoch);
      }
    }
    arrive1(BAR(B_QTD));
    {
      REGION_IDS;
      const uint32_t tag = opaque(~lane & 1);
      const uint32_t io = 16 * i0;
      uint4* gp = (uint4*)((char*)(G->xs + 256 * blockIdx.x) + io);
      constexpr int QO = -D_ * 256;
      const uint32_t sa = base + io;
      uint4 q[2];
      if (w == 0 && P.mr2 == 1) mr_poll(G, base, epoch);
      mbar_wait(BAR(B_QTOK));
      q[0] = ld_relaxed128(gp + QO);
      q[1] = ld_relaxed128(gp + QO + 128);
#pragma unroll 1
      for (int it = 0; it < SPIN_LIMIT; it++) {
        mbar_wait(BAR(B_MR), it & 1);
        const uint32_t x = lds32(sa + 16 * i0 + OFF_MR), y = lds32(sa + 16 * i0 + OFF_MR + 4096);
        sts32(sa + 16 * i0 + OFF_MR, x & 0xFFFF7FFFu);
        if (bar_all(3, !(((x >> 15 ^ epoch) | (y ^ epoch)) & 1))) break;
        if (w == 0 && elect()) { fence_async_smem(); mbar_expect_tx(BAR(B_MR), 8192); bulk_load(base + OFF_MR, G->st1, 8192, BAR(B_MR)); }
      }
#pragma unroll 1
      for (int c = 0; c < 5; c++) {
        mbar_wait(BAR(B_MODR + c));
        uint4 co = lds128(base + OFF_MODR + 16 * c);
        co.x = bmul2(co.x, co.z); co.y = bmul2(co.y, co.z);
        mbar_wait(BAR(B_PFULL + c));
        const uint32_t pb = io + (base + tab(T_P, c));
        gp = (uint4*)((char*)(G->xs + 256 * blockIdx.x + 32768 * c) + io);
#pragma unroll
        for (int hf = 0; hf < 2; hf++) {
#pragma unroll 1
          for (int it = 0; __any_sync(~0u, set_tag(q[hf].x, tag, epoch) != q[hf].x) && it < SPIN_LIMIT; it++) {
            q[hf] = ld_relaxed128(gp + QO + 128 * hf);
          }
          uint4 y = lds128(pb + 2048 * hf);
          if (c) planes(pb + 2048 * hf, y);
          const uint4 z = lds128(sa + OFF_MR + 2048 * hf), m = lds128(sa + OFF_MR + 2048 * hf + 4096);
          y.x = bfma2(bfma2(bfma2(q[hf].x, z.x, m.x), co.y, co.x), y.x, q[hf].x);
          if (hf) {
            __syncwarp();
            asm volatile("{.reg .pred p; elect.sync _|p, 0xffffffff; @p red.relaxed.gpu.global.add.u32 [%0], 1; @p mbarrier.arrive.shared::cta.b64 _, [%1];}"
                         ::"l"(G->xsh[c][2 * w + (blockIdx.x >> 6)]), "r"(BAR(B_PEMPTY + c)), "r"(y.x) : "memory");
          }
          y.y = bfma2(bfma2(bfma2(q[hf].y, z.y, m.y), co.y, co.x), y.y, q[hf].y);
          y.z = bfma2(bfma2(bfma2(q[hf].z, z.z, m.z), co.y, co.x), y.z, q[hf].z);
          y.w = bfma2(bfma2(bfma2(q[hf].w, z.w, m.w), co.y, co.x), y.w, q[hf].w);
          st_relaxed128(gp + 128 * hf, set_tag(bmul2(y.x, co.w), tag, epoch), bmul2(y.y, co.w), bmul2(y.z, co.w), bmul2(y.w, co.w));
          asm volatile("{.reg .pred p; .reg .b32 t; setp.ne.u32 p, %5, 0; max.u32 t, %1, 1; @!p st.relaxed.gpu.global.v4.u32 [%0+%6], {t,%2,%3,%4}; @p st.relaxed.gpu.global.v4.u32 [%0+%7], {t,%2,%3,%4};}"
                       ::"l"(gp + 128 * hf), "r"(y.x), "r"(y.y), "r"(y.z), "r"(y.w), "r"(epoch & 1), "n"(D_ * 4096), "n"(D_ * 8192) : "memory");
          if (c < 4) q[hf] = ld_relaxed128(gp + QO + 32768 + 128 * hf);
        }
      }
    }
    int h, j, r;
    ffn_role(h, j, r);
    {
      REGION_IDS;
      mbar_wait(BAR(B_UVB));
      float d[12] = {};
      fence_regs(d);
      wg_fence();
#pragma unroll
      for (int k = 0; k < 15; k++) {
        if (k == 12) { wg_commit(); mbar_wait(BAR(B_UVE)); wg_fence(); }
        wg_ss8_10(d + 4 * (k % 3), mkdesc(DB + (k < 12 ? OFF_UV + 12288 * (k / 6) + 4096 * (k % 3) + 2048 * (k / 3 & 1) : OFF_UVE + 2048 * (k % 3)), 16, 1024, 1),
                  mkdesc(DB + OFF_CO + 64 * (k / 3), 32, 128, 0), 1);
      }
      wg_commit();
      const int row = (r & 14) + (lane >> 2 & 1);
      uint32_t* dst = &G->uv[4 * h + j][32 * row + 4 * ((2 * w ^ row) & 6) + (lane & 3)];
      const uint32_t tag = !(lane & 3);
      wg_wait<0>();
      fence_regs(d);
      if (elect()) { red_hint(G->hint[8][4 * h + j]); mbar_arrive(BAR(B_UVD)); }
      uint32_t x[6];
#pragma unroll
      for (int k = 0; k < 6; k++) asm volatile("movmatrix.sync.aligned.m8n8.trans.b16 %0, %1;" : "=r"(x[k]) : "r"(pack_bf16(d[2 * k], d[2 * k + 1])));
      if (lane < 8) {
#pragma unroll
        for (int k = 0; k < 6; k++) st_relaxed32(dst + 512 * w_block(r & 1, k >> 1) + ((4 * k ^ lane) & 4), set_tag(x[k], tag, epoch));
      }
    }
    {
      REGION_IDS;
      if (w == 0) {
        int it = 0;
#pragma unroll 1
        while (__any_sync(~0u, ld_relaxed32(G->hint[8][4 * h + j]) != 64 * epoch) && ++it < SPIN_LIMIT);
        if (elect()) { mbar_expect_tx(BAR(B_BX), 12288); bulk_load(base + OFF_BX, G->uv[4 * h + j], 12288, BAR(B_BX)); }
      }
      const uint32_t* sp = &G->st2[2 * r + (h ^ (w >> 1))][0][2 * (i0 & 63)];
      uint2 x[4];
      int it = 0;
#pragma unroll 1
      do {
#pragma unroll
        for (int k = 0; k < 4; k++) x[k] = ld_relaxed64(sp + 128 * k);
      } while (__any_sync(~0u, ((x[0].x ^ epoch) | (x[1].x ^ epoch) | (x[2].x ^ epoch) | (x[3].x ^ epoch)) & 1) && ++it < SPIN_LIMIT);
      float m, sd;
      ln_final((__uint_as_float(x[0].x) + __uint_as_float(x[1].x)) + (__uint_as_float(x[2].x) + __uint_as_float(x[3].x)),
               (__uint_as_float(x[0].y) + __uint_as_float(x[1].y)) + (__uint_as_float(x[2].y) + __uint_as_float(x[3].y)), m, sd);
      const uint32_t e = pack_bf16(-m, sd);
      sts128(base + OFF_AX + 16 * i0, e, e, e, e);
      sts32(base + OFF_RT + 4 * i0, __float_as_uint(rcpf(sd)));
      fence_async_smem();
#pragma unroll 1
      for (it = 0; it < SPIN_LIMIT; it++) {
        mbar_wait(BAR(B_BX), it & 1);
        uint32_t y = 0;
#pragma unroll
        for (int k = 0; k < 6; k++) y |= lds32(base + OFF_BX + 16 * i0 + 2048 * k) ^ epoch;
        if (bar_all(3, !(y & 1))) break;
        if (w == 0 && elect()) { mbar_expect_tx(BAR(B_BX), 12288); bulk_load(base + OFF_BX, G->uv[4 * h + j], 12288, BAR(B_BX)); }
      }
      arrive1(BAR(B_EXT));
      {
        uint2 g0, g1;
        int it = 0;
#pragma unroll 1
        do {
          g0 = ld_relaxed64(&G->modv[1][128 * j + i0]);
          g1 = ld_relaxed64(&G->modv[1][512 + 32 * j + lane]);
        } while (__any_sync(~0u, ((g0.x ^ epoch) | (g0.y ^ epoch) | (g1.x ^ epoch) | (g1.y ^ epoch)) & 1) && ++it < SPIN_LIMIT);
        const uint32_t ga = base + OFF_GB + 80 * (lane >> 1 & 3) + 2 * (lane & 1) + (lane >> 3) * 4;
        asm volatile("st.shared.u16 [%0], %1;" ::"r"(ga + 16 * (w ^ (j & 1))), "h"((uint16_t)(mod_sum(g0) >> 16)) : "memory");
        asm volatile("st.shared.u16 [%0], %1;" ::"r"(ga + 64), "h"((uint16_t)(mod_sum(g1) >> 16)) : "memory");
        arrive1(BAR(B_GB));
      }
      const int id = 16 * r + 4 * h + fslice(j, w);
      const unsigned* fp = &G->hhf[8 * id + 64 * (lane & 1)];
#pragma unroll 1
      for (int q = w == 3 ? 3 : 0; q < 3; q++) {
        const int m = 3 * q + w;
        const uint4* src = G->hh + id * 1536 + 512 * q;
        it = 0;
#pragma unroll 1
        while (__any_sync(~0u, ld_relaxed32(fp + q) != 4 * epoch) && ++it < SPIN_LIMIT);
        mbar_wait(BAR(P.hid[2][m]));
        if (elect()) {
          bulk_load(base + OFF_A + h * ARING + P.hid[h][m], src, ASLOT, BAR(B_FULL + 23 + m));
          bulk_load(base + OFF_A + ARING - h * ARING + P.hid[h ^ 1][m], src + 8 * 1536, ASLOT, BAR(B_FULL + 23 + m));
        }
      }
    }
  } else {
    asm volatile("setmaxnreg.inc.sync.aligned.u32 224;");
    LAUNCHES;
    uint32_t par = EPOCH & 1;
    cluster_wait();
    uint32_t ck = 0;
    {
      float acc[128];
      uint32_t A[64];
#pragma unroll
      for (int i = 0; i < 64; i++) A[i] = 0;
      int c = wg;
#pragma unroll 1
      for (uint64_t prog = P.cprog[wg]; prog; prog >>= 8) {
        REGION_IDS;
        const int s = prog & 7;
        if (s < 5) {
          const uint32_t a = base + tab(T_KV, s) + 128 * (lane & 3) + ((w ^ (lane & 3)) << 4) + 4 * (lane & 16) + (lane & 12), keep = ~(lane & 1), bit = par & lane;
          uint4* dst = G->xr + (128 * s + 64 * (bid & 1) + 8 * w + 2 * (lane & 16) + (lane >> 1 & 6)) * 256 + 255 - 4 * (bid >> 1) - (lane & 3);
          mbar_wait(BAR(B_KV));
          mbar_wait(BAR(B_KV + s));
          const uint4 wv = lds128(base + OFF_TAP + 512 * s + 64 * w + 16 * (lane & 16) + 4 * (lane & 12));
          uint32_t kk[11], r[8];
#pragma unroll
          for (int k = 0; k < 11; k++) kk[k] = k < 3 ? lds32((a ^ (64 * (k & 1))) + KV_H + 512 * k) : lds32((a ^ (64 * (~k & 1))) + 512 * (k - 3));
          if (elect()) red_hint(G->hint[s][4 * (bid & 1) + w]);
#pragma unroll
          for (int k = 0; k < 8; k++) r[k] = lds32((a ^ (64 * (k & 1))) + KV_V + 512 * k);
          const uint32_t w0 = __byte_perm(wv.x, wv.z, 0x5410), w1 = __byte_perm(wv.x, wv.z, 0x7632),
                         w2 = __byte_perm(wv.y, wv.w, 0x5410), w3 = __byte_perm(wv.y, wv.w, 0x7632);
#pragma unroll
          for (int k = 0; k < 8; k++) r[k] = bmul2(bfma2(kk[k + 3], w0, bfma2(kk[k + 2], w1, bfma2(kk[k + 1], w2, bmul2(kk[k], w3)))), r[k]);
          st_relaxed128(dst, (__byte_perm(r[7], r[6], 0x5410) & keep) | bit, __byte_perm(r[5], r[4], 0x5410), __byte_perm(r[3], r[2], 0x5410), __byte_perm(r[1], r[0], 0x5410));
          st_relaxed128(dst + 256, (__byte_perm(r[7], r[6], 0x7632) & keep) | bit, __byte_perm(r[5], r[4], 0x7632), __byte_perm(r[3], r[2], 0x7632), __byte_perm(r[1], r[0], 0x7632));
        }
        if (prog & 8) {
          float s0 = 0.f, s1 = 0.f, q0 = 0.f, q1 = 0.f;
          const uint32_t a = OFF_Q + 1024 * w + 128 * (lane & 7) + (((lane >> 3) ^ (lane & 7)) << 4);
          const uint32_t ra = mapa(base + OFF_ST + 128 * (bid & 1) + 64 * (lane & 1) + 16 * w + 8 * (lane >> 2), lane >> 1 & 1), rb = mapa(BAR(B_ST1), lane >> 1 & 1);
          if (w == 3 && elect()) mbar_expect_tx(BAR(B_ST1), 256);
#pragma unroll 1
          for (int k = 0; k < 5; k++) {
            mbar_wait(BAR(B_Q + k));
            const uint32_t o = opaque(base + 4096 * k);
            const uint4 x = lds128(o + a), y = lds128(o + (a ^ 64));
            const uint32_t e[8] = {x.x, x.y, x.z, x.w, y.x, y.y, y.z, y.w};
#pragma unroll
            for (int i = 0; i < 8; i++) { const float lo = bf_lo(e[i]), hi = bf_hi(e[i]); s0 += lo; s1 += hi; q0 = fmaf(lo, lo, q0); q1 = fmaf(hi, hi, q1); }
          }
          s0 += s1; q0 += q1;
          s0 += __shfl_xor_sync(~0u, s0, 8); q0 += __shfl_xor_sync(~0u, q0, 8);
          s0 += __shfl_xor_sync(~0u, s0, 16); q0 += __shfl_xor_sync(~0u, q0, 16);
          if (lane < 8) asm volatile("st.async.shared::cluster.mbarrier::complete_tx::bytes.v2.b32 [%0], {%1,%2}, [%3];" ::"r"(ra), "r"(__float_as_uint(s0)), "r"(__float_as_uint(q0)), "r"(rb) : "memory");
        }
        if (prog & 32) {
          const int L = 16 * w + (lane >> 2) + 2 * (lane & 3) - 7;
          const uint32_t fo = base + ((L & 1) ? F_O + 2 * (L + 1) : F_E + 2 * L);
          mbar_wait(BAR(B_FRDY + c));
          cload<0, 0>(A, fo + tab(T_F, c));
          cload<15, 1>(A, fo + tab(T_F, c));
          arrive1(BAR(B_FL + c));
        }
        if (!(prog & 64)) continue;
        uint32_t xo;
        if (P.turn >> c & 1) mbar_wait(BAR(B_TURN - 3 + c));
        if (c == 0) mbar_wait(BAR(P.c0));
#pragma unroll 1
        for (int it = 0; it < SPIN_LIMIT; it++) {
          xo = tab(T_X, opaque(c));
          mbar_wait(BAR(B_XR + c), it & 1);
          const uint32_t tag = lds32(base + xo + 32 * i0);
          wg_fence();
          csteps<0, 0>(acc, A, mkdesc(DB + xo, 16, 128, 0));
          csteps<15, 6>(acc, A, mkdesc(DB + xo, 16, 128, 0));
          wg_commit();
          if (bar_all(1 + wg, !((tag ^ par) & 1))) break;
          wg_wait<0>();
          if (w == 0 && elect()) { mbar_expect_tx(BAR(B_XR + c), 4096); bulk_load(base + xo, G->xr + (128 * c + bid) * 256, 4096, BAR(B_XR + c)); }
        }
        wg_fence();
        csteps<5, 1>(acc, A, mkdesc(DB + tab(T_X, opaque(c)), 16, 128, 0));
        wg_commit();
        if (c >= 2 && c < 4 && elect()) mbar_arrive(BAR(B_TURN - 2 + c));
        if (c >= 3) mbar_wait(BAR(B_PEMPTY + c - 3));
        wg_wait<0>();
        fence_regs(acc);
        ck = base + OFF_A + wg * ARING + lane * 128 + (((2 * w) ^ (lane & 7)) << 4);
        const uint32_t pb = base + tab(T_P, c) + 4096 * w;
#pragma unroll
        for (int k = 0; k < 8; k++) {
          uint32_t p[4];
#pragma unroll
          for (int e = 0; e < 4; e++) { const int i = 4 * k + e; p[e] = i < 31 ? pack_bf16(acc[4 * i] + acc[4 * i + 6], acc[4 * i + 1] + acc[4 * i + 7]) : pack_bf16(acc[124], acc[125]); }
          if (k == 0 && (lane & 3) < w) p[0] = 0;
          stmatrix_x4_t(k == 0 ? pb + 16 * ((255 - lane + 2 * w) & 255) : pb + 16 * (255 - lane + 2 * w) - 512 * k, p[0], p[1], p[2], p[3]);
        }
        arrive1(BAR(B_PFULL + c));
        c += 2;
      }
    }
    const uint32_t abd = DB + OFF_A + wg * ARING;
    auto a_tile = [&](int as, int n, bool first) {
#pragma unroll 1
      for (int it = 0; __any_sync(~0u, ((lds32(ck + as) ^ par) | (lds32(ck + as + (first ? 4096 : 256)) ^ par)) & 1) && it < SPIN_LIMIT; it++) {
        int h, j, r;
        ffn_role(h, j, r);
        if (elect()) {
          const uint32_t dst = base + OFF_A + wg * ARING + as;
          mbar_expect_tx(BAR(B_RETRY + wid), ASLOT);
          if (first) tma2d(dst, &maps.xs, 128 * r + 64 * (h ^ wg), 64 * n, BAR(B_RETRY + wid));
          else bulk_load(dst, G->hh + ((2 * r + (h ^ wg)) * 8 + 4 * h + fslice(j, n % 3)) * 1536 + (n / 3) * 512, ASLOT, BAR(B_RETRY + wid));
        }
        mbar_wait(BAR(B_RETRY + wid), par >> 1);
        par ^= 2;
      }
    };
    float acc[192];
    int ws = 0, as = 0;
#pragma unroll 1
    for (int u = 0; u < 20 - NT; u++) {
      mbar_wait(BAR(B_FULL + u));
      if (!(u & 1)) a_tile(as, u >> 1, true);
      wg_fence();
#pragma unroll
      for (int k = 0; k < 4; k++) wg_ss192_11(acc + 96 * (k & 1), mkdesc(abd + as + k / 2 * 2048, 16, 1024, 1), mkdesc(DB + ws + 12288 * (k & 1) + k / 2 * 2048, 4096, 1024, 1), u + k / 2);
      wg_commit();
      wg_wait<1>();
      if (elect()) mbar_arrive(BAR(B_EMPTY + u - 1));
      ws = next_slot(ws);
      as = as == 5 * ASLOT / 2 ? 0 : as + ASLOT / 2;
    }
    auto tail = [&](int v, int i) {
      const int u = 20 - NT + i / 2;
      if (i < 2 * NT) wg_ss192_11(acc + 96 * v, mkdesc(opaque(abd) + u % 6 * 4096 + (i & 1) * 2048, 16, 1024, 1), mkdesc(DB + u % 5 * WSLOT + (i & 1) * 2048 + 12288 * v, 4096, 1024, 1), 1);
      if (i == 2 * NT) wg_ss192_01(acc + 96 * v, mkdesc(DB + OFF_AX + 1024 * opaque(wg), 0, 128, 0), mkdesc(DB + OFF_BX + 6144 * v, 2048, 1024, 1), 1);
    };
#pragma unroll
    for (int u = 20 - NT; u <= 20; u++) {
      mbar_wait(BAR(u < 20 ? B_FULL + u : B_EXT));
      if (u == 16 || u == 18) a_tile(u % 6 * 4096, u >> 1, true);
      wg_fence();
      tail(0, 2 * (u + NT - 20));
      tail(0, 2 * (u + NT - 20) + 1);
      wg_commit();
      if (u == 20 - NT) { wg_wait<1>(); if (elect()) mbar_arrive(BAR(B_EMPTY + u - 1)); }
    }
    float o[80];
    uint32_t fr[3][16], bo;
    {
      int h, j, r;
      ffn_role(h, j, r);
      REGION_IDS;
      const float r0 = 0.5f * __uint_as_float(lds32(base + OFF_RT + 256 * wg + 64 * w + (lane & 28))), r1 = 0.5f * __uint_as_float(lds32(base + OFF_RT + 256 * wg + 64 * w + 32 + (lane & 28)));
      const int id = (2 * r + (h ^ wg)) * 8 + 4 * h + j;
      uint4* const hdst = G->hh + id * 1536 + 128 * w + (lane ^ lane >> 3);
      const uint32_t keep = ~(~lane & 1), bit = par & ~keep;
      bo = 1024 + ((j & 1) << 23);
      auto own = [&](int i) { wg_rs160_1(o, fr[i >> 2] + 4 * (i & 3), mkdesc(DB + (5 + i / 4) % 6 * WSLOT + (i & 3) * 2048, 8192, bo, 1), i); };
      auto gate = [&](float* g, int d) {
#pragma unroll
        for (int e = 0; e < 4; e++) { g[e] *= e < 2 ? r0 : r1; g[e + d] *= g[e]; asm("tanh.approx.f32 %0, %0;" : "+f"(g[e])); }
      };
      auto mix = [&](uint32_t* x, const float* g, int d) {
        x[0] = pack_bf16(fmaf(g[d], g[0], g[d]), fmaf(g[d + 1], g[1], g[d + 1]));
        x[1] = pack_bf16(fmaf(g[d + 2], g[2], g[d + 2]), fmaf(g[d + 3], g[3], g[d + 3]));
      };
      auto hint = [&](int v) { asm volatile("{.reg .pred p; setp.eq.u32 p, %1, 0; @p red.relaxed.gpu.global.add.u32 [%0], 1;}" ::"l"(&G->hhf[id * 8 + v]), "r"(lane) : "memory"); };
      auto put = [&](int v, int k) {
        uint32_t* x = fr[v] + 2 * k;
        const uint32_t t0 = (x[k / 2] & keep) | bit, t1 = (x[5 + k / 2] & keep) | bit;
        if (!v) { x[k / 2] = t0; x[5 + k / 2] = t1; }
        st_relaxed128(hdst + 512 * v + 8 * k, k ? x[0] : t0, k ? t0 : x[2], x[4], x[6]);
        st_relaxed128(hdst + 512 * v + 8 * k + 64, x[1], x[3], k ? x[5] : t1, k ? t1 : x[7]);
      };
      auto move = [&](uint32_t* x) {
#pragma unroll
        for (int k = 0; k < 16; k++) asm volatile("mul.rn.f32 %0, %0, %1;" : "+r"(x[k]) : "f"(P.one));
      };
      wg_fence();
      tail(1, 0);
      tail(1, 1);
      wg_commit();
      wg_wait<1>();
#pragma unroll
      for (int k = 0; k < 96; k++) asm volatile("" : "+f"(acc[k])::"memory");
      if (elect()) mbar_arrive(BAR(B_EMPTY + 18));
      gate(acc + 28, 32);
#pragma unroll
      for (int k = 7; k >= 0; k--) {
        if (k >= 8 - 2 * NT) split(P.zero, k);
        if (k > 8 - 2 * NT) tail(1, 9 - k);
        if (k == 9 - 2 * NT) wg_commit();
        if (k) gate(acc + 4 * k - 4, 32);
        mix(fr[0] + 2 * k, acc + 4 * k, 32);
        if (k == 1) hint(0);
        if (!(k & 3)) put(0, k);
      }
      move(fr[0]);
      split(P.zero, 14);
      wg_wait<0>();
#pragma unroll
      for (int k = 96; k < 192; k++) asm volatile("" : "+f"(acc[k])::"memory");
      if (elect()) mbar_arrive(BAR(B_EMPTY + 19));
#pragma unroll
      for (int k = 7; k >= 0; k--) gate(acc + 64 + 4 * k, 96);
      mbar_wait(BAR(B_FULL + 20));
      mbar_wait(BAR(B_FULL + 21));
#pragma unroll
      for (int k = 7; k >= 0; k--) mix(fr[1] + 2 * k, acc + 64 + 4 * k, 96);
#pragma unroll
      for (int k = 0; k < 4; k++) pin4(P.zero, fr[1] + 4 * k);
      wg_fence();
      own(0);
      own(1);
      split(P.zero, 15);
      put(1, 4);
      hint(1);
      own(2);
      put(1, 0);
      own(3);
      wg_commit();
      gate(acc + 124, 32);
#pragma unroll
      for (int k = 7; k >= 0; k--) {
        if (k & 1 || k == 6) split(P.zero, 16 + k);
        if (!(k & 1)) own(7 - k / 2);
        if (k == 4 || k == 0) wg_commit();
        if (k == 4) { wg_wait<1>(); if (elect()) mbar_arrive(BAR(B_EMPTY + 20)); }
        if (k) gate(acc + 92 + 4 * k, 32);
        mix(fr[2] + 2 * k, acc + 96 + 4 * k, 32);
        if (k == 1) hint(2);
        if (!(k & 3)) put(2, k);
      }
      mbar_wait(BAR(B_FULL + 22));
      wg_fence();
#pragma unroll
      for (int i = 8; i < 12; i++) own(i);
      wg_commit();
      wg_wait<1>();
      if (elect()) mbar_arrive(BAR(B_EMPTY + 21));
      ck = base + OFF_A + wg * ARING + 2048 * w + 516 * (lane >> 3) + 144 * (lane >> 2 & 1) + 32 * (lane & 3);
    }
    uint32_t x1[40];
    if (!wg) {
      REGION_IDS;
      const uint32_t xa = base + (lane >> 4) * 1024 + (lane & 7) * 128 + (((2 * w + ((lane >> 3) & 1)) ^ (lane & 7)) << 4);
      mbar_wait(BAR(B_FULL + 32));
#pragma unroll
      for (int k = 0; k < 10; k++) ldmatrix_x4_t(x1 + 4 * k, xa + (k < 6 ? OFF_X1 + k / 2 * WSLOT + (k & 1) * 2048 : OFF_SX + 2048 * (k - 6)));
    }
#pragma unroll 1
    for (int u = 23; u < (wg ? 32 : LAG2); u++) {
      as = P.hid[wg][u - 23];
      const uint64_t wd = mkdesc(0, 0, bo, 1) | P.w2t[u - 20].x;
      mbar_wait(BAR(B_FULL + u));
      a_tile(as, u - 23, false);
      wg_fence();
#pragma unroll
      for (int kk = 0; kk < 4; kk++) wg_ss160_01(o, mkdesc(abd + as + kk / 2 * 512 + (kk & 1) * 32, 16, 1024, 2), wd + kk * 128, 1);
      wg_commit();
      if (u == 31 && elect()) mbar_arrive(BAR(B_LAG));
      wg_wait<1>();
      if (elect()) mbar_arrive(BAR(B_EMPTY + u - 1));
    }
    int h, j, r;
    ffn_role(h, j, r);
    REGION_IDS;
    const uint32_t xb = base + OFF_XCH + 5120 * w;
    if (wg) {
      const uint32_t rdst = mapa(xb + 16 * lane, h ^ 1), rbar = mapa(BAR(B_FULL), h ^ 1);
      mbar_wait(BAR(B_XFREE));
      wg_wait<0>();
      fence_regs(o);
#pragma unroll
      for (int k = 0; k < 10; k++)
        asm volatile("st.async.shared::cluster.mbarrier::complete_tx::bytes.v4.b32 [%0], {%1,%2,%3,%4}, [%5];" ::"r"(rdst + 512 * k), "r"(pack_bf16(o[8 * k], o[8 * k + 1])),
                     "r"(pack_bf16(o[8 * k + 2], o[8 * k + 3])), "r"(pack_bf16(o[8 * k + 4], o[8 * k + 5])), "r"(pack_bf16(o[8 * k + 6], o[8 * k + 7])), "r"(rbar + 8 * (k / 4)) : "memory");
    } else {
      uint32_t gr[40];
      const float r0 = __uint_as_float(lds32(base + OFF_RT + 64 * w + (lane & 28))), r1 = __uint_as_float(lds32(base + OFF_RT + 64 * w + 32 + (lane & 28)));
      const uint32_t p0 = pack_bf16(r0, r0), p1 = pack_bf16(r1, r1), q0 = pack_bf16(r0 - bf_lo(p0), r0 - bf_lo(p0)), q1 = pack_bf16(r1 - bf_lo(p1), r1 - bf_lo(p1));
      mbar_wait(BAR(B_GB));
#pragma unroll
      for (int k = 0; k < 5; k++) {
        const uint4 g = lds128(base + OFF_GB + 80 * (lane & 3) + 16 * k);
        gr[8 * k] = g.x; gr[8 * k + 2] = g.y; gr[8 * k + 4] = g.z; gr[8 * k + 6] = g.w;
      }
      auto scale = [&](int k) {
#pragma unroll
        for (int e = 4 * k; e < 4 * k + 4; e += 2) { gr[e + 1] = bfma2(gr[e], p1, bmul2(gr[e], q1)); gr[e] = bfma2(gr[e], p0, bmul2(gr[e], q0)); }
      };
#pragma unroll
      for (int k = max(127 - 4 * LAG2, 0); k < 10; k++) scale(k);
      wg_wait<0>();
      if (elect()) mbar_arrive(BAR(B_EMPTY + LAG2 - 1));
#pragma unroll 1
      for (int u = LAG2; u < 32; u++) {
        mbar_wait(BAR(B_FULL + u));
        a_tile(P.hid[0][u - 23], u - 23, false);
      }
      auto da = [&](int i) { return mkdesc(DB + hid_at(i / 4 + LAG2 - 23, 0) + (i & 2) * 256 + (i & 1) * 32, 16, 1024, 2); };
      auto db = [&](int i, int b) { return mkdesc(DB + w2_at(i / 4 + LAG2 - 20) + b * w2_step(i / 4 + LAG2 - 20) + (i & 3) * 2048, w2_step(i / 4 + LAG2 - 20), bo, 1); };
      const int row = 128 * r + 64 * h + 16 * w;
      auto merge = [&](int e) {
        if (e % 4 == 0) mbar_wait_cluster(BAR(B_FULL + e / 4), 1);
        const uint4 p = lds128(xb + 16 * lane + 512 * e);
        x1[4 * e] = bfma2(gr[4 * e], p.x, x1[4 * e]); x1[4 * e + 1] = bfma2(gr[4 * e + 1], p.y, x1[4 * e + 1]);
        x1[4 * e + 2] = bfma2(gr[4 * e + 2], p.z, x1[4 * e + 2]); x1[4 * e + 3] = bfma2(gr[4 * e + 3], p.w, x1[4 * e + 3]);
      };
      auto out = [&](int k) {
        const float* v = o + 8 * k;
        uint32_t y[4];
#pragma unroll
        for (int e = 0; e < 4; e++) y[e] = bfma2(gr[4 * k + e], pack_bf16(v[2 * e], v[2 * e + 1]), x1[4 * k + e]);
        stmatrix_x4(k < 8 ? xb + 2048 * (k >> 2) + (lane & 15) * 128 + (((2 * (k & 3) + (lane >> 4)) ^ (lane & 7) ^ 4 * (j & 1)) << 4)
                          : xb + 4096 + (lane & 15) * 64 + (((2 * (k & 1) + (lane >> 4)) ^ (lane >> 1 & 3)) << 4), y[0], y[1], y[2], y[3]);
        if ((k & 3) == 3 || k == 9) {
          fence_async_smem();
          __syncwarp();
          if (lane == 0) tma2d_store(k < 8 ? &maps.outa : &maps.outb, k < 8 ? 128 * j + 64 * (k >> 2) : 512 + 32 * j, row, xb + 2048 * (k >> 2));
        }
      };
      constexpr int ND = 128 - 4 * LAG2;
      mbar_wait(BAR(B_LAG));
      wg_fence();
#pragma unroll
      for (int i = 0; i < ND; i++) {
        wg_ss160_01(o, da(i), db(i, 0), 1);
        if (i >= 1 && i <= 10) { scale(i - 1); split(P.zero, 32 + i); }
      }
      wg_commit();
#pragma unroll
      for (int e = 0; e < MG; e++) merge(e);
      __syncwarp();
      wg_wait<0>();
      fence_regs(o);
#pragma unroll
      for (int k = 0; k < 10; k++) {
        if (k >= MG && k % 4 == 0) {
#pragma unroll
          for (int e = k; e < min(k + 4, 10); e++) merge(e);
          __syncwarp();
        }
        out(k);
      }
      if (lane == 0) { bulk_commit(); bulk_wait_read(); }
    }
  }
}

typedef CUresult (*EncFn)(CUtensorMap*, CUtensorMapDataType, cuuint32_t, void*, const cuuint64_t*, const cuuint64_t*, const cuuint32_t*,
                          const cuuint32_t*, CUtensorMapInterleave, CUtensorMapSwizzle, CUtensorMapL2promotion, CUtensorMapFloatOOBfill);
static int enc_err = 0;
static void enc(EncFn fn, CUtensorMap* m, const void* p, int rank, const cuuint64_t* gd, const cuuint64_t* gs, const cuuint32_t* bd, CUtensorMapSwizzle sw) {
  cuuint32_t es[5] = {1, 1, 1, 1, 1};
  enc_err = 2 * enc_err + (fn(m, CU_TENSOR_MAP_DATA_TYPE_BFLOAT16, rank, (void*)p, gd, gs, bd, es, CU_TENSOR_MAP_INTERLEAVE_NONE, sw,
                              CU_TENSOR_MAP_L2_PROMOTION_L2_128B, CU_TENSOR_MAP_FLOAT_OOB_FILL_NONE) != CUDA_SUCCESS);
}

extern "C" void kernel_launch(void* const* d_in, const int* in_sizes, int n_in, void* d_out, int out_size) {
  const bf16 *q = (const bf16*)d_in[0], *k = (const bf16*)d_in[1], *v = (const bf16*)d_in[2], *shift = (const bf16*)d_in[3],
             *ssmk = (const bf16*)d_in[4], *ssmd = (const bf16*)d_in[5], *w1 = (const bf16*)d_in[7], *w3 = (const bf16*)d_in[8],
             *w2 = (const bf16*)d_in[9], *c = (const bf16*)d_in[10], *wmod = (const bf16*)d_in[11];
  EncFn fn = nullptr;
  cudaDriverEntryPointQueryResult qr;
  cudaGetDriverEntryPoint("cuTensorMapEncodeTiled", (void**)&fn, cudaEnableDefault, &qr);
  Scratch* pg;
  cudaGetSymbolAddress((void**)&pg, g_s);
  Maps maps;
  enc_err = 0;
  const CUtensorMapSwizzle S128 = CU_TENSOR_MAP_SWIZZLE_128B;
  { cuuint64_t gd[3] = {D_, S_ / 8, 8}, gs[2] = {D_ * 16, D_ * 2}; cuuint32_t b[3] = {64, 4, 8};
    enc(fn, &maps.km, k, 3, gd, gs, b, S128);
    enc(fn, &maps.v, v, 3, gd, gs, b, S128);
    enc(fn, &maps.q, q, 3, gd, gs, b, S128);
    b[2] = 3;
    enc(fn, &maps.kh, k, 3, gd, gs, b, S128); }
  { cuuint64_t gd[3] = {256, 2, 5}, gs[2] = {512, 1024}; cuuint32_t b[3] = {256, 1, 5};
    enc(fn, &maps.tap, shift, 3, gd, gs, b, CU_TENSOR_MAP_SWIZZLE_NONE); }
  { cuuint64_t gd[3] = {6 * D_, D_, 1}, gs[2] = {6 * D_ * 2, 6 * D_ * 2 * D_}; cuuint32_t b[3] = {64, 64, 1};
    enc(fn, &maps.wm, wmod, 3, gd, gs, b, S128); }
  { cuuint64_t gd[3] = {64, D_, F_ / 64}, gs[2] = {F_ * 2, 128}; cuuint32_t b[3] = {64, 32, 3};
    enc(fn, &maps.w1, w1, 3, gd, gs, b, S128);
    enc(fn, &maps.w3, w3, 3, gd, gs, b, S128);
    b[1] = 16;
    enc(fn, &maps.w1e, w1, 3, gd, gs, b, S128);
    enc(fn, &maps.w3e, w3, 3, gd, gs, b, S128);
    b[1] = 32; b[2] = 1;
    enc(fn, &maps.w1s, w1, 3, gd, gs, b, S128);
    enc(fn, &maps.w3s, w3, 3, gd, gs, b, S128); }
  { cuuint64_t gd[2] = {S_, D_}, gs[1] = {S_ * 2}; cuuint32_t b1[2] = {64, 64}, b2[2] = {64, 32};
    enc(fn, &maps.xs, pg->xs, 2, gd, gs, b1, S128);
    gd[1] = 2 * D_;
    enc(fn, &maps.x1b, pg->x1, 2, gd, gs, b2, S128);
    enc(fn, &maps.x1s, pg->x1, 2, gd, gs, b2, CU_TENSOR_MAP_SWIZZLE_NONE); }
  { cuuint64_t gd[5] = {D_, 2, 4, 4, 48}, gs[4] = {D_ * 2, D_ * 4, D_ * 16, D_ * 64}; cuuint32_t b[5] = {64, 2, 4, 4, 2};
    enc(fn, &maps.w2a, w2, 5, gd, gs, b, S128);
    gs[1] = D_ * 16; gs[2] = D_ * 4;
    enc(fn, &maps.w2b, w2, 5, gd, gs, b, S128); }
  { cuuint64_t gd[2] = {D_, S_}, gs[1] = {D_ * 2}; cuuint32_t b1[2] = {64, 16}, b2[2] = {32, 16};
    enc(fn, &maps.outa, d_out, 2, gd, gs, b1, S128);
    enc(fn, &maps.outb, d_out, 2, gd, gs, b2, CU_TENSOR_MAP_SWIZZLE_64B); }
  if (enc_err) return;
  cudaFuncSetAttribute(k_fused, cudaFuncAttributeMaxDynamicSharedMemorySize, SMEM_BYTES);
  cudaLaunchConfig_t cfg = {132, 512, SMEM_BYTES};
  cudaLaunchAttribute at = {cudaLaunchAttributeClusterDimension};
  at.val.clusterDim.x = 2; at.val.clusterDim.y = at.val.clusterDim.z = 1;
  cfg.attrs = &at; cfg.numAttrs = 1;
  int nc = 0;
  cudaOccupancyMaxActiveClusters(&nc, k_fused, &cfg);
  Ptrs P = {ssmk, c, ssmd, pg, 0x4E8DCBA9ull, {0x676760, 0x64620F01}, 0, 700, 420, 5500, 0, 0, 0, 6, B_KV, 0, 0, 1, 1, 0x57010, 1.f};
  const char* sched = "k10v14f04q04q14q24q34q44k24v24f14k34v34f24k44v44f34f44";
  int t = 700, pace = 440;
  for (int e = 0; e < NE; e++) {
    const char x = sched[3 * e];
    const int r = sched[3 * e + 1] - '0', kind = x == 'k' ? 0 : x == 'v' ? 1 : x == 'q' ? 2 : x == 'f' ? 3 : 4;
    t += (sched[3 * e + 2] - '0') * pace / 4;
    P.sched[e] = make_uint2(t | kind << 16 | r << 20, (kind < 2 ? tab(T_KV, r) + kind * KV_V : kind == 2 ? OFF_Q + 4096 * r : tab(T_F, r) + F_E) | (r + (kind < 2 ? B_KV : kind == 2 ? B_Q : B_FRAW)) << 18);
  }
  for (int u = 0; u < 5; u++) P.wt[u] = 11500 + 400 * u;
  const int dep[5] = {B_FL + 1, B_FL + 2, B_PFULL + 2, B_FL + 1, B_PEMPTY + 2};
  for (int u = 0; u < 20; u++) P.wdep[u] = u % 5 * WSLOT | (~u & 1) << 12 | (u < 5 ? dep[u] : B_EMPTY + u - 5);
  for (int v = 0; v < 12; v++) P.w2t[v] = make_uint2(w2_desc(v), v ? B_EMPTY + (v > 5 ? 15 + v : v > 3 ? 14 + v : v > 1 ? 16 : 15) : B_UVD);
  for (int m = 0; m < 9; m++) { P.hid[0][m] = hid_at(m, 0) - OFF_A; P.hid[1][m] = hid_at(m, 1) - OFF_A - ARING; P.hid[2][m] = B_EMPTY + 19 + (m > 2 ? m : m / 2); }
  if (nc < 66) { P.boff = 128; k_fused<<<4, 512, SMEM_BYTES, cudaStreamPerThread>>>(P, maps); P.boff = 0; }
  k_fused<<<nc < 66 ? 128 : 132, 512, SMEM_BYTES, cudaStreamPerThread>>>(P, maps);
}
```

```cpp
#include <cuda_runtime.h>
#include <cuda.h>
#include <cuda_bf16.h>
#include <stdint.h>
#include <stdlib.h>

typedef __nv_bfloat16 bf16;
constexpr int S_ = 2048, D_ = 640, F_ = 1536;

struct Scratch {
  uint32_t st1[2][1024];
  uint32_t st2[32][4][128];
  uint2 modc[128][32];
  uint2 modv[3][D_];
  uint32_t uv[8][3072];
  unsigned hint[9][8][32];
  unsigned xsh[5][8][32], hhf[256 * 8];
  uint4 xr[D_ * 256];
  uint4 qt[D_ * 256];
  uint4 xs[D_ * 256];
  uint4 x1[2][D_ * 256];
  uint4 hh[32 * 8 * 1536];
};
__device__ __align__(1024) Scratch g_s;

__device__ __forceinline__ uint32_t smem_u32(const void* p) { return (uint32_t)__cvta_generic_to_shared(p); }
__device__ __forceinline__ void mbar_expect_tx(uint32_t b, uint32_t n) { asm volatile("mbarrier.arrive.expect_tx.shared::cta.b64 _, [%0], %1;" ::"r"(b), "r"(n) : "memory"); }
__device__ __forceinline__ void mbar_arrive(uint32_t b) { asm volatile("mbarrier.arrive.shared::cta.b64 _, [%0];" ::"r"(b) : "memory"); }
__device__ __forceinline__ void mbar_arrive2(uint32_t b) { asm volatile("mbarrier.arrive.shared::cta.b64 _, [%0], 2;" ::"r"(b) : "memory"); }
__device__ __forceinline__ uint32_t mapa(uint32_t a, uint32_t cta) { uint32_t r; asm volatile("mapa.shared::cluster.u32 %0, %1, %2;" : "=r"(r) : "r"(a), "r"(cta)); return r; }
__device__ __forceinline__ void mbar_arrive_remote(uint32_t rb) { asm volatile("mbarrier.arrive.shared::cluster.b64 _, [%0];" ::"r"(rb) : "memory"); }
constexpr int SPIN_LIMIT = 1 << 16;
template <int N> __device__ __forceinline__ void mbar_init(uint32_t b, uint32_t count) {
#pragma unroll
  for (int i = 0; i < N; i++) asm volatile("mbarrier.init.shared::cta.b64 [%0], %1;" ::"r"(b + 8 * i), "r"(count) : "memory");
}
__device__ __forceinline__ bool elect() { uint32_t p; asm volatile("{.reg .pred q; elect.sync _|q, 0xffffffff; selp.u32 %0, 1, 0, q;}" : "=r"(p)); return p; }
__device__ __forceinline__ void arrive1(uint32_t b) { __syncwarp(); if (elect()) mbar_arrive(b); }
__device__ __forceinline__ bool mbar_test(uint32_t b) {
  uint32_t ok;
  asm volatile("{.reg .pred p; mbarrier.test_wait.parity.shared::cta.b64 p, [%1], 0; selp.u32 %0,1,0,p;}" : "=r"(ok) : "r"(b) : "memory");
  return ok;
}
#define WAIT_LOOP(sem) "{.reg .pred p; mov.u32 %0, 0; W: mbarrier.try_wait.parity" sem ".shared::cta.b64 p, [%1], %2; @p bra.uni D; add.u32 %0, %0, 1; setp.lt.u32 p, %0, %3; @p bra.uni W; D:}"
__device__ __forceinline__ void mbar_wait(uint32_t b, uint32_t ph = 0) {
  int it;
  asm volatile(WAIT_LOOP("") : "=&r"(it) : "r"(b), "r"(ph), "n"(SPIN_LIMIT) : "memory");
}
__device__ __forceinline__ void mbar_wait_cluster(uint32_t b, uint32_t ph = 0) {
  int it;
  asm volatile(WAIT_LOOP(".acquire.cluster") : "=&r"(it) : "r"(b), "r"(ph), "n"(SPIN_LIMIT) : "memory");
}
__device__ __forceinline__ void wait_clock(uint32_t t) {
  asm volatile("{.reg .pred p; .reg .s32 d; W: mov.u32 d, %%clock; sub.s32 d, d, %0; setp.lt.s32 p, d, 0; @p bra.uni W;}" ::"r"(t) : "memory");
}
__device__ __forceinline__ void tma2d(uint32_t dst, const CUtensorMap* m, int c0, int c1, uint32_t bar) {
  asm volatile("cp.async.bulk.tensor.2d.shared::cluster.global.mbarrier::complete_tx::bytes [%0], [%1, {%3,%4}], [%2];" ::"r"(dst), "l"(m), "r"(bar), "r"(c0), "r"(c1) : "memory");
}
__device__ __forceinline__ void tma3d(uint32_t dst, const CUtensorMap* m, int c0, int c1, int c2, uint32_t bar) {
  asm volatile("cp.async.bulk.tensor.3d.shared::cluster.global.mbarrier::complete_tx::bytes [%0], [%1, {%3,%4,%5}], [%2];" ::"r"(dst), "l"(m), "r"(bar), "r"(c0), "r"(c1), "r"(c2) : "memory");
}
__device__ __forceinline__ void tma5d(uint32_t dst, const CUtensorMap* m, int c0, int c4, uint32_t bar) {
  asm volatile("cp.async.bulk.tensor.5d.shared::cluster.global.mbarrier::complete_tx::bytes [%0], [%1, {%4,%3,%3,%3,%5}], [%2];" ::"r"(dst), "l"(m), "r"(bar), "r"(0), "r"(c0), "r"(c4) : "memory");
}
__device__ __forceinline__ void tma2d_store(const CUtensorMap* m, int c0, int c1, uint32_t src) {
  asm volatile("cp.async.bulk.tensor.2d.global.shared::cta.bulk_group [%0, {%2,%3}], [%1];" ::"l"(m), "r"(src), "r"(c0), "r"(c1) : "memory");
}
__device__ __forceinline__ void bulk_load(uint32_t dst, const void* src, uint32_t bytes, uint32_t bar) {
  asm volatile("cp.async.bulk.shared::cluster.global.mbarrier::complete_tx::bytes [%0], [%1], %2, [%3];" ::"r"(dst), "l"(src), "r"(bytes), "r"(bar) : "memory");
}
__device__ __forceinline__ void prefetch_map(const CUtensorMap* m) { asm volatile("prefetch.tensormap [%0];" ::"l"(m) : "memory"); }
__device__ __forceinline__ void bulk_commit() { asm volatile("cp.async.bulk.commit_group;" ::: "memory"); }
__device__ __forceinline__ void bulk_wait_read() { asm volatile("cp.async.bulk.wait_group.read 0;" ::: "memory"); }
__device__ __forceinline__ void fence_async_smem() { asm volatile("fence.proxy.async.shared::cta;" ::: "memory"); }
__device__ __forceinline__ void fence_async_all() { asm volatile("fence.proxy.async.global;" ::: "memory"); }
__device__ __forceinline__ void named_bar(int id, int n) { asm volatile("bar.sync %0, %1;" ::"r"(id), "r"(n) : "memory"); }
__device__ __forceinline__ bool bar_all(int id, bool v) {
  uint32_t r;
  asm volatile("{.reg .pred p, q; setp.ne.u32 p, %2, 0; bar.red.and.pred q, %1, 128, p; selp.u32 %0, 1, 0, q;}" : "=r"(r) : "r"(id), "r"((uint32_t)v) : "memory");
  return __all_sync(~0u, r);
}
__device__ __forceinline__ void cluster_wait() { asm volatile("barrier.cluster.wait.aligned;" ::: "memory"); }
__device__ __forceinline__ void wg_fence() { asm volatile("wgmma.fence.sync.aligned;" ::: "memory"); }
__device__ __forceinline__ void wg_commit() { asm volatile("wgmma.commit_group.sync.aligned;" ::: "memory"); }
template <int N> __device__ __forceinline__ void wg_wait() { asm volatile("wgmma.wait_group.sync.aligned %0;" ::"n"(N) : "memory"); }
template <int N> __device__ __forceinline__ void fence_regs(float (&a)[N]) {
#pragma unroll
  for (int i = 0; i < N; i++) asm volatile("" : "+f"(a[i])::"memory");
}
template <int N> __device__ __forceinline__ void fence_n(float* a) {
#pragma unroll
  for (int i = 0; i < N; i++) asm volatile("" : "+f"(a[i])::"memory");
}
__device__ __forceinline__ uint64_t mkdesc(uint32_t addr, uint32_t lbo, uint32_t sbo, uint32_t swz) {
  uint32_t lo = (addr >> 4) | ((lbo >> 4) << 16), hi = (sbo >> 4) | (swz << 30);
  return ((uint64_t)hi << 32) | lo;
}
__device__ __forceinline__ void stmatrix_x4(uint32_t a, uint32_t r0, uint32_t r1, uint32_t r2, uint32_t r3) {
  asm volatile("stmatrix.sync.aligned.m8n8.x4.shared.b16 [%0], {%1,%2,%3,%4};" ::"r"(a), "r"(r0), "r"(r1), "r"(r2), "r"(r3) : "memory");
}
__device__ __forceinline__ void stmatrix_x4_t(uint32_t a, uint32_t r0, uint32_t r1, uint32_t r2, uint32_t r3) {
  asm volatile("stmatrix.sync.aligned.m8n8.x4.trans.shared.b16 [%0], {%1,%2,%3,%4};" ::"r"(a), "r"(r0), "r"(r1), "r"(r2), "r"(r3) : "memory");
}
__device__ __forceinline__ void ldmatrix_x4_t(uint32_t* r, uint32_t a) {
  asm volatile("ldmatrix.sync.aligned.m8n8.x4.trans.shared.b16 {%0,%1,%2,%3}, [%4];" : "=r"(r[0]), "=r"(r[1]), "=r"(r[2]), "=r"(r[3]) : "r"(a) : "memory");
}
__device__ __forceinline__ uint32_t lds32(uint32_t a) { uint32_t v; asm volatile("ld.shared.b32 %0, [%1];" : "=r"(v) : "r"(a) : "memory"); return v; }
__device__ __forceinline__ uint2 lds64(uint32_t a) { uint2 v; asm volatile("ld.shared.v2.b32 {%0,%1}, [%2];" : "=r"(v.x), "=r"(v.y) : "r"(a) : "memory"); return v; }
__device__ __forceinline__ uint4 lds128(uint32_t a) { uint4 v; asm volatile("ld.shared.v4.b32 {%0,%1,%2,%3}, [%4];" : "=r"(v.x), "=r"(v.y), "=r"(v.z), "=r"(v.w) : "r"(a) : "memory"); return v; }
__device__ __forceinline__ void sts32(uint32_t a, uint32_t v) { asm volatile("st.shared.b32 [%0], %1;" ::"r"(a), "r"(v) : "memory"); }
__device__ __forceinline__ void sts64(uint32_t a, uint32_t x, uint32_t y) { asm volatile("st.shared.v2.b32 [%0], {%1,%2};" ::"r"(a), "r"(x), "r"(y) : "memory"); }
__device__ __forceinline__ void sts128(uint32_t a, uint32_t x, uint32_t y, uint32_t z, uint32_t w) { asm volatile("st.shared.v4.b32 [%0], {%1,%2,%3,%4};" ::"r"(a), "r"(x), "r"(y), "r"(z), "r"(w) : "memory"); }
__device__ __forceinline__ uint4 ld_relaxed128(const void* p) { uint4 v; asm volatile("ld.relaxed.gpu.global.v4.u32 {%0,%1,%2,%3}, [%4];" : "=r"(v.x), "=r"(v.y), "=r"(v.z), "=r"(v.w) : "l"(p) : "memory"); return v; }
__device__ __forceinline__ uint2 ld_relaxed64(const void* p) { uint2 v; asm volatile("ld.relaxed.gpu.global.v2.u32 {%0,%1}, [%2];" : "=r"(v.x), "=r"(v.y) : "l"(p) : "memory"); return v; }
__device__ __forceinline__ uint32_t ld_relaxed32(const void* p) { uint32_t v; asm volatile("ld.relaxed.gpu.global.u32 %0, [%1];" : "=r"(v) : "l"(p) : "memory"); return v; }
__device__ __forceinline__ void st_relaxed128(void* p, uint32_t x, uint32_t y, uint32_t z, uint32_t w) { asm volatile("st.relaxed.gpu.global.v4.u32 [%0], {%1,%2,%3,%4};" ::"l"(p), "r"(x), "r"(y), "r"(z), "r"(w) : "memory"); }
__device__ __forceinline__ void st_relaxed32(void* p, uint32_t x) { asm volatile("st.relaxed.gpu.global.u32 [%0], %1;" ::"l"(p), "r"(x) : "memory"); }
__device__ __forceinline__ void red_hint(unsigned* p) { asm volatile("red.relaxed.gpu.global.add.u32 [%0], 1;" ::"l"(p) : "memory"); }
__device__ __forceinline__ void publish(uint32_t* p, uint32_t x) { asm volatile("{.reg .b32 t; atom.relaxed.gpu.global.exch.b32 t, [%0], %1;}" ::"l"(p), "r"(x) : "memory"); }
__device__ __forceinline__ uint32_t ldg32(const void* p) { uint32_t v; asm volatile("ld.global.nc.L1::no_allocate.b32 %0, [%1];" : "=r"(v) : "l"(p)); return v; }
__device__ __forceinline__ uint32_t pack_bf16(float lo, float hi) { uint32_t r; asm("cvt.rn.bf16x2.f32 %0, %1, %2;" : "=r"(r) : "f"(hi), "f"(lo)); return r; }
__device__ __forceinline__ float bf_lo(uint32_t v) { return __uint_as_float(v << 16); }
__device__ __forceinline__ float bf_hi(uint32_t v) { return __uint_as_float(v & 0xFFFF0000u); }
__device__ __forceinline__ uint32_t bmul2(uint32_t a, uint32_t b) { uint32_t r; asm("mul.rn.bf16x2 %0, %1, %2;" : "=r"(r) : "r"(a), "r"(b)); return r; }
__device__ __forceinline__ uint32_t badd2(uint32_t a, uint32_t b) { uint32_t r; asm("add.rn.bf16x2 %0, %1, %2;" : "=r"(r) : "r"(a), "r"(b)); return r; }
__device__ __forceinline__ uint32_t bfma2(uint32_t a, uint32_t b, uint32_t c) { uint32_t r; asm("fma.rn.bf16x2 %0, %1, %2, %3;" : "=r"(r) : "r"(a), "r"(b), "r"(c)); return r; }
__device__ __forceinline__ uint32_t set_tag(uint32_t x, uint32_t mask, uint32_t e) { uint32_t r; asm("lop3.b32 %0, %1, %2, %3, 0xB8;" : "=r"(r) : "r"(x), "r"(mask), "r"(e)); return r; }
__device__ __forceinline__ uint32_t opaque(uint32_t x) { asm volatile("" : "+r"(x)); return x; }
__device__ __forceinline__ float rbf(float x) { return __bfloat162float(__float2bfloat16(x)); }
__device__ __forceinline__ float silu_f(float x) {
  float e, r;
  asm("ex2.approx.ftz.f32 %0, %1;" : "=f"(e) : "f"(x * -1.4426950408889634f));
  asm("rcp.approx.ftz.f32 %0, %1;" : "=f"(r) : "f"(1.f + e));
  return x * r;
}
__device__ __forceinline__ float silu2(float x) {
  float t;
  asm("tanh.approx.f32 %0, %1;" : "=f"(t) : "f"(x));
  return fmaf(x, t, x);
}
__device__ __forceinline__ void pin(int off, uint32_t x) { asm volatile("{.reg .pred p; setp.lt.s32 p, %0, 0; @p st.shared.b32 [%0], %1;}" ::"r"(off), "r"(x) : "memory"); }
__device__ __forceinline__ void pin4(int off, const uint32_t* x) { asm volatile("{.reg .pred p; setp.lt.s32 p, %0, 0; @p st.shared.v4.b32 [%0], {%1,%2,%3,%4};}" ::"r"(off), "r"(x[0]), "r"(x[1]), "r"(x[2]), "r"(x[3]) : "memory"); }
__device__ __forceinline__ void split(int x, int n) { asm volatile("{.reg .pred p; setp.eq.s32 p, %0, %1; @p trap;}" ::"r"(x), "r"(~n) : "memory"); }
__device__ __forceinline__ void ln_final(float s, float q, float& m, float& sd) {
  m = s * (1.f / D_);
  asm("sqrt.approx.f32 %0, %1;" : "=f"(sd) : "f"(rbf(rbf(fmaxf(fmaf(-m, m, q * (1.f / D_)), 0.f)) + 1e-5f)));
  sd = rbf(sd);
}
__device__ __forceinline__ float rcpf(float x) { float r; asm("rcp.approx.f32 %0, %1;" : "=f"(r) : "f"(x)); return r; }

__device__ __forceinline__ void wg_rs16_0(float* d, const uint32_t* a, uint64_t db, int sc) {
  asm volatile("{.reg .pred p; setp.ne.b32 p, %13, 0; wgmma.mma_async.sync.aligned.m64n16k16.f32.bf16.bf16 {%0,%1,%2,%3,%4,%5,%6,%7}, {%8,%9,%10,%11}, %12, p, 1, 1, 0;}"
    : "+f"(d[0]),"+f"(d[1]),"+f"(d[2]),"+f"(d[3]),"+f"(d[4]),"+f"(d[5]),"+f"(d[6]),"+f"(d[7]) : "r"(a[0]),"r"(a[1]),"r"(a[2]),"r"(a[3]),"l"(db),"r"(sc));
}
__device__ __forceinline__ void wg_rs32_0(float* d, const uint32_t* a, uint64_t db, int sc) {
  asm volatile("{.reg .pred p; setp.ne.b32 p, %21, 0; wgmma.mma_async.sync.aligned.m64n32k16.f32.bf16.bf16 {%0,%1,%2,%3,%4,%5,%6,%7,%8,%9,%10,%11,%12,%13,%14,%15}, {%16,%17,%18,%19}, %20, p, 1, 1, 0;}"
    : "+f"(d[0]),"+f"(d[1]),"+f"(d[2]),"+f"(d[3]),"+f"(d[4]),"+f"(d[5]),"+f"(d[6]),"+f"(d[7]),"+f"(d[8]),"+f"(d[9]),"+f"(d[10]),"+f"(d[11]),"+f"(d[12]),"+f"(d[13]),"+f"(d[14]),"+f"(d[15]) : "r"(a[0]),"r"(a[1]),"r"(a[2]),"r"(a[3]),"l"(db),"r"(sc));
}
__device__ __forceinline__ void wg_rs48_0(float* d, const uint32_t* a, uint64_t db, int sc) {
  asm volatile("{.reg .pred p; setp.ne.b32 p, %29, 0; wgmma.mma_async.sync.aligned.m64n48k16.f32.bf16.bf16 {%0,%1,%2,%3,%4,%5,%6,%7,%8,%9,%10,%11,%12,%13,%14,%15,%16,%17,%18,%19,%20,%21,%22,%23}, {%24,%25,%26,%27}, %28, p, 1, 1, 0;}"
    : "+f"(d[0]),"+f"(d[1]),"+f"(d[2]),"+f"(d[3]),"+f"(d[4]),"+f"(d[5]),"+f"(d[6]),"+f"(d[7]),"+f"(d[8]),"+f"(d[9]),"+f"(d[10]),"+f"(d[11]),"+f"(d[12]),"+f"(d[13]),"+f"(d[14]),"+f"(d[15]),"+f"(d[16]),"+f"(d[17]),"+f"(d[18]),"+f"(d[19]),"+f"(d[20]),"+f"(d[21]),"+f"(d[22]),"+f"(d[23]) : "r"(a[0]),"r"(a[1]),"r"(a[2]),"r"(a[3]),"l"(db),"r"(sc));
}
__device__ __forceinline__ void wg_rs64_0(float* d, const uint32_t* a, uint64_t db, int sc) {
  asm volatile("{.reg .pred p; setp.ne.b32 p, %37, 0; wgmma.mma_async.sync.aligned.m64n64k16.f32.bf16.bf16 {%0,%1,%2,%3,%4,%5,%6,%7,%8,%9,%10,%11,%12,%13,%14,%15,%16,%17,%18,%19,%20,%21,%22,%23,%24,%25,%26,%27,%28,%29,%30,%31}, {%32,%33,%34,%35}, %36, p, 1, 1, 0;}"
    : "+f"(d[0]),"+f"(d[1]),"+f"(d[2]),"+f"(d[3]),"+f"(d[4]),"+f"(d[5]),"+f"(d[6]),"+f"(d[7]),"+f"(d[8]),"+f"(d[9]),"+f"(d[10]),"+f"(d[11]),"+f"(d[12]),"+f"(d[13]),"+f"(d[14]),"+f"(d[15]),"+f"(d[16]),"+f"(d[17]),"+f"(d[18]),"+f"(d[19]),"+f"(d[20]),"+f"(d[21]),"+f"(d[22]),"+f"(d[23]),"+f"(d[24]),"+f"(d[25]),"+f"(d[26]),"+f"(d[27]),"+f"(d[28]),"+f"(d[29]),"+f"(d[30]),"+f"(d[31]) : "r"(a[0]),"r"(a[1]),"r"(a[2]),"r"(a[3]),"l"(db),"r"(sc));
}
__device__ __forceinline__ void wg_rs80_0(float* d, const uint32_t* a, uint64_t db, int sc) {
  asm volatile("{.reg .pred p; setp.ne.b32 p, %45, 0; wgmma.mma_async.sync.aligned.m64n80k16.f32.bf16.bf16 {%0,%1,%2,%3,%4,%5,%6,%7,%8,%9,%10,%11,%12,%13,%14,%15,%16,%17,%18,%19,%20,%21,%22,%23,%24,%25,%26,%27,%28,%29,%30,%31,%32,%33,%34,%35,%36,%37,%38,%39}, {%40,%41,%42,%43}, %44, p, 1, 1, 0;}"
    : "+f"(d[0]),"+f"(d[1]),"+f"(d[2]),"+f"(d[3]),"+f"(d[4]),"+f"(d[5]),"+f"(d[6]),"+f"(d[7]),"+f"(d[8]),"+f"(d[9]),"+f"(d[10]),"+f"(d[11]),"+f"(d[12]),"+f"(d[13]),"+f"(d[14]),"+f"(d[15]),"+f"(d[16]),"+f"(d[17]),"+f"(d[18]),"+f"(d[19]),"+f"(d[20]),"+f"(d[21]),"+f"(d[22]),"+f"(d[23]),"+f"(d[24]),"+f"(d[25]),"+f"(d[26]),"+f"(d[27]),"+f"(d[28]),"+f"(d[29]),"+f"(d[30]),"+f"(d[31]),"+f"(d[32]),"+f"(d[33]),"+f"(d[34]),"+f"(d[35]),"+f"(d[36]),"+f"(d[37]),"+f"(d[38]),"+f"(d[39]) : "r"(a[0]),"r"(a[1]),"r"(a[2]),"r"(a[3]),"l"(db),"r"(sc));
}
__device__ __forceinline__ void wg_rs96_0(float* d, const uint32_t* a, uint64_t db, int sc) {
  asm volatile("{.reg .pred p; setp.ne.b32 p, %53, 0; wgmma.mma_async.sync.aligned.m64n96k16.f32.bf16.bf16 {%0,%1,%2,%3,%4,%5,%6,%7,%8,%9,%10,%11,%12,%13,%14,%15,%16,%17,%18,%19,%20,%21,%22,%23,%24,%25,%26,%27,%28,%29,%30,%31,%32,%33,%34,%35,%36,%37,%38,%39,%40,%41,%42,%43,%44,%45,%46,%47}, {%48,%49,%50,%51}, %52, p, 1, 1, 0;}"
    : "+f"(d[0]),"+f"(d[1]),"+f"(d[2]),"+f"(d[3]),"+f"(d[4]),"+f"(d[5]),"+f"(d[6]),"+f"(d[7]),"+f"(d[8]),"+f"(d[9]),"+f"(d[10]),"+f"(d[11]),"+f"(d[12]),"+f"(d[13]),"+f"(d[14]),"+f"(d[15]),"+f"(d[16]),"+f"(d[17]),"+f"(d[18]),"+f"(d[19]),"+f"(d[20]),"+f"(d[21]),"+f"(d[22]),"+f"(d[23]),"+f"(d[24]),"+f"(d[25]),"+f"(d[26]),"+f"(d[27]),"+f"(d[28]),"+f"(d[29]),"+f"(d[30]),"+f"(d[31]),"+f"(d[32]),"+f"(d[33]),"+f"(d[34]),"+f"(d[35]),"+f"(d[36]),"+f"(d[37]),"+f"(d[38]),"+f"(d[39]),"+f"(d[40]),"+f"(d[41]),"+f"(d[42]),"+f"(d[43]),"+f"(d[44]),"+f"(d[45]),"+f"(d[46]),"+f"(d[47]) : "r"(a[0]),"r"(a[1]),"r"(a[2]),"r"(a[3]),"l"(db),"r"(sc));
}
__device__ __forceinline__ void wg_rs112_0(float* d, const uint32_t* a, uint64_t db, int sc) {
  asm volatile("{.reg .pred p; setp.ne.b32 p, %61, 0; wgmma.mma_async.sync.aligned.m64n112k16.f32.bf16.bf16 {%0,%1,%2,%3,%4,%5,%6,%7,%8,%9,%10,%11,%12,%13,%14,%15,%16,%17,%18,%19,%20,%21,%22,%23,%24,%25,%26,%27,%28,%29,%30,%31,%32,%33,%34,%35,%36,%37,%38,%39,%40,%41,%42,%43,%44,%45,%46,%47,%48,%49,%50,%51,%52,%53,%54,%55}, {%56,%57,%58,%59}, %60, p, 1, 1, 0;}"
    : "+f"(d[0]),"+f"(d[1]),"+f"(d[2]),"+f"(d[3]),"+f"(d[4]),"+f"(d[5]),"+f"(d[6]),"+f"(d[7]),"+f"(d[8]),"+f"(d[9]),"+f"(d[10]),"+f"(d[11]),"+f"(d[12]),"+f"(d[13]),"+f"(d[14]),"+f"(d[15]),"+f"(d[16]),"+f"(d[17]),"+f"(d[18]),"+f"(d[19]),"+f"(d[20]),"+f"(d[21]),"+f"(d[22]),"+f"(d[23]),"+f"(d[24]),"+f"(d[25]),"+f"(d[26]),"+f"(d[27]),"+f"(d[28]),"+f"(d[29]),"+f"(d[30]),"+f"(d[31]),"+f"(d[32]),"+f"(d[33]),"+f"(d[34]),"+f"(d[35]),"+f"(d[36]),"+f"(d[37]),"+f"(d[38]),"+f"(d[39]),"+f"(d[40]),"+f"(d[41]),"+f"(d[42]),"+f"(d[43]),"+f"(d[44]),"+f"(d[45]),"+f"(d[46]),"+f"(d[47]),"+f"(d[48]),"+f"(d[49]),"+f"(d[50]),"+f"(d[51]),"+f"(d[52]),"+f"(d[53]),"+f"(d[54]),"+f"(d[55]) : "r"(a[0]),"r"(a[1]),"r"(a[2]),"r"(a[3]),"l"(db),"r"(sc));
}
__device__ __forceinline__ void wg_rs128_0(float* d, const uint32_t* a, uint64_t db, int sc) {
  asm volatile("{.reg .pred p; setp.ne.b32 p, %69, 0; wgmma.mma_async.sync.aligned.m64n128k16.f32.bf16.bf16 {%0,%1,%2,%3,%4,%5,%6,%7,%8,%9,%10,%11,%12,%13,%14,%15,%16,%17,%18,%19,%20,%21,%22,%23,%24,%25,%26,%27,%28,%29,%30,%31,%32,%33,%34,%35,%36,%37,%38,%39,%40,%41,%42,%43,%44,%45,%46,%47,%48,%49,%50,%51,%52,%53,%54,%55,%56,%57,%58,%59,%60,%61,%62,%63}, {%64,%65,%66,%67}, %68, p, 1, 1, 0;}"
    : "+f"(d[0]),"+f"(d[1]),"+f"(d[2]),"+f"(d[3]),"+f"(d[4]),"+f"(d[5]),"+f"(d[6]),"+f"(d[7]),"+f"(d[8]),"+f"(d[9]),"+f"(d[10]),"+f"(d[11]),"+f"(d[12]),"+f"(d[13]),"+f"(d[14]),"+f"(d[15]),"+f"(d[16]),"+f"(d[17]),"+f"(d[18]),"+f"(d[19]),"+f"(d[20]),"+f"(d[21]),"+f"(d[22]),"+f"(d[23]),"+f"(d[24]),"+f"(d[25]),"+f"(d[26]),"+f"(d[27]),"+f"(d[28]),"+f"(d[29]),"+f"(d[30]),"+f"(d[31]),"+f"(d[32]),"+f"(d[33]),"+f"(d[34]),"+f"(d[35]),"+f"(d[36]),"+f"(d[37]),"+f"(d[38]),"+f"(d[39]),"+f"(d[40]),"+f"(d[41]),"+f"(d[42]),"+f"(d[43]),"+f"(d[44]),"+f"(d[45]),"+f"(d[46]),"+f"(d[47]),"+f"(d[48]),"+f"(d[49]),"+f"(d[50]),"+f"(d[51]),"+f"(d[52]),"+f"(d[53]),"+f"(d[54]),"+f"(d[55]),"+f"(d[56]),"+f"(d[57]),"+f"(d[58]),"+f"(d[59]),"+f"(d[60]),"+f"(d[61]),"+f"(d[62]),"+f"(d[63]) : "r"(a[0]),"r"(a[1]),"r"(a[2]),"r"(a[3]),"l"(db),"r"(sc));
}
__device__ __forceinline__ void wg_rs144_0(float* d, const uint32_t* a, uint64_t db, int sc) {
  asm volatile("{.reg .pred p; setp.ne.b32 p, %77, 0; wgmma.mma_async.sync.aligned.m64n144k16.f32.bf16.bf16 {%0,%1,%2,%3,%4,%5,%6,%7,%8,%9,%10,%11,%12,%13,%14,%15,%16,%17,%18,%19,%20,%21,%22,%23,%24,%25,%26,%27,%28,%29,%30,%31,%32,%33,%34,%35,%36,%37,%38,%39,%40,%41,%42,%43,%44,%45,%46,%47,%48,%49,%50,%51,%52,%53,%54,%55,%56,%57,%58,%59,%60,%61,%62,%63,%64,%65,%66,%67,%68,%69,%70,%71}, {%72,%73,%74,%75}, %76, p, 1, 1, 0;}"
    : "+f"(d[0]),"+f"(d[1]),"+f"(d[2]),"+f"(d[3]),"+f"(d[4]),"+f"(d[5]),"+f"(d[6]),"+f"(d[7]),"+f"(d[8]),"+f"(d[9]),"+f"(d[10]),"+f"(d[11]),"+f"(d[12]),"+f"(d[13]),"+f"(d[14]),"+f"(d[15]),"+f"(d[16]),"+f"(d[17]),"+f"(d[18]),"+f"(d[19]),"+f"(d[20]),"+f"(d[21]),"+f"(d[22]),"+f"(d[23]),"+f"(d[24]),"+f"(d[25]),"+f"(d[26]),"+f"(d[27]),"+f"(d[28]),"+f"(d[29]),"+f"(d[30]),"+f"(d[31]),"+f"(d[32]),"+f"(d[33]),"+f"(d[34]),"+f"(d[35]),"+f"(d[36]),"+f"(d[37]),"+f"(d[38]),"+f"(d[39]),"+f"(d[40]),"+f"(d[41]),"+f"(d[42]),"+f"(d[43]),"+f"(d[44]),"+f"(d[45]),"+f"(d[46]),"+f"(d[47]),"+f"(d[48]),"+f"(d[49]),"+f"(d[50]),"+f"(d[51]),"+f"(d[52]),"+f"(d[53]),"+f"(d[54]),"+f"(d[55]),"+f"(d[56]),"+f"(d[57]),"+f"(d[58]),"+f"(d[59]),"+f"(d[60]),"+f"(d[61]),"+f"(d[62]),"+f"(d[63]),"+f"(d[64]),"+f"(d[65]),"+f"(d[66]),"+f"(d[67]),"+f"(d[68]),"+f"(d[69]),"+f"(d[70]),"+f"(d[71]) : "r"(a[0]),"r"(a[1]),"r"(a[2]),"r"(a[3]),"l"(db),"r"(sc));
}
__device__ __forceinline__ void wg_rs160_0(float* d, const uint32_t* a, uint64_t db, int sc) {
  asm volatile("{.reg .pred p; setp.ne.b32 p, %85, 0; wgmma.mma_async.sync.aligned.m64n160k16.f32.bf16.bf16 {%0,%1,%2,%3,%4,%5,%6,%7,%8,%9,%10,%11,%12,%13,%14,%15,%16,%17,%18,%19,%20,%21,%22,%23,%24,%25,%26,%27,%28,%29,%30,%31,%32,%33,%34,%35,%36,%37,%38,%39,%40,%41,%42,%43,%44,%45,%46,%47,%48,%49,%50,%51,%52,%53,%54,%55,%56,%57,%58,%59,%60,%61,%62,%63,%64,%65,%66,%67,%68,%69,%70,%71,%72,%73,%74,%75,%76,%77,%78,%79}, {%80,%81,%82,%83}, %84, p, 1, 1, 0;}"
    : "+f"(d[0]),"+f"(d[1]),"+f"(d[2]),"+f"(d[3]),"+f"(d[4]),"+f"(d[5]),"+f"(d[6]),"+f"(d[7]),"+f"(d[8]),"+f"(d[9]),"+f"(d[10]),"+f"(d[11]),"+f"(d[12]),"+f"(d[13]),"+f"(d[14]),"+f"(d[15]),"+f"(d[16]),"+f"(d[17]),"+f"(d[18]),"+f"(d[19]),"+f"(d[20]),"+f"(d[21]),"+f"(d[22]),"+f"(d[23]),"+f"(d[24]),"+f"(d[25]),"+f"(d[26]),"+f"(d[27]),"+f"(d[28]),"+f"(d[29]),"+f"(d[30]),"+f"(d[31]),"+f"(d[32]),"+f"(d[33]),"+f"(d[34]),"+f"(d[35]),"+f"(d[36]),"+f"(d[37]),"+f"(d[38]),"+f"(d[39]),"+f"(d[40]),"+f"(d[41]),"+f"(d[42]),"+f"(d[43]),"+f"(d[44]),"+f"(d[45]),"+f"(d[46]),"+f"(d[47]),"+f"(d[48]),"+f"(d[49]),"+f"(d[50]),"+f"(d[51]),"+f"(d[52]),"+f"(d[53]),"+f"(d[54]),"+f"(d[55]),"+f"(d[56]),"+f"(d[57]),"+f"(d[58]),"+f"(d[59]),"+f"(d[60]),"+f"(d[61]),"+f"(d[62]),"+f"(d[63]),"+f"(d[64]),"+f"(d[65]),"+f"(d[66]),"+f"(d[67]),"+f"(d[68]),"+f"(d[69]),"+f"(d[70]),"+f"(d[71]),"+f"(d[72]),"+f"(d[73]),"+f"(d[74]),"+f"(d[75]),"+f"(d[76]),"+f"(d[77]),"+f"(d[78]),"+f"(d[79]) : "r"(a[0]),"r"(a[1]),"r"(a[2]),"r"(a[3]),"l"(db),"r"(sc));
}
__device__ __forceinline__ void wg_rs176_0(float* d, const uint32_t* a, uint64_t db, int sc) {
  asm volatile("{.reg .pred p; setp.ne.b32 p, %93, 0; wgmma.mma_async.sync.aligned.m64n176k16.f32.bf16.bf16 {%0,%1,%2,%3,%4,%5,%6,%7,%8,%9,%10,%11,%12,%13,%14,%15,%16,%17,%18,%19,%20,%21,%22,%23,%24,%25,%26,%27,%28,%29,%30,%31,%32,%33,%34,%35,%36,%37,%38,%39,%40,%41,%42,%43,%44,%45,%46,%47,%48,%49,%50,%51,%52,%53,%54,%55,%56,%57,%58,%59,%60,%61,%62,%63,%64,%65,%66,%67,%68,%69,%70,%71,%72,%73,%74,%75,%76,%77,%78,%79,%80,%81,%82,%83,%84,%85,%86,%87}, {%88,%89,%90,%91}, %92, p, 1, 1, 0;}"
    : "+f"(d[0]),"+f"(d[1]),"+f"(d[2]),"+f"(d[3]),"+f"(d[4]),"+f"(d[5]),"+f"(d[6]),"+f"(d[7]),"+f"(d[8]),"+f"(d[9]),"+f"(d[10]),"+f"(d[11]),"+f"(d[12]),"+f"(d[13]),"+f"(d[14]),"+f"(d[15]),"+f"(d[16]),"+f"(d[17]),"+f"(d[18]),"+f"(d[19]),"+f"(d[20]),"+f"(d[21]),"+f"(d[22]),"+f"(d[23]),"+f"(d[24]),"+f"(d[25]),"+f"(d[26]),"+f"(d[27]),"+f"(d[28]),"+f"(d[29]),"+f"(d[30]),"+f"(d[31]),"+f"(d[32]),"+f"(d[33]),"+f"(d[34]),"+f"(d[35]),"+f"(d[36]),"+f"(d[37]),"+f"(d[38]),"+f"(d[39]),"+f"(d[40]),"+f"(d[41]),"+f"(d[42]),"+f"(d[43]),"+f"(d[44]),"+f"(d[45]),"+f"(d[46]),"+f"(d[47]),"+f"(d[48]),"+f"(d[49]),"+f"(d[50]),"+f"(d[51]),"+f"(d[52]),"+f"(d[53]),"+f"(d[54]),"+f"(d[55]),"+f"(d[56]),"+f"(d[57]),"+f"(d[58]),"+f"(d[59]),"+f"(d[60]),"+f"(d[61]),"+f"(d[62]),"+f"(d[63]),"+f"(d[64]),"+f"(d[65]),"+f"(d[66]),"+f"(d[67]),"+f"(d[68]),"+f"(d[69]),"+f"(d[70]),"+f"(d[71]),"+f"(d[72]),"+f"(d[73]),"+f"(d[74]),"+f"(d[75]),"+f"(d[76]),"+f"(d[77]),"+f"(d[78]),"+f"(d[79]),"+f"(d[80]),"+f"(d[81]),"+f"(d[82]),"+f"(d[83]),"+f"(d[84]),"+f"(d[85]),"+f"(d[86]),"+f"(d[87]) : "r"(a[0]),"r"(a[1]),"r"(a[2]),"r"(a[3]),"l"(db),"r"(sc));
}
__device__ __forceinline__ void wg_rs192_0(float* d, const uint32_t* a, uint64_t db, int sc) {
  asm volatile("{.reg .pred p; setp.ne.b32 p, %101, 0; wgmma.mma_async.sync.aligned.m64n192k16.f32.bf16.bf16 {%0,%1,%2,%3,%4,%5,%6,%7,%8,%9,%10,%11,%12,%13,%14,%15,%16,%17,%18,%19,%20,%21,%22,%23,%24,%25,%26,%27,%28,%29,%30,%31,%32,%33,%34,%35,%36,%37,%38,%39,%40,%41,%42,%43,%44,%45,%46,%47,%48,%49,%50,%51,%52,%53,%54,%55,%56,%57,%58,%59,%60,%61,%62,%63,%64,%65,%66,%67,%68,%69,%70,%71,%72,%73,%74,%75,%76,%77,%78,%79,%80,%81,%82,%83,%84,%85,%86,%87,%88,%89,%90,%91,%92,%93,%94,%95}, {%96,%97,%98,%99}, %100, p, 1, 1, 0;}"
    : "+f"(d[0]),"+f"(d[1]),"+f"(d[2]),"+f"(d[3]),"+f"(d[4]),"+f"(d[5]),"+f"(d[6]),"+f"(d[7]),"+f"(d[8]),"+f"(d[9]),"+f"(d[10]),"+f"(d[11]),"+f"(d[12]),"+f"(d[13]),"+f"(d[14]),"+f"(d[15]),"+f"(d[16]),"+f"(d[17]),"+f"(d[18]),"+f"(d[19]),"+f"(d[20]),"+f"(d[21]),"+f"(d[22]),"+f"(d[23]),"+f"(d[24]),"+f"(d[25]),"+f"(d[26]),"+f"(d[27]),"+f"(d[28]),"+f"(d[29]),"+f"(d[30]),"+f"(d[31]),"+f"(d[32]),"+f"(d[33]),"+f"(d[34]),"+f"(d[35]),"+f"(d[36]),"+f"(d[37]),"+f"(d[38]),"+f"(d[39]),"+f"(d[40]),"+f"(d[41]),"+f"(d[42]),"+f"(d[43]),"+f"(d[44]),"+f"(d[45]),"+f"(d[46]),"+f"(d[47]),"+f"(d[48]),"+f"(d[49]),"+f"(d[50]),"+f"(d[51]),"+f"(d[52]),"+f"(d[53]),"+f"(d[54]),"+f"(d[55]),"+f"(d[56]),"+f"(d[57]),"+f"(d[58]),"+f"(d[59]),"+f"(d[60]),"+f"(d[61]),"+f"(d[62]),"+f"(d[63]),"+f"(d[64]),"+f"(d[65]),"+f"(d[66]),"+f"(d[67]),"+f"(d[68]),"+f"(d[69]),"+f"(d[70]),"+f"(d[71]),"+f"(d[72]),"+f"(d[73]),"+f"(d[74]),"+f"(d[75]),"+f"(d[76]),"+f"(d[77]),"+f"(d[78]),"+f"(d[79]),"+f"(d[80]),"+f"(d[81]),"+f"(d[82]),"+f"(d[83]),"+f"(d[84]),"+f"(d[85]),"+f"(d[86]),"+f"(d[87]),"+f"(d[88]),"+f"(d[89]),"+f"(d[90]),"+f"(d[91]),"+f"(d[92]),"+f"(d[93]),"+f"(d[94]),"+f"(d[95]) : "r"(a[0]),"r"(a[1]),"r"(a[2]),"r"(a[3]),"l"(db),"r"(sc));
}
__device__ __forceinline__ void wg_ss192_11(float* d, uint64_t da, uint64_t db, int sc) {
  asm volatile("{.reg .pred p; setp.ne.b32 p, %98, 0; wgmma.mma_async.sync.aligned.m64n192k16.f32.bf16.bf16 {%0,%1,%2,%3,%4,%5,%6,%7,%8,%9,%10,%11,%12,%13,%14,%15,%16,%17,%18,%19,%20,%21,%22,%23,%24,%25,%26,%27,%28,%29,%30,%31,%32,%33,%34,%35,%36,%37,%38,%39,%40,%41,%42,%43,%44,%45,%46,%47,%48,%49,%50,%51,%52,%53,%54,%55,%56,%57,%58,%59,%60,%61,%62,%63,%64,%65,%66,%67,%68,%69,%70,%71,%72,%73,%74,%75,%76,%77,%78,%79,%80,%81,%82,%83,%84,%85,%86,%87,%88,%89,%90,%91,%92,%93,%94,%95}, %96, %97, p, 1, 1, 1, 1;}"
    : "+f"(d[0]),"+f"(d[1]),"+f"(d[2]),"+f"(d[3]),"+f"(d[4]),"+f"(d[5]),"+f"(d[6]),"+f"(d[7]),"+f"(d[8]),"+f"(d[9]),"+f"(d[10]),"+f"(d[11]),"+f"(d[12]),"+f"(d[13]),"+f"(d[14]),"+f"(d[15]),"+f"(d[16]),"+f"(d[17]),"+f"(d[18]),"+f"(d[19]),"+f"(d[20]),"+f"(d[21]),"+f"(d[22]),"+f"(d[23]),"+f"(d[24]),"+f"(d[25]),"+f"(d[26]),"+f"(d[27]),"+f"(d[28]),"+f"(d[29]),"+f"(d[30]),"+f"(d[31]),"+f"(d[32]),"+f"(d[33]),"+f"(d[34]),"+f"(d[35]),"+f"(d[36]),"+f"(d[37]),"+f"(d[38]),"+f"(d[39]),"+f"(d[40]),"+f"(d[41]),"+f"(d[42]),"+f"(d[43]),"+f"(d[44]),"+f"(d[45]),"+f"(d[46]),"+f"(d[47]),"+f"(d[48]),"+f"(d[49]),"+f"(d[50]),"+f"(d[51]),"+f"(d[52]),"+f"(d[53]),"+f"(d[54]),"+f"(d[55]),"+f"(d[56]),"+f"(d[57]),"+f"(d[58]),"+f"(d[59]),"+f"(d[60]),"+f"(d[61]),"+f"(d[62]),"+f"(d[63]),"+f"(d[64]),"+f"(d[65]),"+f"(d[66]),"+f"(d[67]),"+f"(d[68]),"+f"(d[69]),"+f"(d[70]),"+f"(d[71]),"+f"(d[72]),"+f"(d[73]),"+f"(d[74]),"+f"(d[75]),"+f"(d[76]),"+f"(d[77]),"+f"(d[78]),"+f"(d[79]),"+f"(d[80]),"+f"(d[81]),"+f"(d[82]),"+f"(d[83]),"+f"(d[84]),"+f"(d[85]),"+f"(d[86]),"+f"(d[87]),"+f"(d[88]),"+f"(d[89]),"+f"(d[90]),"+f"(d[91]),"+f"(d[92]),"+f"(d[93]),"+f"(d[94]),"+f"(d[95]) : "l"(da),"l"(db),"r"(sc));
}
__device__ __forceinline__ void wg_ss192_01(float* d, uint64_t da, uint64_t db, int sc) {
  asm volatile("{.reg .pred p; setp.ne.b32 p, %98, 0; wgmma.mma_async.sync.aligned.m64n192k16.f32.bf16.bf16 {%0,%1,%2,%3,%4,%5,%6,%7,%8,%9,%10,%11,%12,%13,%14,%15,%16,%17,%18,%19,%20,%21,%22,%23,%24,%25,%26,%27,%28,%29,%30,%31,%32,%33,%34,%35,%36,%37,%38,%39,%40,%41,%42,%43,%44,%45,%46,%47,%48,%49,%50,%51,%52,%53,%54,%55,%56,%57,%58,%59,%60,%61,%62,%63,%64,%65,%66,%67,%68,%69,%70,%71,%72,%73,%74,%75,%76,%77,%78,%79,%80,%81,%82,%83,%84,%85,%86,%87,%88,%89,%90,%91,%92,%93,%94,%95}, %96, %97, p, 1, 1, 0, 1;}"
    : "+f"(d[0]),"+f"(d[1]),"+f"(d[2]),"+f"(d[3]),"+f"(d[4]),"+f"(d[5]),"+f"(d[6]),"+f"(d[7]),"+f"(d[8]),"+f"(d[9]),"+f"(d[10]),"+f"(d[11]),"+f"(d[12]),"+f"(d[13]),"+f"(d[14]),"+f"(d[15]),"+f"(d[16]),"+f"(d[17]),"+f"(d[18]),"+f"(d[19]),"+f"(d[20]),"+f"(d[21]),"+f"(d[22]),"+f"(d[23]),"+f"(d[24]),"+f"(d[25]),"+f"(d[26]),"+f"(d[27]),"+f"(d[28]),"+f"(d[29]),"+f"(d[30]),"+f"(d[31]),"+f"(d[32]),"+f"(d[33]),"+f"(d[34]),"+f"(d[35]),"+f"(d[36]),"+f"(d[37]),"+f"(d[38]),"+f"(d[39]),"+f"(d[40]),"+f"(d[41]),"+f"(d[42]),"+f"(d[43]),"+f"(d[44]),"+f"(d[45]),"+f"(d[46]),"+f"(d[47]),"+f"(d[48]),"+f"(d[49]),"+f"(d[50]),"+f"(d[51]),"+f"(d[52]),"+f"(d[53]),"+f"(d[54]),"+f"(d[55]),"+f"(d[56]),"+f"(d[57]),"+f"(d[58]),"+f"(d[59]),"+f"(d[60]),"+f"(d[61]),"+f"(d[62]),"+f"(d[63]),"+f"(d[64]),"+f"(d[65]),"+f"(d[66]),"+f"(d[67]),"+f"(d[68]),"+f"(d[69]),"+f"(d[70]),"+f"(d[71]),"+f"(d[72]),"+f"(d[73]),"+f"(d[74]),"+f"(d[75]),"+f"(d[76]),"+f"(d[77]),"+f"(d[78]),"+f"(d[79]),"+f"(d[80]),"+f"(d[81]),"+f"(d[82]),"+f"(d[83]),"+f"(d[84]),"+f"(d[85]),"+f"(d[86]),"+f"(d[87]),"+f"(d[88]),"+f"(d[89]),"+f"(d[90]),"+f"(d[91]),"+f"(d[92]),"+f"(d[93]),"+f"(d[94]),"+f"(d[95]) : "l"(da),"l"(db),"r"(sc));
}
__device__ __forceinline__ void wg_ss160_01(float* d, uint64_t da, uint64_t db, int sc) {
  asm volatile("{.reg .pred p; setp.ne.b32 p, %82, 0; wgmma.mma_async.sync.aligned.m64n160k16.f32.bf16.bf16 {%0,%1,%2,%3,%4,%5,%6,%7,%8,%9,%10,%11,%12,%13,%14,%15,%16,%17,%18,%19,%20,%21,%22,%23,%24,%25,%26,%27,%28,%29,%30,%31,%32,%33,%34,%35,%36,%37,%38,%39,%40,%41,%42,%43,%44,%45,%46,%47,%48,%49,%50,%51,%52,%53,%54,%55,%56,%57,%58,%59,%60,%61,%62,%63,%64,%65,%66,%67,%68,%69,%70,%71,%72,%73,%74,%75,%76,%77,%78,%79}, %80, %81, p, 1, 1, 0, 1;}"
    : "+f"(d[0]),"+f"(d[1]),"+f"(d[2]),"+f"(d[3]),"+f"(d[4]),"+f"(d[5]),"+f"(d[6]),"+f"(d[7]),"+f"(d[8]),"+f"(d[9]),"+f"(d[10]),"+f"(d[11]),"+f"(d[12]),"+f"(d[13]),"+f"(d[14]),"+f"(d[15]),"+f"(d[16]),"+f"(d[17]),"+f"(d[18]),"+f"(d[19]),"+f"(d[20]),"+f"(d[21]),"+f"(d[22]),"+f"(d[23]),"+f"(d[24]),"+f"(d[25]),"+f"(d[26]),"+f"(d[27]),"+f"(d[28]),"+f"(d[29]),"+f"(d[30]),"+f"(d[31]),"+f"(d[32]),"+f"(d[33]),"+f"(d[34]),"+f"(d[35]),"+f"(d[36]),"+f"(d[37]),"+f"(d[38]),"+f"(d[39]),"+f"(d[40]),"+f"(d[41]),"+f"(d[42]),"+f"(d[43]),"+f"(d[44]),"+f"(d[45]),"+f"(d[46]),"+f"(d[47]),"+f"(d[48]),"+f"(d[49]),"+f"(d[50]),"+f"(d[51]),"+f"(d[52]),"+f"(d[53]),"+f"(d[54]),"+f"(d[55]),"+f"(d[56]),"+f"(d[57]),"+f"(d[58]),"+f"(d[59]),"+f"(d[60]),"+f"(d[61]),"+f"(d[62]),"+f"(d[63]),"+f"(d[64]),"+f"(d[65]),"+f"(d[66]),"+f"(d[67]),"+f"(d[68]),"+f"(d[69]),"+f"(d[70]),"+f"(d[71]),"+f"(d[72]),"+f"(d[73]),"+f"(d[74]),"+f"(d[75]),"+f"(d[76]),"+f"(d[77]),"+f"(d[78]),"+f"(d[79]) : "l"(da),"l"(db),"r"(sc));
}
__device__ __forceinline__ void wg_ss96_01(float* d, uint64_t da, uint64_t db, int sc) {
  asm volatile("{.reg .pred p; setp.ne.b32 p, %50, 0; wgmma.mma_async.sync.aligned.m64n96k16.f32.bf16.bf16 {%0,%1,%2,%3,%4,%5,%6,%7,%8,%9,%10,%11,%12,%13,%14,%15,%16,%17,%18,%19,%20,%21,%22,%23,%24,%25,%26,%27,%28,%29,%30,%31,%32,%33,%34,%35,%36,%37,%38,%39,%40,%41,%42,%43,%44,%45,%46,%47}, %48, %49, p, 1, 1, 0, 1;}"
    : "+f"(d[0]),"+f"(d[1]),"+f"(d[2]),"+f"(d[3]),"+f"(d[4]),"+f"(d[5]),"+f"(d[6]),"+f"(d[7]),"+f"(d[8]),"+f"(d[9]),"+f"(d[10]),"+f"(d[11]),"+f"(d[12]),"+f"(d[13]),"+f"(d[14]),"+f"(d[15]),"+f"(d[16]),"+f"(d[17]),"+f"(d[18]),"+f"(d[19]),"+f"(d[20]),"+f"(d[21]),"+f"(d[22]),"+f"(d[23]),"+f"(d[24]),"+f"(d[25]),"+f"(d[26]),"+f"(d[27]),"+f"(d[28]),"+f"(d[29]),"+f"(d[30]),"+f"(d[31]),"+f"(d[32]),"+f"(d[33]),"+f"(d[34]),"+f"(d[35]),"+f"(d[36]),"+f"(d[37]),"+f"(d[38]),"+f"(d[39]),"+f"(d[40]),"+f"(d[41]),"+f"(d[42]),"+f"(d[43]),"+f"(d[44]),"+f"(d[45]),"+f"(d[46]),"+f"(d[47]) : "l"(da),"l"(db),"r"(sc));
}
__device__ __forceinline__ void wg_ss64_01(float* d, uint64_t da, uint64_t db, int sc) {
  asm volatile("{.reg .pred p; setp.ne.b32 p, %34, 0; wgmma.mma_async.sync.aligned.m64n64k16.f32.bf16.bf16 {%0,%1,%2,%3,%4,%5,%6,%7,%8,%9,%10,%11,%12,%13,%14,%15,%16,%17,%18,%19,%20,%21,%22,%23,%24,%25,%26,%27,%28,%29,%30,%31}, %32, %33, p, 1, 1, 0, 1;}"
    : "+f"(d[0]),"+f"(d[1]),"+f"(d[2]),"+f"(d[3]),"+f"(d[4]),"+f"(d[5]),"+f"(d[6]),"+f"(d[7]),"+f"(d[8]),"+f"(d[9]),"+f"(d[10]),"+f"(d[11]),"+f"(d[12]),"+f"(d[13]),"+f"(d[14]),"+f"(d[15]),"+f"(d[16]),"+f"(d[17]),"+f"(d[18]),"+f"(d[19]),"+f"(d[20]),"+f"(d[21]),"+f"(d[22]),"+f"(d[23]),"+f"(d[24]),"+f"(d[25]),"+f"(d[26]),"+f"(d[27]),"+f"(d[28]),"+f"(d[29]),"+f"(d[30]),"+f"(d[31]) : "l"(da),"l"(db),"r"(sc));
}
__device__ __forceinline__ void wg_rs160_1(float* d, const uint32_t* a, uint64_t db, int sc) {
  asm volatile("{.reg .pred p; setp.ne.b32 p, %85, 0; wgmma.mma_async.sync.aligned.m64n160k16.f32.bf16.bf16 {%0,%1,%2,%3,%4,%5,%6,%7,%8,%9,%10,%11,%12,%13,%14,%15,%16,%17,%18,%19,%20,%21,%22,%23,%24,%25,%26,%27,%28,%29,%30,%31,%32,%33,%34,%35,%36,%37,%38,%39,%40,%41,%42,%43,%44,%45,%46,%47,%48,%49,%50,%51,%52,%53,%54,%55,%56,%57,%58,%59,%60,%61,%62,%63,%64,%65,%66,%67,%68,%69,%70,%71,%72,%73,%74,%75,%76,%77,%78,%79}, {%80,%81,%82,%83}, %84, p, 1, 1, 1;}"
    : "+f"(d[0]),"+f"(d[1]),"+f"(d[2]),"+f"(d[3]),"+f"(d[4]),"+f"(d[5]),"+f"(d[6]),"+f"(d[7]),"+f"(d[8]),"+f"(d[9]),"+f"(d[10]),"+f"(d[11]),"+f"(d[12]),"+f"(d[13]),"+f"(d[14]),"+f"(d[15]),"+f"(d[16]),"+f"(d[17]),"+f"(d[18]),"+f"(d[19]),"+f"(d[20]),"+f"(d[21]),"+f"(d[22]),"+f"(d[23]),"+f"(d[24]),"+f"(d[25]),"+f"(d[26]),"+f"(d[27]),"+f"(d[28]),"+f"(d[29]),"+f"(d[30]),"+f"(d[31]),"+f"(d[32]),"+f"(d[33]),"+f"(d[34]),"+f"(d[35]),"+f"(d[36]),"+f"(d[37]),"+f"(d[38]),"+f"(d[39]),"+f"(d[40]),"+f"(d[41]),"+f"(d[42]),"+f"(d[43]),"+f"(d[44]),"+f"(d[45]),"+f"(d[46]),"+f"(d[47]),"+f"(d[48]),"+f"(d[49]),"+f"(d[50]),"+f"(d[51]),"+f"(d[52]),"+f"(d[53]),"+f"(d[54]),"+f"(d[55]),"+f"(d[56]),"+f"(d[57]),"+f"(d[58]),"+f"(d[59]),"+f"(d[60]),"+f"(d[61]),"+f"(d[62]),"+f"(d[63]),"+f"(d[64]),"+f"(d[65]),"+f"(d[66]),"+f"(d[67]),"+f"(d[68]),"+f"(d[69]),"+f"(d[70]),"+f"(d[71]),"+f"(d[72]),"+f"(d[73]),"+f"(d[74]),"+f"(d[75]),"+f"(d[76]),"+f"(d[77]),"+f"(d[78]),"+f"(d[79]) : "r"(a[0]),"r"(a[1]),"r"(a[2]),"r"(a[3]),"l"(db),"r"(sc));
}
__device__ __forceinline__ void wg_ss8_10(float* d, uint64_t da, uint64_t db, int sc) {
  asm volatile("{.reg .pred p; setp.ne.b32 p, %6, 0; wgmma.mma_async.sync.aligned.m64n8k16.f32.bf16.bf16 {%0,%1,%2,%3}, %4, %5, p, 1, 1, 1, 0;}"
    : "+f"(d[0]),"+f"(d[1]),"+f"(d[2]),"+f"(d[3]) : "l"(da),"l"(db),"r"(sc));
}

constexpr uint32_t DB = 1024;
constexpr int WSLOT = 24576, NW = 6, ASLOT = 8192, ARING = 4 * ASLOT;
constexpr int OFF_A = NW * WSLOT;
constexpr int OFF_PB = OFF_A + 2 * ARING;
constexpr int OFF_CV = OFF_PB + 16384, OFF_ST = OFF_CV + 768, OFF_TS = OFF_ST + 256, OFF_MODR = OFF_TS + 512, OFF_BAR = OFF_MODR + 80, SMEM_BYTES = OFF_BAR + 1168;
constexpr int OFF_BX = OFF_PB, OFF_AX = OFF_BX + 12288, OFF_RT = OFF_AX + 2048, OFF_GB = OFF_RT + 512, OFF_CO = OFF_CV;
constexpr int OFF_UV = 5 * WSLOT, OFF_UVE = OFF_PB, OFF_SX = OFF_A + ARING + 3 * ASLOT, OFF_X1 = 2 * WSLOT + ASLOT, OFF_XCH = WSLOT;
constexpr int OFF_Q = 0, KV_V = 4096, KV_H = 8192, F_E = 16, F_O = 4176, OFF_TAP = 168576, OFF_MR = OFF_A + 3 * ASLOT;
constexpr uint64_t pk5(int a, int b, int c, int d, int e) { return (uint64_t)(a / 128) | (uint64_t)(b / 128) << 12 | (uint64_t)(c / 128) << 24 | (uint64_t)(d / 128) << 36 | (uint64_t)(e / 128) << 48; }
constexpr uint64_t T_KV = pk5(20480, 30720, 40960, 180224, 190464), T_F = pk5(51200, 59648, 200192, 147456, 155904), T_X = pk5(208512, 164352, 68096, 208512, 164352),
                   T_P = pk5(131072, OFF_PB, 114688, 131072, OFF_PB);
__host__ __device__ __forceinline__ uint32_t tab(uint64_t t, int c) { return ((uint32_t)(t >> (12 * c)) & 0xFFF) << 7; }
enum { B_KV = 0, B_FRAW = 5, B_Q = 10, B_XR = 16, B_MR = B_XR + 5, B_QTOK, B_ST1, B_MODR, B_S3 = B_MODR + 5, B_FIN, B_FL = 32, B_PFULL = B_FL + 5, B_PEMPTY = B_PFULL + 5, B_FRDY = B_PEMPTY + 5,
       B_EXT = B_FRDY + 5, B_QTD, B_LAG, B_GB, B_UVD, B_TURN, B_FULL = 60, B_RETRY = B_FULL + 33, B_XFREE = B_RETRY + 9, B_BX, B_UVB, B_UVE, B_SX, B_EMPTY = 109 };
static_assert(B_MODR + 5 <= B_FL && B_UVD < B_FULL && B_SX + 2 == B_EMPTY - 1, "barrier groups");
#define BAR(i) (base + OFF_BAR + 8 * (i))

constexpr int NE = 18;
struct Maps { CUtensorMap km, v, q, kh, tap, wm, w1s, w3s, xs, w1, w3, w1e, w3e, x1s, x1b, w2a, w2b, outa, outb; };
struct Ptrs { const bf16 *ssmk, *c, *ssmd; Scratch* g; uint64_t prog, cprog[2]; int boff, te, pe, th, zero; uint32_t xd, aw, cn, c0, fin, turn, mr2, m3, seq; float one; uint2 sched[NE]; uint32_t wdep[20], wt[5]; uint2 w2t[12]; int hid[3][9]; };

#define REGION_IDS int tid, lane, bid; \
  asm volatile("mov.u32 %0, %%tid.x;" : "=r"(tid)); asm volatile("mov.u32 %0, %%laneid;" : "=r"(lane)); asm volatile("mov.u32 %0, %%ctaid.x;" : "=r"(bid)); \
  const int i0 = tid & 127; (void)i0; (void)lane; (void)bid

__device__ __forceinline__ void ffn_role(int& h, int& j, int& r) {
  uint32_t b;
  asm volatile("mov.u32 %0, %%ctaid.x;" : "=r"(b));
  const uint32_t c = b >> 1, q = (c - 36) * 37 >> 8, e = c - 36 - 7 * q;
  h = b & 1;
  const uint32_t k = c < 4 ? 0 : c < 36 ? (c - 4) & 7 : e + 1, p = c < 4 ? c : c < 36 ? (c - 4) >> 3 : q, up = c - 4 >= 32;
  j = 2 * (k & 1) + up;
  r = 2 * (k & 6) + p;
}
__device__ __forceinline__ int fslice(int j, int e) { return e == 2 ? j ^ 1 : (~j & 2) + e; }
__device__ __forceinline__ int mod_ch(int p) { return p < 40 ? (p >> 3) * 128 + (p & 1) * 64 : 64 * (p < 50 ? p - 40 : p - 50); }
__device__ __forceinline__ int mod_col(int p) { return mod_ch(p) + 640 * (p < 40 ? 0x4210 >> (2 * (p & 6)) & 7 : p < 50 ? 3 : 5); }
__device__ __forceinline__ uint32_t mod_sum(uint2 v) { return pack_bf16(0.f, __uint_as_float(v.x) + __uint_as_float(v.y)); }

constexpr int NT = 3, LAG2 = 29, MG = 4, NP = 1, P0 = 0, ST = 1, NB = 0, PA = 2, O3 = 0, O0 = 1, OS = 2;
__device__ __forceinline__ int w_block(int up, int m) { return m == 1 ? 2 + 3 * up : 3 * (m >> 1) + up; }
__host__ __device__ constexpr int w2_at(int v) { return 8192 * (v ? 0x0613030008ull >> v % 5 * 8 & 255 : 15); }
__host__ __device__ constexpr int w2_step(int v) { return 8192 * (v ? 0x32113 >> v % 5 * 4 & 15 : 1); }
__host__ __device__ constexpr int hid_at(int m, int g) { return 8192 * ((g ? 0x0D07110F1816ull : 0x0A19101A1412ull) >> m % 6 * 8 & 255); }
__host__ __device__ constexpr uint32_t w2_desc(int v) { return (DB + w2_at(v)) >> 4 | w2_step(v) << 12; }
__device__ __forceinline__ int next_slot(int s) { return s >= 4 * WSLOT ? 0 : s + WSLOT; }

template <int U> __device__ __forceinline__ void cstep(float* acc, const uint32_t* A, uint64_t db) {
  const uint32_t* a = A + 4 * U;
  const uint64_t d = db + 16 * U;
  if (U == 4) { wg_rs64_0(acc + 96, A, db + 192, 0); wg_rs48_0(acc + 96, A + 4, db + 208, 1); wg_rs32_0(acc + 96, A + 8, db + 224, 1); wg_rs16_0(acc + 96, A + 12, db + 240, 1); }
  if (U <= 4) wg_rs192_0(acc, a, d, U);
  if (U == 5) wg_rs176_0(acc, a, d, 1);
  if (U == 6) wg_rs160_0(acc, a, d, 1);
  if (U == 7) wg_rs144_0(acc, a, d, 1);
  if (U == 8) wg_rs128_0(acc, a, d, 1);
  if (U == 9) wg_rs112_0(acc, a, d, 1);
  if (U == 10) wg_rs96_0(acc, a, d, 1);
  if (U == 11) wg_rs80_0(acc, a, d, 1);
  if (U == 12) wg_rs64_0(acc, a, d, 1);
  if (U == 13) wg_rs48_0(acc, a, d, 1);
  if (U == 14) wg_rs32_0(acc, a, d, 1);
  if (U == 15) wg_rs16_0(acc, a, d, 1);
}
template <int U0, int U1> __device__ __forceinline__ void csteps(float* acc, const uint32_t* A, uint64_t db) {
  cstep<U0>(acc, A, db);
  if constexpr (U0 > U1) csteps<U0 - 1, U1>(acc, A, db);
}
template <int U0, int U1> __device__ __forceinline__ void cload(uint32_t* A, uint32_t fa) {
  asm volatile("{ld.shared.b32 %0, [%4+%5]; ld.shared.b32 %1, [%4+%5+128]; ld.shared.b32 %2, [%4+%5+16]; ld.shared.b32 %3, [%4+%5+144];}"
               : "=r"(A[4 * U0]), "=r"(A[4 * U0 + 1]), "=r"(A[4 * U0 + 2]), "=r"(A[4 * U0 + 3]) : "r"(fa), "n"(256 * U0) : "memory");
  if constexpr (U0 > U1) cload<U0 - 1, U1>(A, fa);
}

__device__ __forceinline__ uint2 c_load(const bf16* c) {
  REGION_IDS;
  return make_uint2(ldg32(c + 320 * (bid & 1) + 2 * i0), ldg32(c + 320 * (bid & 1) + 256 + 2 * lane));
}
__device__ __forceinline__ void silu_vector(uint2 c, uint32_t base) {
  REGION_IDS;
  sts32(base + OFF_CV + 4 * i0, pack_bf16(silu_f(bf_lo(c.x)), silu_f(bf_hi(c.x))));
  sts32(base + OFF_CV + 512 + 4 * lane, pack_bf16(silu_f(bf_lo(c.y)), silu_f(bf_hi(c.y))));
  fence_async_smem();
}

__device__ __forceinline__ void mod_poll(Scratch* G, uint32_t base, int c, int n, uint32_t epoch) {
  REGION_IDS;
  const int e = 4 * c + (lane & (4 * n - 1));
  uint2 m;
  int it = 0;
#pragma unroll 1
  do m = ld_relaxed64(&G->modc[bid][8 + e]); while (__any_sync(~0u, ((m.x ^ epoch) | (m.y ^ epoch)) & 1) && ++it < SPIN_LIMIT);
  sts32(base + OFF_MODR + 4 * e, __byte_perm(badd2(mod_sum(m), (lane & 1) * 0x3F800000u), 0, 0x3232));
  __syncwarp();
  if (elect()) { mbar_arrive(BAR(B_MODR + c)); if (n > 1) mbar_arrive(BAR(B_MODR + c + 1)); }
}
__device__ __forceinline__ void row_stats(Scratch* G, uint32_t base, uint32_t epoch) {
  REGION_IDS;
  mbar_wait_cluster(BAR(B_ST1));
  if (lane < 8) red_hint(G->hint[5][lane]);
  const uint2 x = lds64(base + OFF_ST + 8 * (lane & 15)), y = lds64(base + OFF_ST + 128 + 8 * (lane & 15));
  float m, sd;
  ln_final(__uint_as_float(x.x) + __uint_as_float(y.x), __uint_as_float(x.y) + __uint_as_float(y.y), m, sd);
  sd = rbf(rcpf(sd));
  const uint32_t mr = pack_bf16(sd, -rbf(m) * sd), tg = lane & 7 ? 0 : lane & 8 ? 1 : 0x8000;
  const uint32_t o = __byte_perm(__shfl_sync(~0u, mr, 2 * lane & 14), __shfl_sync(~0u, mr, (2 * lane & 14) + 1), (lane & 8) ? 0x7632 : 0x5410);
  if (lane < 16) st_relaxed32(&G->st1[lane >> 3][8 * bid + (lane & 7)], (o & ~tg) | ((epoch & 1) * tg));
  if (elect()) mbar_arrive(BAR(B_FIN));
}
template <int B, int NEXT> __device__ __forceinline__ void strip(Scratch* G, const CUtensorMap* map, uint32_t base, int c, uint32_t epoch, uint32_t& ph, uint32_t& pre, float4& s) {
  REGION_IDS;
  int h, j, r, it = 0;
  ffn_role(h, j, r);
  const uint32_t buf = base + OFF_SX + 4096 * B, a = buf + 32 * lane;
#pragma unroll 1
  while (__any_sync(~0u, pre != 64 * epoch) && ++it < SPIN_LIMIT) pre = ld_relaxed32(G->xsh[c][(r & 6) + (j >> 1)]);
#pragma unroll 1
  for (it = 0; it < SPIN_LIMIT; it++) {
    if (elect()) { mbar_expect_tx(BAR(B_SX + B), 4096); tma2d(buf, map, 128 * r + 64 * h, D_ * (epoch & 1) + 128 * c + 32 * j, BAR(B_SX + B)); }
    mbar_wait(BAR(B_SX + B), ph);
    ph ^= 1;
    if (__all_sync(~0u, min(min(lds32(a), lds32(a + 1024)), min(lds32(a + 2048), lds32(a + 3072))))) break;
  }
  pre = 0;
  if (c == NEXT - 1 || c == NEXT - 2) pre = ld_relaxed32(G->xsh[c + 1][(r & 6) + (j >> 1)]);
#pragma unroll 1
  for (uint32_t o = buf + 4 * lane; o < buf + 4096; o += 1024) {
    uint32_t x[8];
#pragma unroll
    for (int i = 0; i < 8; i++) x[i] = lds32(o + 128 * i);
#pragma unroll
    for (int i = 0; i < 8; i++) { const float lo = bf_lo(x[i]), hi = bf_hi(x[i]); s.x += lo; s.y = fmaf(lo, lo, s.y); s.z += hi; s.w = fmaf(hi, hi, s.w); }
  }
}
__device__ __forceinline__ void planes(uint32_t a, uint4& y) {
  uint4 z = lds128(a + 4096);
  y.x = badd2(y.x, z.x); y.y = badd2(y.y, z.y); y.z = badd2(y.z, z.z); y.w = badd2(y.w, z.w);
  z = lds128(a + 8192);
  const uint4 m = lds128(a + 12288);
  y.x = badd2(y.x, badd2(z.x, m.x)); y.y = badd2(y.y, badd2(z.y, m.y)); y.z = badd2(y.z, badd2(z.z, m.z)); y.w = badd2(y.w, badd2(z.w, m.w));
}
__device__ __forceinline__ void mr_poll(Scratch* G, uint32_t base, uint32_t epoch) {
  int it = 0;
#pragma unroll 1
  while (__any_sync(~0u, ld_relaxed32(G->hint[5][4 * (blockIdx.x >> 6) + (blockIdx.x >> 3 & 3)]) != epoch << 7) && ++it < SPIN_LIMIT);
  if (elect()) { mbar_expect_tx(BAR(B_MR), 8192); bulk_load(base + OFF_MR, G->st1, 8192, BAR(B_MR)); mbar_arrive(BAR(B_QTOK)); }
}

__global__ void __cluster_dims__(2, 1, 1) __launch_bounds__(512, 1) k_fused(const __grid_constant__ Ptrs P, const __grid_constant__ Maps maps) {
  Scratch* const G = P.g;
  extern __shared__ __align__(1024) uint8_t smem_raw[];
  const uint32_t t_start = clock();
  const uint32_t base = __shfl_sync(~0u, smem_u32(smem_raw), 0);
  uint32_t t_iss = 0;
  if (threadIdx.x < 32 && blockIdx.x < 128) {
    mbar_init<1>(BAR(0), 1);
    if (elect()) {
      const int c0 = 64 * (blockIdx.x & 1), c1 = 2 * (blockIdx.x & 126);
      mbar_expect_tx(BAR(B_KV), 12288);
      tma3d(base + tab(T_KV, 0), &maps.km, c0, c1, 0, BAR(B_KV));
      tma3d(base + tab(T_KV, 0) + KV_V, &maps.v, c0, c1, 0, BAR(B_KV));
      tma3d(base + tab(T_KV, 0) + KV_H, &maps.kh, c0, c1 - 1, 5, BAR(B_KV));
      tma3d(base + OFF_TAP, &maps.tap, 0, blockIdx.x & 1, 0, BAR(B_KV));
    }
    if (P.boff) mbar_wait(BAR(0));
  }
  if ((base & 0xFFFFFFu) != DB) __trap();
  const int wid = __shfl_sync(~0u, threadIdx.x >> 5, 0), wg = wid >> 2, w = wid & 3;
  if (blockIdx.x + P.boff >= 128) {
    REGION_IDS;
    constexpr int nu = 30;
    auto tile = [&](int n) { return 2 * n + (blockIdx.x >> 1 & 1); };
    auto fetch = [&](int n, int b) {
      if (elect()) {
        mbar_expect_tx(BAR(n), 40960);
#pragma unroll
        for (int k = 0; k < 5; k++) tma3d(base + 40960 * b + 8192 * k, &maps.wm, mod_col(tile(n)), 320 * (blockIdx.x & 1) + 64 * k, 0, BAR(n));
      }
    };
    if (P.boff) __syncthreads();
    if (wid == 12) {
      mbar_init<4>(BAR(0), 1);
#pragma unroll 1
      for (int n = 0; n < 4; n++) fetch(n, n);
      mbar_init<26>(BAR(4), 1);
      mbar_init<60>(BAR(32), 4);
    }
    const uint32_t par = ~ld_relaxed32(G->hint[7][0]) >> 7 & 1;
    silu_vector(c_load(P.c), base);
    __syncthreads();
    if (wid == 12) {
      wait_clock(t_start + P.th);
#pragma unroll 1
      for (int n = 4, b = 4; n < nu; n++) {
        if (n >= 5) mbar_wait(BAR(27 + n));
        fetch(n, b);
        b = b == 4 ? 0 : b + 1;
      }
    } else if (wg < 2) {
      uint32_t cv[40];
#pragma unroll
      for (int k = 0; k < 40; k++) cv[k] = lds32(base + OFF_CV + 16 * k + 4 * (lane & 3));
      const uint32_t a0 = base + 128 * ((lane & 7) + (lane >> 4) * 8) + (((2 * w + (lane >> 3 & 1)) ^ (lane & 7)) << 4);
#pragma unroll 1
      for (int n = wg; n < nu; n += 2) {
        float d[16] = {};
        mbar_wait(BAR(n));
#pragma unroll
        for (int k0 = 0; k0 < 20; k0 += 10) {
          uint32_t a[40];
#pragma unroll
          for (int k = 0; k < 10; k++) ldmatrix_x4_t(a + 4 * k, a0 + 40960 * (n % 5) + 2048 * (k0 + k));
#pragma unroll
          for (int k = 0; k < 10; k++)
            asm("mma.sync.aligned.m16n8k16.row.col.f32.bf16.bf16.f32 {%0,%1,%2,%3}, {%4,%5,%6,%7}, {%8,%9}, {%0,%1,%2,%3};"
                : "+f"(d[4 * (k & 3)]), "+f"(d[4 * (k & 3) + 1]), "+f"(d[4 * (k & 3) + 2]), "+f"(d[4 * (k & 3) + 3])
                : "r"(a[4 * k]), "r"(a[4 * k + 1]), "r"(a[4 * k + 2]), "r"(a[4 * k + 3]), "r"(cv[2 * (k0 + k)]), "r"(cv[2 * (k0 + k) + 1]));
        }
        arrive1(BAR(32 + n));
        if (!(lane & 3)) {
          sts32(base + 204800 + 256 * n + 64 * w + lane, __float_as_uint(d[0] + d[4] + (d[8] + d[12])));
          sts32(base + 204800 + 256 * n + 64 * w + lane + 32, __float_as_uint(d[2] + d[6] + (d[10] + d[14])));
        }
        arrive1(BAR(62 + n));
      }
    } else if (wg == 2) {
#pragma unroll 1
      for (int n = w; n < nu; n += 4) {
        const int t = tile(n), ch = mod_ch(t) + lane;
        uint32_t* q = (uint32_t*)(t < 40 ? &G->modc[ch & 127][8 + (t >> 1)] : &G->modv[t >= 50][ch]) + (bid & 1);
        mbar_wait(BAR(62 + n));
        const uint32_t x = (lds32(base + 204800 + 256 * n + 4 * lane) & ~1u) | par, y = (lds32(base + 204928 + 256 * n + 4 * lane) & ~1u) | par;
        publish(q, x);
        publish(q + (t < 40 ? 2048 : 64), y);
        if (t < 40 && (t & 6) == 6) {
          q = (uint32_t*)&G->modv[2][ch] + (bid & 1);
          publish(q, x);
          publish(q + 64, y);
        }
      }
    }
    return;
  }
  if (wid < 15) mbar_init<4>(BAR(4 * wid + (wid == 0)), wid < 8 ? 1 : 4);
  asm volatile("fence.mbarrier_init.release.cluster; bar.sync 0, 512;" ::: "memory");
  asm volatile("barrier.cluster.arrive.relaxed.aligned;" ::: "memory");
  if (wid == 4) {
    const int c0 = 64 * (blockIdx.x & 1), c1 = 2 * (blockIdx.x & 126);
    wait_clock(t_start + P.te);
    if (elect()) { tma3d(base + tab(T_KV, 1), &maps.km, 128 + c0, c1, 0, BAR(B_KV + 1)); tma3d(base + tab(T_KV, 1) + KV_H, &maps.kh, 128 + c0, c1 - 1, 5, BAR(B_KV + 1)); }
    wait_clock(t_start + P.te + P.pe);
    if (elect()) tma3d(base + tab(T_KV, 1) + KV_V, &maps.v, 128 + c0, c1, 0, BAR(B_KV + 1));
    wait_clock(t_start + P.te + 2 * P.pe);
    if (elect()) bulk_load(base + tab(T_F, 0) + F_E, P.ssmk + blockIdx.x * S_, 4096, BAR(B_FRAW));
    wait_clock(t_start + P.te + 3 * P.pe);
    if (elect()) tma3d(base + OFF_Q, &maps.q, c0, c1, 0, BAR(B_Q));
  }
#define LAUNCHES const uint32_t launches = ld_relaxed32(G->hint[7][blockIdx.x >> 4])
#define EPOCH ((__shfl_sync(~0u, launches, 0) >> 7) + 1)
  if (wg == 3) {
    asm volatile("setmaxnreg.dec.sync.aligned.u32 24;");
    if (w == 1) {
      {
        LAUNCHES;
        REGION_IDS;
        const int c1 = 2 * (bid & 126);
#pragma unroll 1
        for (int e = 4; e < NE; e++) {
          const uint2 x = P.sched[e];
          const uint32_t kind = x.x >> 16 & 15, ch = x.x >> 13 & 0x380, dst = base + (x.y & 0x3FFFF), b = BAR(x.y >> 18);
          wait_clock(t_start + (x.x & 0xFFFF));
          if (kind < 3 && elect()) tma3d(dst, &maps.km + kind, ch + 64 * (bid & 1), c1, 0, b);
          if (kind == 0 && elect()) tma3d(dst + KV_H, &maps.kh, ch + 64 * (bid & 1), c1 - 1, 5, b);
          if (kind == 3 && elect()) bulk_load(dst, P.ssmk + (ch + bid) * S_, 4096, b);
        }
        if (P.mr2 == 2) mr_poll(G, base, EPOCH);
      }
      cluster_wait();
      int h, j, r;
      ffn_role(h, j, r);
      mbar_wait(BAR(B_QTD));
      mbar_wait(BAR(B_FL));
#pragma unroll 1
      for (int u = 0; u < 20; u++) {
        const uint32_t x = P.wdep[u], s = base + (x & ~8191u);
        if (u < 5) wait_clock(t_start + P.wt[u]);
        mbar_wait(BAR(opaque(x & 255)));
        if (elect()) {
          mbar_expect_tx(BAR(B_FULL + u), WSLOT + 4 * (x & 4096));
#pragma unroll
          for (int k = 0; k < 6; k++) tma3d(s + 4096 * w_block(k & 1, k >> 1), &maps.w1s + (k & 1), 0, 32 * u, 3 * (4 * h + j) + (k >> 1), BAR(B_FULL + u));
        }
      }
#pragma unroll 1
      for (int v = 0; v < 12; v++) {
        const int q = v * 11 >> 5, e = v - 3 * q, k32 = 24 * h + (q ? 6 * fslice(j, e) + 2 * q - 2 : 6 * j + 2 * e);
        const uint2 x = P.w2t[v];
        mbar_wait(BAR(x.y));
        if (elect()) {
          mbar_expect_tx(BAR(B_FULL + 20 + v), q ? WSLOT + 2 * ASLOT : WSLOT);
#pragma unroll
          for (int k = 0; k < 3; k++) tma5d(base - DB + 16 * ((x.x & 0xFFFF) + k * (x.x >> 16)), &maps.w2a + (q > 0), k < 2 ? 128 * j + 64 * k : 512 + 32 * (j & 2), k32, BAR(B_FULL + 20 + v));
        }
      }
    } else if (w == 0) {
      LAUNCHES;
      uint32_t epoch;
      {
        REGION_IDS;
        const unsigned* hp = G->hint[0][4 * (bid >> 6) + (bid >> 3 & 3)];
        uint32_t v = ld_relaxed32(hp + 256 * min(lane, 5));
        if (lane < 3) sts128(base + tab(T_X, lane) + 4096, 0, 0, 0, 0);
        if (lane && lane < B_Q + 5) mbar_expect_tx(BAR(lane), lane < B_FRAW ? 9728 : 4096);
        epoch = EPOCH;
        fence_async_smem();
        const uint32_t rdy = __ballot_sync(~0u, v == epoch << 6);
        uint32_t nx = 0, nm = 0;
#pragma unroll 1
        for (uint32_t seq = P.seq; seq; seq >>= 2) {
          int it = 0;
          if (seq & 1) {
            if (!(seq & 2)) mod_poll(G, base, nm, 1 + (seq == 13), epoch);
            nm++;
          } else if (seq & 2) {
            mr_poll(G, base, epoch);
          } else {
            if (!(rdy >> nx & 1)) {
#pragma unroll 1
              while (__any_sync(~0u, ld_relaxed32(hp + 256 * nx) != epoch << 6) && ++it < SPIN_LIMIT);
            }
            wait_clock(clock() + P.xd);
            if (nx >= 3) mbar_wait(BAR(B_PFULL - 3 + nx));
            if (elect()) { mbar_expect_tx(BAR(B_XR + nx), 4096); bulk_load(base + tab(T_X, nx), G->xr + (128 * nx + bid) * 256, 4096, BAR(B_XR + nx)); }
            nx++;
          }
        }
      }
      REGION_IDS;
      int h, j, r;
      ffn_role(h, j, r);
      mbar_wait(BAR(B_PFULL + 3));
      {
        float4 s = {};
        uint32_t ph = 0, pre = 0;
#pragma unroll 1
        for (int c = 2; c < 4; c++) strip<1, 3>(G, &maps.x1s, base, c, epoch, ph, pre, s);
        __syncwarp();
        sts128(base + OFF_SX + 4096 + 16 * lane, __float_as_uint(s.x), __float_as_uint(s.y), __float_as_uint(s.z), __float_as_uint(s.w));
        arrive1(BAR(B_S3));
      }
      ffn_role(h, j, r);
      cluster_wait();
      mbar_wait(BAR(B_UVD));
      asm volatile("fence.acq_rel.gpu;" ::: "memory");
      if (lane < 8) red_hint(G->hint[7][lane]);
      unsigned x;
      int it = 0;
#pragma unroll 1
      do { asm volatile("ld.acquire.gpu.global.u32 %0, [%1];" : "=r"(x) : "l"(G->hint[7][bid >> 4]) : "memory"); } while (__any_sync(~0u, x != 128 * epoch) && ++it < SPIN_LIMIT);
      fence_async_all();
      const int ch = D_ * (epoch & 1);
      mbar_wait(BAR(B_EXT));
      mbar_wait(BAR(B_EMPTY + 18));
      if (elect()) {
        mbar_expect_tx(BAR(B_FULL + 32), 20480);
#pragma unroll
        for (int k = 0; k < 4; k++) tma2d(base + (k < 3 ? OFF_X1 + k * WSLOT : OFF_SX), &maps.x1b, 128 * r + 64 * h, ch + 128 * j + 32 * (k ^ (j & 1)), BAR(B_FULL + 32));
        tma2d(base + OFF_SX + 4096, &maps.x1b, 128 * r + 64 * h, ch + 512 + 32 * j, BAR(B_FULL + 32));
        mbar_expect_tx(BAR(B_FULL), 8192); mbar_expect_tx(BAR(B_FULL + 1), 8192); mbar_expect_tx(BAR(B_FULL + 2), 4096);
      }
      mbar_wait(BAR(B_EMPTY + 27));
      if (elect()) mbar_arrive_remote(mapa(BAR(B_XFREE), h ^ 1));
    } else {
      LAUNCHES;
      uint32_t epoch;
      {
        REGION_IDS;
        uint32_t dv;
        asm volatile("ld.global.nc.u16 %0, [%1];" : "=r"(dv) : "l"(P.ssmd + 128 * (lane & 7) % D_ + bid));
        if (lane < 5) sts128(base + tab(T_F, lane) + (w & 1) * (F_O - 16), 0, 0, 0, 0);
        epoch = EPOCH;
        __syncwarp();
#pragma unroll 1
        for (int c = 0; c < 5; c++) {
          const float d = i0 == 64 ? bf_lo(dv) : 0.f;
          dv = __shfl_down_sync(~0u, dv, 1);
          const uint32_t a = base + tab(T_F, c) + 16 * (i0 - 64);
          mbar_wait(BAR(B_FRAW + c));
#pragma unroll
          for (int k = 0; k < 4; k++) {
            uint4 x = lds128(a + F_E + 1024 * k);
            const uint32_t pv = lds32(a + F_E - 4 + 1024 * k);
            if (k == 0) { x.x = pack_bf16(bf_lo(x.x) + d, bf_hi(x.x)); sts32(a + F_E, x.x); }
            sts128(a + F_O + 1024 * k, __byte_perm(pv, x.x, 0x5432), __byte_perm(x.x, x.y, 0x5432), __byte_perm(x.y, x.z, 0x5432), __byte_perm(x.z, x.w, 0x5432));
          }
          __syncwarp();
          if (elect()) mbar_arrive2(BAR(B_FRDY + c));
          if (c == 0 && w == P.fin) row_stats(G, base, epoch);
        }
      }
      REGION_IDS;
      int h, j, r;
      ffn_role(h, j, r);
      cluster_wait();
      if (w == 2) {
        uint32_t rdy = 0, s = 0;
        mbar_wait(BAR(B_QTD));
        mbar_wait(BAR(B_FL + 2));
#pragma unroll 1
        for (int n = 0; n < 10; n++) {
          if (n == P.cn) {
            mbar_wait(BAR(B_PEMPTY + 3));
            if (elect()) {
              tma3d(base + OFF_UV, &maps.w1 + (r & 1), 0, 40 * (r & 14), 3 * (4 * h + j), BAR(B_UVB));
              tma3d(base + OFF_UV + 12288, &maps.w1 + (r & 1), 0, 40 * (r & 14) + 32, 3 * (4 * h + j), BAR(B_UVB));
            }
            {
              const uint2* mp = &G->modv[lane & 4 ? 0 : 2][40 * (r & 14) + (lane & 24) + 2 * (lane & 3)];
              uint4 v[3];
              int it = 0;
#pragma unroll 1
              do {
                v[0] = ld_relaxed128(mp); v[1] = ld_relaxed128(mp + 32); v[2] = ld_relaxed128(mp + 64 - (lane & 16));
              } while (__any_sync(~0u, ((v[0].x ^ epoch) | (v[0].y ^ epoch) | (v[0].z ^ epoch) | (v[0].w ^ epoch) | (v[1].x ^ epoch) | (v[1].y ^ epoch) | (v[1].z ^ epoch) | (v[1].w ^ epoch) |
                                        (v[2].x ^ epoch) | (v[2].y ^ epoch) | (v[2].z ^ epoch) | (v[2].w ^ epoch)) & 1) && ++it < SPIN_LIMIT);
#pragma unroll
              for (int i = 0; i < 3; i++)
                sts32(base + OFF_CO + 128 * i + 4 * lane, badd2(pack_bf16(__uint_as_float(v[i].x) + __uint_as_float(v[i].y), __uint_as_float(v[i].z) + __uint_as_float(v[i].w)), lane & 4 ? 0 : 0x3F803F80u));
            }
            fence_async_smem();
            __syncwarp();
            if (elect()) mbar_expect_tx(BAR(B_UVB), WSLOT);
          }
          mbar_wait(BAR(n < 2 ? B_FL + 3 + n : n == 2 ? B_PFULL + 4 : B_EMPTY + 2 * n - 5));
#pragma unroll 1
          for (int it = 0; !(rdy >> n & 1) && it < SPIN_LIMIT; it++) rdy = __ballot_sync(~0u, ld_relaxed32(G->xsh[min(lane >> 1, n ? 4 : P.aw)][(r & 6) + (lane & 1)]) == 64 * epoch) & (n ? ~0u : (4u << 2 * P.aw) - 1);
          if (elect()) {
            tma2d(base + OFF_A + s, &maps.xs, 128 * r + 64 * h, 64 * n, BAR(B_FULL + 2 * n));
            tma2d(base + OFF_A + ARING + s, &maps.xs, 128 * r + 64 - 64 * h, 64 * n, BAR(B_FULL + 2 * n));
          }
          s = s == 2 * ASLOT ? 0 : s + ASLOT;
        }
      } else {
        if (P.m3 < 5) mod_poll(G, base, P.m3, 1, epoch);
        float4 s = {};
        uint32_t ph = 0, pre = 0;
        mbar_wait(BAR(B_FL + 2));
        mbar_wait(BAR(B_PFULL + 3));
#pragma unroll 1
        for (int c = 0; c < 5; c = c == 1 ? 4 : c + 1) {
          if (c == 4) {
            ffn_role(h, j, r);
            mbar_wait(BAR(B_PEMPTY + 4));
            if (elect()) {
              mbar_expect_tx(BAR(B_UVE), 6144);
              tma3d(base + OFF_UVE, &maps.w1e + (r & 1), 0, 40 * (r & 14) + 64, 3 * (4 * h + j), BAR(B_UVE));
            }
          }
          strip<0, 1>(G, &maps.x1s, base, c, epoch, ph, pre, s);
        }
        mbar_wait(BAR(B_S3));
        const uint4 y = lds128(base + OFF_SX + 4096 + 16 * lane);
        const float s0 = s.x + __uint_as_float(y.x), q0 = s.y + __uint_as_float(y.y), s1 = s.z + __uint_as_float(y.z), q1 = s.w + __uint_as_float(y.w);
        ffn_role(h, j, r);
        asm volatile("{.reg .b128 t, x; .reg .b64 a, b; mov.b64 a, {%1,%2}; mov.b64 b, {%3,%4}; mov.b128 x, {a,b}; atom.relaxed.gpu.global.exch.b128 t, [%0], x;}"
                     ::"l"(&G->st2[2 * r + h][j][4 * lane]), "r"((__float_as_uint(s0) & ~1u) | (epoch & 1)), "f"(q0), "r"((__float_as_uint(s1) & ~1u) | (epoch & 1)), "f"(q1) : "memory");
        uint4* z = G->x1[~epoch & 1] + 1280 * bid + lane;
#pragma unroll 1
        for (int k = 0; k < 40; k++) st_relaxed128(z + 32 * k, 0, 0, 0, 0);
      }
    }
  } else if (wg == 2) {
    asm volatile("setmaxnreg.dec.sync.aligned.u32 40;");
    mbar_init<12>(BAR(B_FULL + 12 * w), 1);
    mbar_init<9>(BAR(B_EMPTY - 1 + 9 * w), 8);
    asm volatile("fence.mbarrier_init.release.cluster;" ::: "memory");
    LAUNCHES;
    const uint32_t epoch = EPOCH;
    cluster_wait();
#pragma unroll 1
    for (uint64_t prog = P.prog; prog; prog >>= 4) {
      REGION_IDS;
      const int s = (prog & 7) - 1;
      if (!(prog & 8)) {
        const uint32_t a = base + tab(T_KV, s) + 128 * (lane & 3) + ((w ^ (lane & 3)) << 4) + 4 * (lane & 16) + (lane & 12), keep = ~(lane & 1), bit = epoch & lane & 1;
        uint4* dst = G->xr + (128 * s + 64 * (bid & 1) + 8 * w + 2 * (lane & 16) + (lane >> 1 & 6)) * 256 + 255 - 4 * (bid >> 1) - (lane & 3);
        mbar_wait(BAR(B_KV));
        mbar_wait(BAR(B_KV + s));
        const uint4 wv = lds128(base + OFF_TAP + 512 * s + 64 * w + 16 * (lane & 16) + 4 * (lane & 12));
        uint32_t kk[11], r[8];
#pragma unroll
        for (int k = 0; k < 11; k++) kk[k] = k < 3 ? lds32((a ^ (64 * (k & 1))) + KV_H + 512 * k) : lds32((a ^ (64 * (~k & 1))) + 512 * (k - 3));
        if (elect()) red_hint(G->hint[s][4 * (bid & 1) + w]);
#pragma unroll
        for (int k = 0; k < 8; k++) r[k] = lds32((a ^ (64 * (k & 1))) + KV_V + 512 * k);
        const uint32_t w0 = __byte_perm(wv.x, wv.z, 0x5410), w1 = __byte_perm(wv.x, wv.z, 0x7632),
                       w2 = __byte_perm(wv.y, wv.w, 0x5410), w3 = __byte_perm(wv.y, wv.w, 0x7632);
#pragma unroll
        for (int k = 0; k < 8; k++) r[k] = bmul2(bfma2(kk[k + 3], w0, bfma2(kk[k + 2], w1, bfma2(kk[k + 1], w2, bmul2(kk[k], w3)))), r[k]);
        st_relaxed128(dst, (__byte_perm(r[7], r[6], 0x5410) & keep) | bit, __byte_perm(r[5], r[4], 0x5410), __byte_perm(r[3], r[2], 0x5410), __byte_perm(r[1], r[0], 0x5410));
        st_relaxed128(dst + 256, (__byte_perm(r[7], r[6], 0x7632) & keep) | bit, __byte_perm(r[5], r[4], 0x7632), __byte_perm(r[3], r[2], 0x7632), __byte_perm(r[1], r[0], 0x7632));
      } else if (s == 5) {
        mbar_wait(BAR(B_PFULL));
#pragma unroll
        for (int hf = 0; hf < 2; hf++) {
          const uint32_t a = base + tab(T_P, 0) + 16 * i0 + 2048 * hf;
          uint4 y = lds128(a);
          planes(a, y);
          sts128(a, y.x, y.y, y.z, y.w);
        }
      } else if (s >= 0) {
        const int tr = 4 * (lane & 1) + (lane >> 1 & 3);
        const uint32_t a = base + OFF_Q + 4096 * s + 128 * ((lane & 24) + tr) + ((w ^ tr) << 4);
        uint4* dst = G->qt + (128 * s + 64 * (bid & 1) + 8 * w + (lane >> 2)) * 256 + 4 * (bid >> 1) + (lane & 3);
        mbar_wait(BAR(B_Q + s));
#pragma unroll
        for (int k = 0; k < 2; k++) {
          uint32_t x[4];
          ldmatrix_x4_t(x, a ^ (64 * k));
          st_relaxed128(dst + 8192 * k, set_tag(x[0], ~lane & 1, epoch), x[1], x[2], x[3]);
        }
      } else if (w == 3) {
        row_stats(G, base, epoch);
      }
    }
    arrive1(BAR(B_QTD));
    {
      REGION_IDS;
      const uint32_t tag = opaque(~lane & 1);
      const uint32_t io = 16 * i0;
      uint4* gp = (uint4*)((char*)(G->xs + 256 * blockIdx.x) + io);
      constexpr int QO = -D_ * 256;
      const uint32_t sa = base + io;
      uint4 q[2];
      if (w == 0 && P.mr2 == 1) mr_poll(G, base, epoch);
      mbar_wait(BAR(B_QTOK));
      q[0] = ld_relaxed128(gp + QO);
      q[1] = ld_relaxed128(gp + QO + 128);
#pragma unroll 1
      for (int it = 0; it < SPIN_LIMIT; it++) {
        mbar_wait(BAR(B_MR), it & 1);
        const uint32_t x = lds32(sa + 16 * i0 + OFF_MR), y = lds32(sa + 16 * i0 + OFF_MR + 4096);
        sts32(sa + 16 * i0 + OFF_MR, x & 0xFFFF7FFFu);
        if (bar_all(3, !(((x >> 15 ^ epoch) | (y ^ epoch)) & 1))) break;
        if (w == 0 && elect()) { fence_async_smem(); mbar_expect_tx(BAR(B_MR), 8192); bulk_load(base + OFF_MR, G->st1, 8192, BAR(B_MR)); }
      }
#pragma unroll 1
      for (int c = 0; c < 5; c++) {
        mbar_wait(BAR(B_MODR + c));
        uint4 co = lds128(base + OFF_MODR + 16 * c);
        co.x = bmul2(co.x, co.z); co.y = bmul2(co.y, co.z);
        mbar_wait(BAR(B_PFULL + c));
        const uint32_t pb = io + (base + tab(T_P, c));
        gp = (uint4*)((char*)(G->xs + 256 * blockIdx.x + 32768 * c) + io);
#pragma unroll
        for (int hf = 0; hf < 2; hf++) {
#pragma unroll 1
          for (int it = 0; __any_sync(~0u, set_tag(q[hf].x, tag, epoch) != q[hf].x) && it < SPIN_LIMIT; it++) {
            q[hf] = ld_relaxed128(gp + QO + 128 * hf);
          }
          uint4 y = lds128(pb + 2048 * hf);
          if (c) planes(pb + 2048 * hf, y);
          const uint4 z = lds128(sa + OFF_MR + 2048 * hf), m = lds128(sa + OFF_MR + 2048 * hf + 4096);
          y.x = bfma2(bfma2(bfma2(q[hf].x, z.x, m.x), co.y, co.x), y.x, q[hf].x);
          if (hf) {
            __syncwarp();
            asm volatile("{.reg .pred p; elect.sync _|p, 0xffffffff; @p red.relaxed.gpu.global.add.u32 [%0], 1; @p mbarrier.arrive.shared::cta.b64 _, [%1];}"
                         ::"l"(G->xsh[c][2 * w + (blockIdx.x >> 6)]), "r"(BAR(B_PEMPTY + c)), "r"(y.x) : "memory");
          }
          y.y = bfma2(bfma2(bfma2(q[hf].y, z.y, m.y), co.y, co.x), y.y, q[hf].y);
          y.z = bfma2(bfma2(bfma2(q[hf].z, z.z, m.z), co.y, co.x), y.z, q[hf].z);
          y.w = bfma2(bfma2(bfma2(q[hf].w, z.w, m.w), co.y, co.x), y.w, q[hf].w);
          st_relaxed128(gp + 128 * hf, set_tag(bmul2(y.x, co.w), tag, epoch), bmul2(y.y, co.w), bmul2(y.z, co.w), bmul2(y.w, co.w));
          asm volatile("{.reg .pred p; .reg .b32 t; setp.ne.u32 p, %5, 0; max.u32 t, %1, 1; @!p st.relaxed.gpu.global.v4.u32 [%0+%6], {t,%2,%3,%4}; @p st.relaxed.gpu.global.v4.u32 [%0+%7], {t,%2,%3,%4};}"
                       ::"l"(gp + 128 * hf), "r"(y.x), "r"(y.y), "r"(y.z), "r"(y.w), "r"(epoch & 1), "n"(D_ * 4096), "n"(D_ * 8192) : "memory");
          if (c < 4) q[hf] = ld_relaxed128(gp + QO + 32768 + 128 * hf);
        }
      }
    }
    int h, j, r;
    ffn_role(h, j, r);
    {
      REGION_IDS;
      mbar_wait(BAR(B_UVB));
      float d[12] = {};
      fence_regs(d);
      wg_fence();
#pragma unroll
      for (int k = 0; k < 15; k++) {
        if (k == 12) { wg_commit(); mbar_wait(BAR(B_UVE)); wg_fence(); }
        wg_ss8_10(d + 4 * (k % 3), mkdesc(DB + (k < 12 ? OFF_UV + 12288 * (k / 6) + 4096 * (k % 3) + 2048 * (k / 3 & 1) : OFF_UVE + 2048 * (k % 3)), 16, 1024, 1),
                  mkdesc(DB + OFF_CO + 64 * (k / 3), 32, 128, 0), 1);
      }
      wg_commit();
      const int row = (r & 14) + (lane >> 2 & 1);
      uint32_t* dst = &G->uv[4 * h + j][32 * row + 4 * ((2 * w ^ row) & 6) + (lane & 3)];
      const uint32_t tag = !(lane & 3);
      wg_wait<0>();
      fence_regs(d);
      if (elect()) { red_hint(G->hint[8][4 * h + j]); mbar_arrive(BAR(B_UVD)); }
      uint32_t x[6];
#pragma unroll
      for (int k = 0; k < 6; k++) asm volatile("movmatrix.sync.aligned.m8n8.trans.b16 %0, %1;" : "=r"(x[k]) : "r"(pack_bf16(d[2 * k], d[2 * k + 1])));
      if (lane < 8) {
#pragma unroll
        for (int k = 0; k < 6; k++) st_relaxed32(dst + 512 * w_block(r & 1, k >> 1) + ((4 * k ^ lane) & 4), set_tag(x[k], tag, epoch));
      }
    }
    {
      REGION_IDS;
      if (w == 0) {
        int it = 0;
#pragma unroll 1
        while (__any_sync(~0u, ld_relaxed32(G->hint[8][4 * h + j]) != 64 * epoch) && ++it < SPIN_LIMIT);
        if (elect()) { mbar_expect_tx(BAR(B_BX), 12288); bulk_load(base + OFF_BX, G->uv[4 * h + j], 12288, BAR(B_BX)); }
      }
      const uint32_t* sp = &G->st2[2 * r + (h ^ (w >> 1))][0][2 * (i0 & 63)];
      uint2 x[4];
      int it = 0;
#pragma unroll 1
      do {
#pragma unroll
        for (int k = 0; k < 4; k++) x[k] = ld_relaxed64(sp + 128 * k);
      } while (__any_sync(~0u, ((x[0].x ^ epoch) | (x[1].x ^ epoch) | (x[2].x ^ epoch) | (x[3].x ^ epoch)) & 1) && ++it < SPIN_LIMIT);
      float m, sd;
      ln_final((__uint_as_float(x[0].x) + __uint_as_float(x[1].x)) + (__uint_as_float(x[2].x) + __uint_as_float(x[3].x)),
               (__uint_as_float(x[0].y) + __uint_as_float(x[1].y)) + (__uint_as_float(x[2].y) + __uint_as_float(x[3].y)), m, sd);
      const uint32_t e = pack_bf16(-m, sd);
      sts128(base + OFF_AX + 16 * i0, e, e, e, e);
      sts32(base + OFF_RT + 4 * i0, __float_as_uint(rcpf(sd)));
      fence_async_smem();
#pragma unroll 1
      for (it = 0; it < SPIN_LIMIT; it++) {
        mbar_wait(BAR(B_BX), it & 1);
        uint32_t y = 0;
#pragma unroll
        for (int k = 0; k < 6; k++) y |= lds32(base + OFF_BX + 16 * i0 + 2048 * k) ^ epoch;
        if (bar_all(3, !(y & 1))) break;
        if (w == 0 && elect()) { mbar_expect_tx(BAR(B_BX), 12288); bulk_load(base + OFF_BX, G->uv[4 * h + j], 12288, BAR(B_BX)); }
      }
      arrive1(BAR(B_EXT));
      {
        uint2 g0, g1;
        int it = 0;
#pragma unroll 1
        do {
          g0 = ld_relaxed64(&G->modv[1][128 * j + i0]);
          g1 = ld_relaxed64(&G->modv[1][512 + 32 * j + lane]);
        } while (__any_sync(~0u, ((g0.x ^ epoch) | (g0.y ^ epoch) | (g1.x ^ epoch) | (g1.y ^ epoch)) & 1) && ++it < SPIN_LIMIT);
        const uint32_t ga = base + OFF_GB + 80 * (lane >> 1 & 3) + 2 * (lane & 1) + (lane >> 3) * 4;
        asm volatile("st.shared.u16 [%0], %1;" ::"r"(ga + 16 * (w ^ (j & 1))), "h"((uint16_t)(mod_sum(g0) >> 16)) : "memory");
        asm volatile("st.shared.u16 [%0], %1;" ::"r"(ga + 64), "h"((uint16_t)(mod_sum(g1) >> 16)) : "memory");
        arrive1(BAR(B_GB));
      }
      const int id = 16 * r + 4 * h + fslice(j, w);
      const unsigned* fp = &G->hhf[8 * id + 64 * (lane & 1)];
#pragma unroll 1
      for (int q = w == 3 ? 3 : 0; q < 3; q++) {
        const int m = 3 * q + w;
        const uint4* src = G->hh + id * 1536 + 512 * q;
        it = 0;
#pragma unroll 1
        while (__any_sync(~0u, ld_relaxed32(fp + q) != 4 * epoch) && ++it < SPIN_LIMIT);
        mbar_wait(BAR(P.hid[2][m]));
        if (elect()) {
          bulk_load(base + OFF_A + h * ARING + P.hid[h][m], src, ASLOT, BAR(B_FULL + 23 + m));
          bulk_load(base + OFF_A + ARING - h * ARING + P.hid[h ^ 1][m], src + 8 * 1536, ASLOT, BAR(B_FULL + 23 + m));
        }
      }
    }
  } else {
    asm volatile("setmaxnreg.inc.sync.aligned.u32 224;");
    LAUNCHES;
    uint32_t par = EPOCH & 1;
    cluster_wait();
    uint32_t ck = 0;
    {
      float acc[128];
      uint32_t A[64];
#pragma unroll
      for (int i = 0; i < 64; i++) A[i] = 0;
      int c = wg;
#pragma unroll 1
      for (uint64_t prog = P.cprog[wg]; prog; prog >>= 8) {
        REGION_IDS;
        const int s = prog & 7;
        if (s < 5) {
          const uint32_t a = base + tab(T_KV, s) + 128 * (lane & 3) + ((w ^ (lane & 3)) << 4) + 4 * (lane & 16) + (lane & 12), keep = ~(lane & 1), bit = par & lane;
          uint4* dst = G->xr + (128 * s + 64 * (bid & 1) + 8 * w + 2 * (lane & 16) + (lane >> 1 & 6)) * 256 + 255 - 4 * (bid >> 1) - (lane & 3);
          mbar_wait(BAR(B_KV));
          mbar_wait(BAR(B_KV + s));
          const uint4 wv = lds128(base + OFF_TAP + 512 * s + 64 * w + 16 * (lane & 16) + 4 * (lane & 12));
          uint32_t kk[11], r[8];
#pragma unroll
          for (int k = 0; k < 11; k++) kk[k] = k < 3 ? lds32((a ^ (64 * (k & 1))) + KV_H + 512 * k) : lds32((a ^ (64 * (~k & 1))) + 512 * (k - 3));
          if (elect()) red_hint(G->hint[s][4 * (bid & 1) + w]);
#pragma unroll
          for (int k = 0; k < 8; k++) r[k] = lds32((a ^ (64 * (k & 1))) + KV_V + 512 * k);
          const uint32_t w0 = __byte_perm(wv.x, wv.z, 0x5410), w1 = __byte_perm(wv.x, wv.z, 0x7632),
                         w2 = __byte_perm(wv.y, wv.w, 0x5410), w3 = __byte_perm(wv.y, wv.w, 0x7632);
#pragma unroll
          for (int k = 0; k < 8; k++) r[k] = bmul2(bfma2(kk[k + 3], w0, bfma2(kk[k + 2], w1, bfma2(kk[k + 1], w2, bmul2(kk[k], w3)))), r[k]);
          st_relaxed128(dst, (__byte_perm(r[7], r[6], 0x5410) & keep) | bit, __byte_perm(r[5], r[4], 0x5410), __byte_perm(r[3], r[2], 0x5410), __byte_perm(r[1], r[0], 0x5410));
          st_relaxed128(dst + 256, (__byte_perm(r[7], r[6], 0x7632) & keep) | bit, __byte_perm(r[5], r[4], 0x7632), __byte_perm(r[3], r[2], 0x7632), __byte_perm(r[1], r[0], 0x7632));
        }
        if (prog & 8) {
          float s0 = 0.f, s1 = 0.f, q0 = 0.f, q1 = 0.f;
          const uint32_t a = OFF_Q + 1024 * w + 128 * (lane & 7) + (((lane >> 3) ^ (lane & 7)) << 4);
          const uint32_t ra = mapa(base + OFF_ST + 128 * (bid & 1) + 64 * (lane & 1) + 16 * w + 8 * (lane >> 2), lane >> 1 & 1), rb = mapa(BAR(B_ST1), lane >> 1 & 1);
          if (w == 3 && elect()) mbar_expect_tx(BAR(B_ST1), 256);
#pragma unroll 1
          for (int k = 0; k < 5; k++) {
            mbar_wait(BAR(B_Q + k));
            const uint32_t o = opaque(base + 4096 * k);
            const uint4 x = lds128(o + a), y = lds128(o + (a ^ 64));
            const uint32_t e[8] = {x.x, x.y, x.z, x.w, y.x, y.y, y.z, y.w};
#pragma unroll
            for (int i = 0; i < 8; i++) { const float lo = bf_lo(e[i]), hi = bf_hi(e[i]); s0 += lo; s1 += hi; q0 = fmaf(lo, lo, q0); q1 = fmaf(hi, hi, q1); }
          }
          s0 += s1; q0 += q1;
          s0 += __shfl_xor_sync(~0u, s0, 8); q0 += __shfl_xor_sync(~0u, q0, 8);
          s0 += __shfl_xor_sync(~0u, s0, 16); q0 += __shfl_xor_sync(~0u, q0, 16);
          if (lane < 8) asm volatile("st.async.shared::cluster.mbarrier::complete_tx::bytes.v2.b32 [%0], {%1,%2}, [%3];" ::"r"(ra), "r"(__float_as_uint(s0)), "r"(__float_as_uint(q0)), "r"(rb) : "memory");
        }
        if (prog & 32) {
          const int L = 16 * w + (lane >> 2) + 2 * (lane & 3) - 7;
          const uint32_t fo = base + ((L & 1) ? F_O + 2 * (L + 1) : F_E + 2 * L);
          mbar_wait(BAR(B_FRDY + c));
          cload<0, 0>(A, fo + tab(T_F, c));
          cload<15, 1>(A, fo + tab(T_F, c));
          arrive1(BAR(B_FL + c));
        }
        if (!(prog & 64)) continue;
        uint32_t xo;
        if (P.turn >> c & 1) mbar_wait(BAR(B_TURN - 3 + c));
        if (c == 0) mbar_wait(BAR(P.c0));
#pragma unroll 1
        for (int it = 0; it < SPIN_LIMIT; it++) {
          xo = tab(T_X, opaque(c));
          mbar_wait(BAR(B_XR + c), it & 1);
          const uint32_t tag = lds32(base + xo + 32 * i0);
          wg_fence();
          csteps<0, 0>(acc, A, mkdesc(DB + xo, 16, 128, 0));
          csteps<15, 6>(acc, A, mkdesc(DB + xo, 16, 128, 0));
          wg_commit();
          if (bar_all(1 + wg, !((tag ^ par) & 1))) break;
          wg_wait<0>();
          if (w == 0 && elect()) { mbar_expect_tx(BAR(B_XR + c), 4096); bulk_load(base + xo, G->xr + (128 * c + bid) * 256, 4096, BAR(B_XR + c)); }
        }
        wg_fence();
        csteps<5, 1>(acc, A, mkdesc(DB + tab(T_X, opaque(c)), 16, 128, 0));
        wg_commit();
        if (c >= 2 && c < 4 && elect()) mbar_arrive(BAR(B_TURN - 2 + c));
        if (c >= 3) mbar_wait(BAR(B_PEMPTY + c - 3));
        wg_wait<0>();
        fence_regs(acc);
        ck = base + OFF_A + wg * ARING + lane * 128 + (((2 * w) ^ (lane & 7)) << 4);
        const uint32_t pb = base + tab(T_P, c) + 4096 * w;
#pragma unroll
        for (int k = 0; k < 8; k++) {
          uint32_t p[4];
#pragma unroll
          for (int e = 0; e < 4; e++) { const int i = 4 * k + e; p[e] = i < 31 ? pack_bf16(acc[4 * i] + acc[4 * i + 6], acc[4 * i + 1] + acc[4 * i + 7]) : pack_bf16(acc[124], acc[125]); }
          if (k == 0 && (lane & 3) < w) p[0] = 0;
          stmatrix_x4_t(k == 0 ? pb + 16 * ((255 - lane + 2 * w) & 255) : pb + 16 * (255 - lane + 2 * w) - 512 * k, p[0], p[1], p[2], p[3]);
        }
        arrive1(BAR(B_PFULL + c));
        c += 2;
      }
    }
    const uint32_t abd = DB + OFF_A + wg * ARING;
    auto a_tile = [&](int as, int n, bool first) {
#pragma unroll 1
      for (int it = 0; __any_sync(~0u, ((lds32(ck + as) ^ par) | (lds32(ck + as + (first ? 4096 : 256)) ^ par)) & 1) && it < SPIN_LIMIT; it++) {
        int h, j, r;
        ffn_role(h, j, r);
        if (elect()) {
          const uint32_t dst = base + OFF_A + wg * ARING + as;
          mbar_expect_tx(BAR(B_RETRY + wid), ASLOT);
          if (first) tma2d(dst, &maps.xs, 128 * r + 64 * (h ^ wg), 64 * n, BAR(B_RETRY + wid));
          else bulk_load(dst, G->hh + ((2 * r + (h ^ wg)) * 8 + 4 * h + fslice(j, n % 3)) * 1536 + (n / 3) * 512, ASLOT, BAR(B_RETRY + wid));
        }
        mbar_wait(BAR(B_RETRY + wid), par >> 1);
        par ^= 2;
      }
    };
    float acc[192];
    int ws = 0, as = 0;
#pragma unroll 1
    for (int u = 0; u < 20 - NT; u++) {
      mbar_wait(BAR(B_FULL + u));
      if (!(u & 1)) a_tile(as, u >> 1, true);
      wg_fence();
#pragma unroll
      for (int k = 0; k < 4; k++) wg_ss192_11(acc + 96 * (k & 1), mkdesc(abd + as + k / 2 * 2048, 16, 1024, 1), mkdesc(DB + ws + 12288 * (k & 1) + k / 2 * 2048, 4096, 1024, 1), u + k / 2);
      wg_commit();
      wg_wait<1>();
      if (elect()) mbar_arrive(BAR(B_EMPTY + u - 1));
      ws = next_slot(ws);
      as = as == 5 * ASLOT / 2 ? 0 : as + ASLOT / 2;
    }
    auto tail = [&](int v, int i) {
      const int u = 20 - NT + i / 2;
      if (i < 2 * NT) wg_ss192_11(acc + 96 * v, mkdesc(opaque(abd) + u % 6 * 4096 + (i & 1) * 2048, 16, 1024, 1), mkdesc(DB + u % 5 * WSLOT + (i & 1) * 2048 + 12288 * v, 4096, 1024, 1), 1);
      if (i == 2 * NT) wg_ss192_01(acc + 96 * v, mkdesc(DB + OFF_AX + 1024 * opaque(wg), 0, 128, 0), mkdesc(DB + OFF_BX + 6144 * v, 2048, 1024, 1), 1);
    };
#pragma unroll
    for (int u = 20 - NT; u <= 20; u++) {
      mbar_wait(BAR(u < 20 ? B_FULL + u : B_EXT));
      if (u == 16 || u == 18) a_tile(u % 6 * 4096, u >> 1, true);
      wg_fence();
      tail(0, 2 * (u + NT - 20));
      tail(0, 2 * (u + NT - 20) + 1);
      wg_commit();
      if (u == 20 - NT) { wg_wait<1>(); if (elect()) mbar_arrive(BAR(B_EMPTY + u - 1)); }
    }
    float o[80];
    uint32_t fr[3][16], bo;
    {
      int h, j, r;
      ffn_role(h, j, r);
      REGION_IDS;
      const float r0 = 0.5f * __uint_as_float(lds32(base + OFF_RT + 256 * wg + 64 * w + (lane & 28))), r1 = 0.5f * __uint_as_float(lds32(base + OFF_RT + 256 * wg + 64 * w + 32 + (lane & 28)));
      const int id = (2 * r + (h ^ wg)) * 8 + 4 * h + j;
      uint4* const hdst = G->hh + id * 1536 + 128 * w + (lane ^ lane >> 3);
      const uint32_t keep = ~(~lane & 1), bit = par & ~keep;
      bo = 1024 + ((j & 1) << 23);
      auto own = [&](int i) { wg_rs160_1(o, fr[i >> 2] + 4 * (i & 3), mkdesc(DB + (5 + i / 4) % 6 * WSLOT + (i & 3) * 2048, 8192, bo, 1), i); };
      auto gate = [&](float* g, int d) {
#pragma unroll
        for (int e = 0; e < 4; e++) { g[e] *= e < 2 ? r0 : r1; g[e + d] *= g[e]; asm("tanh.approx.f32 %0, %0;" : "+f"(g[e])); }
      };
      auto mix = [&](uint32_t* x, const float* g, int d) {
        x[0] = pack_bf16(fmaf(g[d], g[0], g[d]), fmaf(g[d + 1], g[1], g[d + 1]));
        x[1] = pack_bf16(fmaf(g[d + 2], g[2], g[d + 2]), fmaf(g[d + 3], g[3], g[d + 3]));
      };
      auto hint = [&](int v) { asm volatile("{.reg .pred p; setp.eq.u32 p, %1, 0; @p red.relaxed.gpu.global.add.u32 [%0], 1;}" ::"l"(&G->hhf[id * 8 + v]), "r"(lane) : "memory"); };
      auto put = [&](int v, int k) {
        uint32_t* x = fr[v] + 2 * k;
        const uint32_t t0 = (x[k / 2] & keep) | bit, t1 = (x[5 + k / 2] & keep) | bit;
        if (!v) { x[k / 2] = t0; x[5 + k / 2] = t1; }
        st_relaxed128(hdst + 512 * v + 8 * k, k ? x[0] : t0, k ? t0 : x[2], x[4], x[6]);
        st_relaxed128(hdst + 512 * v + 8 * k + 64, x[1], x[3], k ? x[5] : t1, k ? t1 : x[7]);
      };
      auto move = [&](uint32_t* x) {
#pragma unroll
        for (int k = 0; k < 16; k++) asm volatile("mul.rn.f32 %0, %0, %1;" : "+r"(x[k]) : "f"(P.one));
      };
      wg_fence();
#pragma unroll
      for (int i = 0; i < NP; i++) tail(1, i);
      if (NP) wg_commit();
      wg_wait<NP ? 1 : 0>();
#pragma unroll
      for (int k = 0; k < 96; k++) asm volatile("" : "+f"(acc[k])::"memory");
      if (elect()) mbar_arrive(BAR(B_EMPTY + 18));
      gate(acc + 28, 32);
#pragma unroll
      for (int g = 0; g < 8 + NB; g++) {
        const int k = 7 - g, i = (g - P0) / ST + NP;
        const bool mm = g >= P0 && (g - P0) % ST == 0;
        if (mm && i <= 7) split(P.zero, g);
        if (mm && i == 0) wg_fence();
        if (mm && i < 7) tail(1, i);
        if (mm && i == 6) wg_commit();
        if (g < 8) {
          if (k) gate(acc + 4 * k - 4, 32);
          mix(fr[0] + 2 * k, acc + 4 * k, 32);
          if (k == 4) hint(0);
          if (!(k & 3)) put(0, k);
          if (!k) move(fr[0]);
        } else {
#pragma unroll
          for (int e = 0; e < 4; e++) acc[96 + 4 * k + e] = silu2(acc[96 + 4 * k + e] * (e < 2 ? r0 : r1));
        }
      }
      static_assert(P0 + ST * (6 - NP) < 8 + NB, "all products are issued");
      split(P.zero, 14);
      wg_wait<0>();
#pragma unroll
      for (int k = 96; k < 192; k++) asm volatile("" : "+f"(acc[k])::"memory");
      if (elect()) mbar_arrive(BAR(B_EMPTY + 19));
#pragma unroll
      for (int k = 7 - NB; k >= 0; k--) gate(acc + 64 + 4 * k, 96);
      mbar_wait(BAR(B_FULL + 20));
      mbar_wait(BAR(B_FULL + 21));
#pragma unroll
      for (int k = 7; k >= 0; k--) {
        const float* g = acc + 64 + 4 * k;
        if (k < 8 - NB) mix(fr[1] + 2 * k, g, 96);
        else { fr[1][2 * k] = pack_bf16(g[0] * g[96], g[1] * g[97]); fr[1][2 * k + 1] = pack_bf16(g[2] * g[98], g[3] * g[99]); }
      }
#pragma unroll
      for (int k = 0; k < 4; k++) pin4(P.zero, fr[1] + 4 * k);
      if (PA) { put(1, 4); hint(1); }
      if (PA == 2) put(1, 0);
      if (PA) split(P.zero, 31);
      wg_fence();
      own(0);
      own(1);
      split(P.zero, 15);
      if (!PA) { put(1, 4); hint(1); }
      if (!O3) own(2);
      if (PA < 2) put(1, 0);
      if (!O3) { own(3); wg_commit(); }
      gate(acc + 124, 32);
#pragma unroll
      for (int g = 0; g < 8; g++) {
        const int k = 7 - g, i = (g - O0) / OS + (O3 ? 2 : 4);
        const bool mm = g >= O0 && (g - O0) % OS == 0 && i < 8;
        if (mm || g == 0) split(P.zero, 16 + k);
        if (mm) own(i);
        if (mm && (i == 3 || i == 5 || i == 7)) wg_commit();
        if (mm && i == 5) { wg_wait<1>(); if (elect()) mbar_arrive(BAR(B_EMPTY + 20)); }
        if (k) gate(acc + 92 + 4 * k, 32);
        mix(fr[2] + 2 * k, acc + 96 + 4 * k, 32);
        if (k == 1) hint(2);
        if (!(k & 3)) put(2, k);
      }
      static_assert(O0 + OS * (O3 ? 5 : 3) < 8, "all products are issued");
      mbar_wait(BAR(B_FULL + 22));
      wg_fence();
#pragma unroll
      for (int i = 8; i < 12; i++) own(i);
      wg_commit();
      wg_wait<1>();
      if (elect()) mbar_arrive(BAR(B_EMPTY + 21));
      ck = base + OFF_A + wg * ARING + 2048 * w + 516 * (lane >> 3) + 144 * (lane >> 2 & 1) + 32 * (lane & 3);
    }
    uint32_t x1[40];
    if (!wg) {
      REGION_IDS;
      const uint32_t xa = base + (lane >> 4) * 1024 + (lane & 7) * 128 + (((2 * w + ((lane >> 3) & 1)) ^ (lane & 7)) << 4);
      mbar_wait(BAR(B_FULL + 32));
#pragma unroll
      for (int k = 0; k < 10; k++) ldmatrix_x4_t(x1 + 4 * k, xa + (k < 6 ? OFF_X1 + k / 2 * WSLOT + (k & 1) * 2048 : OFF_SX + 2048 * (k - 6)));
    }
#pragma unroll 1
    for (int u = 23; u < (wg ? 32 : LAG2); u++) {
      as = P.hid[wg][u - 23];
      const uint64_t wd = mkdesc(0, 0, bo, 1) | P.w2t[u - 20].x;
      mbar_wait(BAR(B_FULL + u));
      a_tile(as, u - 23, false);
      wg_fence();
#pragma unroll
      for (int kk = 0; kk < 4; kk++) wg_ss160_01(o, mkdesc(abd + as + kk / 2 * 512 + (kk & 1) * 32, 16, 1024, 2), wd + kk * 128, 1);
      wg_commit();
      if (u == 31 && elect()) mbar_arrive(BAR(B_LAG));
      wg_wait<1>();
      if (elect()) mbar_arrive(BAR(B_EMPTY + u - 1));
    }
    int h, j, r;
    ffn_role(h, j, r);
    REGION_IDS;
    const uint32_t xb = base + OFF_XCH + 5120 * w;
    if (wg) {
      const uint32_t rdst = mapa(xb + 16 * lane, h ^ 1), rbar = mapa(BAR(B_FULL), h ^ 1);
      mbar_wait(BAR(B_XFREE));
      wg_wait<0>();
      fence_regs(o);
#pragma unroll
      for (int k = 0; k < 10; k++)
        asm volatile("st.async.shared::cluster.mbarrier::complete_tx::bytes.v4.b32 [%0], {%1,%2,%3,%4}, [%5];" ::"r"(rdst + 512 * k), "r"(pack_bf16(o[8 * k], o[8 * k + 1])),
                     "r"(pack_bf16(o[8 * k + 2], o[8 * k + 3])), "r"(pack_bf16(o[8 * k + 4], o[8 * k + 5])), "r"(pack_bf16(o[8 * k + 6], o[8 * k + 7])), "r"(rbar + 8 * (k / 4)) : "memory");
    } else {
      uint32_t gr[40];
      const float r0 = __uint_as_float(lds32(base + OFF_RT + 64 * w + (lane & 28))), r1 = __uint_as_float(lds32(base + OFF_RT + 64 * w + 32 + (lane & 28)));
      const uint32_t p0 = pack_bf16(r0, r0), p1 = pack_bf16(r1, r1), q0 = pack_bf16(r0 - bf_lo(p0), r0 - bf_lo(p0)), q1 = pack_bf16(r1 - bf_lo(p1), r1 - bf_lo(p1));
      mbar_wait(BAR(B_GB));
#pragma unroll
      for (int k = 0; k < 5; k++) {
        const uint4 g = lds128(base + OFF_GB + 80 * (lane & 3) + 16 * k);
        gr[8 * k] = g.x; gr[8 * k + 2] = g.y; gr[8 * k + 4] = g.z; gr[8 * k + 6] = g.w;
      }
      auto scale = [&](int k) {
#pragma unroll
        for (int e = 4 * k; e < 4 * k + 4; e += 2) { gr[e + 1] = bfma2(gr[e], p1, bmul2(gr[e], q1)); gr[e] = bfma2(gr[e], p0, bmul2(gr[e], q0)); }
      };
#pragma unroll
      for (int k = max(127 - 4 * LAG2, 0); k < 10; k++) scale(k);
      wg_wait<0>();
      if (elect()) mbar_arrive(BAR(B_EMPTY + LAG2 - 1));
#pragma unroll 1
      for (int u = LAG2; u < 32; u++) {
        mbar_wait(BAR(B_FULL + u));
        a_tile(P.hid[0][u - 23], u - 23, false);
      }
      auto da = [&](int i) { return mkdesc(DB + hid_at(i / 4 + LAG2 - 23, 0) + (i & 2) * 256 + (i & 1) * 32, 16, 1024, 2); };
      auto db = [&](int i, int b) { return mkdesc(DB + w2_at(i / 4 + LAG2 - 20) + b * w2_step(i / 4 + LAG2 - 20) + (i & 3) * 2048, w2_step(i / 4 + LAG2 - 20), bo, 1); };
      const int row = 128 * r + 64 * h + 16 * w;
      auto merge = [&](int e) {
        if (e % 4 == 0) mbar_wait_cluster(BAR(B_FULL + e / 4), 1);
        const uint4 p = lds128(xb + 16 * lane + 512 * e);
        x1[4 * e] = bfma2(gr[4 * e], p.x, x1[4 * e]); x1[4 * e + 1] = bfma2(gr[4 * e + 1], p.y, x1[4 * e + 1]);
        x1[4 * e + 2] = bfma2(gr[4 * e + 2], p.z, x1[4 * e + 2]); x1[4 * e + 3] = bfma2(gr[4 * e + 3], p.w, x1[4 * e + 3]);
      };
      auto out = [&](int k) {
        const float* v = o + 8 * k;
        uint32_t y[4];
#pragma unroll
        for (int e = 0; e < 4; e++) y[e] = bfma2(gr[4 * k + e], pack_bf16(v[2 * e], v[2 * e + 1]), x1[4 * k + e]);
        stmatrix_x4(k < 8 ? xb + 2048 * (k >> 2) + (lane & 15) * 128 + (((2 * (k & 3) + (lane >> 4)) ^ (lane & 7) ^ 4 * (j & 1)) << 4)
                          : xb + 4096 + (lane & 15) * 64 + (((2 * (k & 1) + (lane >> 4)) ^ (lane >> 1 & 3)) << 4), y[0], y[1], y[2], y[3]);
        if ((k & 3) == 3 || k == 9) {
          fence_async_smem();
          __syncwarp();
          if (lane == 0) tma2d_store(k < 8 ? &maps.outa : &maps.outb, k < 8 ? 128 * j + 64 * (k >> 2) : 512 + 32 * j, row, xb + 2048 * (k >> 2));
        }
      };
      constexpr int ND = 128 - 4 * LAG2;
      mbar_wait(BAR(B_LAG));
      wg_fence();
#pragma unroll
      for (int i = 0; i < ND; i++) {
        wg_ss160_01(o, da(i), db(i, 0), 1);
        if (i >= 1 && i <= 10) { scale(i - 1); split(P.zero, 32 + i); }
      }
      wg_commit();
#pragma unroll
      for (int e = 0; e < MG; e++) merge(e);
      __syncwarp();
      wg_wait<0>();
      fence_regs(o);
#pragma unroll
      for (int k = 0; k < 10; k++) {
        if (k >= MG && k % 4 == 0) {
#pragma unroll
          for (int e = k; e < min(k + 4, 10); e++) merge(e);
          __syncwarp();
        }
        out(k);
      }
      if (lane == 0) { bulk_commit(); bulk_wait_read(); }
    }
  }
}

typedef CUresult (*EncFn)(CUtensorMap*, CUtensorMapDataType, cuuint32_t, void*, const cuuint64_t*, const cuuint64_t*, const cuuint32_t*,
                          const cuuint32_t*, CUtensorMapInterleave, CUtensorMapSwizzle, CUtensorMapL2promotion, CUtensorMapFloatOOBfill);
static int enc_err = 0;
static void enc(EncFn fn, CUtensorMap* m, const void* p, int rank, const cuuint64_t* gd, const cuuint64_t* gs, const cuuint32_t* bd, CUtensorMapSwizzle sw) {
  cuuint32_t es[5] = {1, 1, 1, 1, 1};
  enc_err = 2 * enc_err + (fn(m, CU_TENSOR_MAP_DATA_TYPE_BFLOAT16, rank, (void*)p, gd, gs, bd, es, CU_TENSOR_MAP_INTERLEAVE_NONE, sw,
                              CU_TENSOR_MAP_L2_PROMOTION_L2_128B, CU_TENSOR_MAP_FLOAT_OOB_FILL_NONE) != CUDA_SUCCESS);
}

extern "C" void kernel_launch(void* const* d_in, const int* in_sizes, int n_in, void* d_out, int out_size) {
  const bf16 *q = (const bf16*)d_in[0], *k = (const bf16*)d_in[1], *v = (const bf16*)d_in[2], *shift = (const bf16*)d_in[3],
             *ssmk = (const bf16*)d_in[4], *ssmd = (const bf16*)d_in[5], *w1 = (const bf16*)d_in[7], *w3 = (const bf16*)d_in[8],
             *w2 = (const bf16*)d_in[9], *c = (const bf16*)d_in[10], *wmod = (const bf16*)d_in[11];
  EncFn fn = nullptr;
  cudaDriverEntryPointQueryResult qr;
  cudaGetDriverEntryPoint("cuTensorMapEncodeTiled", (void**)&fn, cudaEnableDefault, &qr);
  Scratch* pg;
  cudaGetSymbolAddress((void**)&pg, g_s);
  Maps maps;
  enc_err = 0;
  const CUtensorMapSwizzle S128 = CU_TENSOR_MAP_SWIZZLE_128B;
  { cuuint64_t gd[3] = {D_, S_ / 8, 8}, gs[2] = {D_ * 16, D_ * 2}; cuuint32_t b[3] = {64, 4, 8};
    enc(fn, &maps.km, k, 3, gd, gs, b, S128);
    enc(fn, &maps.v, v, 3, gd, gs, b, S128);
    enc(fn, &maps.q, q, 3, gd, gs, b, S128);
    b[2] = 3;
    enc(fn, &maps.kh, k, 3, gd, gs, b, S128); }
  { cuuint64_t gd[3] = {256, 2, 5}, gs[2] = {512, 1024}; cuuint32_t b[3] = {256, 1, 5};
    enc(fn, &maps.tap, shift, 3, gd, gs, b, CU_TENSOR_MAP_SWIZZLE_NONE); }
  { cuuint64_t gd[3] = {6 * D_, D_, 1}, gs[2] = {6 * D_ * 2, 6 * D_ * 2 * D_}; cuuint32_t b[3] = {64, 64, 1};
    enc(fn, &maps.wm, wmod, 3, gd, gs, b, S128); }
  { cuuint64_t gd[3] = {64, D_, F_ / 64}, gs[2] = {F_ * 2, 128}; cuuint32_t b[3] = {64, 32, 3};
    enc(fn, &maps.w1, w1, 3, gd, gs, b, S128);
    enc(fn, &maps.w3, w3, 3, gd, gs, b, S128);
    b[1] = 16;
    enc(fn, &maps.w1e, w1, 3, gd, gs, b, S128);
    enc(fn, &maps.w3e, w3, 3, gd, gs, b, S128);
    b[1] = 32; b[2] = 1;
    enc(fn, &maps.w1s, w1, 3, gd, gs, b, S128);
    enc(fn, &maps.w3s, w3, 3, gd, gs, b, S128); }
  { cuuint64_t gd[2] = {S_, D_}, gs[1] = {S_ * 2}; cuuint32_t b1[2] = {64, 64}, b2[2] = {64, 32};
    enc(fn, &maps.xs, pg->xs, 2, gd, gs, b1, S128);
    gd[1] = 2 * D_;
    enc(fn, &maps.x1b, pg->x1, 2, gd, gs, b2, S128);
    enc(fn, &maps.x1s, pg->x1, 2, gd, gs, b2, CU_TENSOR_MAP_SWIZZLE_NONE); }
  { cuuint64_t gd[5] = {D_, 2, 4, 4, 48}, gs[4] = {D_ * 2, D_ * 4, D_ * 16, D_ * 64}; cuuint32_t b[5] = {64, 2, 4, 4, 2};
    enc(fn, &maps.w2a, w2, 5, gd, gs, b, S128);
    gs[1] = D_ * 16; gs[2] = D_ * 4;
    enc(fn, &maps.w2b, w2, 5, gd, gs, b, S128); }
  { cuuint64_t gd[2] = {D_, S_}, gs[1] = {D_ * 2}; cuuint32_t b1[2] = {64, 16}, b2[2] = {32, 16};
    enc(fn, &maps.outa, d_out, 2, gd, gs, b1, S128);
    enc(fn, &maps.outb, d_out, 2, gd, gs, b2, CU_TENSOR_MAP_SWIZZLE_64B); }
  if (enc_err) return;
  cudaFuncSetAttribute(k_fused, cudaFuncAttributeMaxDynamicSharedMemorySize, SMEM_BYTES);
  cudaLaunchConfig_t cfg = {132, 512, SMEM_BYTES};
  cudaLaunchAttribute at = {cudaLaunchAttributeClusterDimension};
  at.val.clusterDim.x = 2; at.val.clusterDim.y = at.val.clusterDim.z = 1;
  cfg.attrs = &at; cfg.numAttrs = 1;
  int nc = 0;
  cudaOccupancyMaxActiveClusters(&nc, k_fused, &cfg);
  Ptrs P = {ssmk, c, ssmd, pg, 0x4E8DCBA9ull, {0x676760, 0x64620F01}, 0, 700, 420, 5500, 0, 0, 0, 6, B_KV, 0, 0, 1, 1, 0x57010, 1.f};
  const char* sched = "k10v14f04q04q14q24q34q44k24v24f14k34v34f24k44v44f34f44";
  int t = 700, pace = 440;
  for (int e = 0; e < NE; e++) {
    const char x = sched[3 * e];
    const int r = sched[3 * e + 1] - '0', kind = x == 'k' ? 0 : x == 'v' ? 1 : x == 'q' ? 2 : x == 'f' ? 3 : 4;
    t += (sched[3 * e + 2] - '0') * pace / 4;
    P.sched[e] = make_uint2(t | kind << 16 | r << 20, (kind < 2 ? tab(T_KV, r) + kind * KV_V : kind == 2 ? OFF_Q + 4096 * r : tab(T_F, r) + F_E) | (r + (kind < 2 ? B_KV : kind == 2 ? B_Q : B_FRAW)) << 18);
  }
  for (int u = 0; u < 5; u++) P.wt[u] = 11500 + 400 * u;
  const int dep[5] = {B_FL + 1, B_FL + 2, B_PFULL + 2, B_FL + 1, B_PEMPTY + 2};
  for (int u = 0; u < 20; u++) P.wdep[u] = u % 5 * WSLOT | (~u & 1) << 12 | (u < 5 ? dep[u] : B_EMPTY + u - 5);
  for (int v = 0; v < 12; v++) P.w2t[v] = make_uint2(w2_desc(v), v ? B_EMPTY + (v > 5 ? 15 + v : v > 3 ? 14 + v : v > 1 ? 16 : 15) : B_UVD);
  for (int m = 0; m < 9; m++) { P.hid[0][m] = hid_at(m, 0) - OFF_A; P.hid[1][m] = hid_at(m, 1) - OFF_A - ARING; P.hid[2][m] = B_EMPTY + 19 + (m > 2 ? m : m / 2); }
  if (nc < 66) { P.boff = 128; k_fused<<<4, 512, SMEM_BYTES, cudaStreamPerThread>>>(P, maps); P.boff = 0; }
  k_fused<<<nc < 66 ? 128 : 132, 512, SMEM_BYTES, cudaStreamPerThread>>>(P, maps);
}
```

```cpp
#include <cuda_runtime.h>
#include <cuda.h>
#include <cuda_bf16.h>
#include <stdint.h>
#include <stdlib.h>

typedef __nv_bfloat16 bf16;
constexpr int S_ = 2048, D_ = 640, F_ = 1536;

struct Scratch {
  uint32_t st1[2][1024];
  uint32_t st2[32][4][128];
  uint2 modc[128][32];
  uint2 modv[3][D_];
  uint32_t uv[8][3072];
  unsigned hint[9][8][32];
  unsigned xsh[5][8][32], hhf[256 * 8];
  uint4 xr[D_ * 256];
  uint4 qt[D_ * 256];
  uint4 xs[D_ * 256];
  uint4 x1[2][D_ * 256];
  uint4 hh[32 * 8 * 1536];
};
__device__ __align__(1024) Scratch g_s;

__device__ __forceinline__ uint32_t smem_u32(const void* p) { return (uint32_t)__cvta_generic_to_shared(p); }
__device__ __forceinline__ void mbar_expect_tx(uint32_t b, uint32_t n) { asm volatile("mbarrier.arrive.expect_tx.shared::cta.b64 _, [%0], %1;" ::"r"(b), "r"(n) : "memory"); }
__device__ __forceinline__ void mbar_arrive(uint32_t b) { asm volatile("mbarrier.arrive.shared::cta.b64 _, [%0];" ::"r"(b) : "memory"); }
__device__ __forceinline__ void mbar_arrive2(uint32_t b) { asm volatile("mbarrier.arrive.shared::cta.b64 _, [%0], 2;" ::"r"(b) : "memory"); }
__device__ __forceinline__ uint32_t mapa(uint32_t a, uint32_t cta) { uint32_t r; asm volatile("mapa.shared::cluster.u32 %0, %1, %2;" : "=r"(r) : "r"(a), "r"(cta)); return r; }
__device__ __forceinline__ void mbar_arrive_remote(uint32_t rb) { asm volatile("mbarrier.arrive.shared::cluster.b64 _, [%0];" ::"r"(rb) : "memory"); }
constexpr int SPIN_LIMIT = 1 << 16;
template <int N> __device__ __forceinline__ void mbar_init(uint32_t b, uint32_t count) {
#pragma unroll
  for (int i = 0; i < N; i++) asm volatile("mbarrier.init.shared::cta.b64 [%0], %1;" ::"r"(b + 8 * i), "r"(count) : "memory");
}
__device__ __forceinline__ bool elect() { uint32_t p; asm volatile("{.reg .pred q; elect.sync _|q, 0xffffffff; selp.u32 %0, 1, 0, q;}" : "=r"(p)); return p; }
__device__ __forceinline__ void arrive1(uint32_t b) { __syncwarp(); if (elect()) mbar_arrive(b); }
__device__ __forceinline__ bool mbar_test(uint32_t b) {
  uint32_t ok;
  asm volatile("{.reg .pred p; mbarrier.test_wait.parity.shared::cta.b64 p, [%1], 0; selp.u32 %0,1,0,p;}" : "=r"(ok) : "r"(b) : "memory");
  return ok;
}
#define WAIT_LOOP(sem) "{.reg .pred p; mov.u32 %0, 0; W: mbarrier.try_wait.parity" sem ".shared::cta.b64 p, [%1], %2; @p bra.uni D; add.u32 %0, %0, 1; setp.lt.u32 p, %0, %3; @p bra.uni W; D:}"
__device__ __forceinline__ void mbar_wait(uint32_t b, uint32_t ph = 0) {
  int it;
  asm volatile(WAIT_LOOP("") : "=&r"(it) : "r"(b), "r"(ph), "n"(SPIN_LIMIT) : "memory");
}
__device__ __forceinline__ void mbar_wait_cluster(uint32_t b, uint32_t ph = 0) {
  int it;
  asm volatile(WAIT_LOOP(".acquire.cluster") : "=&r"(it) : "r"(b), "r"(ph), "n"(SPIN_LIMIT) : "memory");
}
__device__ __forceinline__ void wait_clock(uint32_t t) {
  asm volatile("{.reg .pred p; .reg .s32 d; W: mov.u32 d, %%clock; sub.s32 d, d, %0; setp.lt.s32 p, d, 0; @p bra.uni W;}" ::"r"(t) : "memory");
}
__device__ __forceinline__ void tma2d(uint32_t dst, const CUtensorMap* m, int c0, int c1, uint32_t bar) {
  asm volatile("cp.async.bulk.tensor.2d.shared::cluster.global.mbarrier::complete_tx::bytes [%0], [%1, {%3,%4}], [%2];" ::"r"(dst), "l"(m), "r"(bar), "r"(c0), "r"(c1) : "memory");
}
__device__ __forceinline__ void tma3d(uint32_t dst, const CUtensorMap* m, int c0, int c1, int c2, uint32_t bar) {
  asm volatile("cp.async.bulk.tensor.3d.shared::cluster.global.mbarrier::complete_tx::bytes [%0], [%1, {%3,%4,%5}], [%2];" ::"r"(dst), "l"(m), "r"(bar), "r"(c0), "r"(c1), "r"(c2) : "memory");
}
__device__ __forceinline__ void tma5d(uint32_t dst, const CUtensorMap* m, int c0, int c4, uint32_t bar) {
  asm volatile("cp.async.bulk.tensor.5d.shared::cluster.global.mbarrier::complete_tx::bytes [%0], [%1, {%4,%3,%3,%3,%5}], [%2];" ::"r"(dst), "l"(m), "r"(bar), "r"(0), "r"(c0), "r"(c4) : "memory");
}
__device__ __forceinline__ void tma2d_store(const CUtensorMap* m, int c0, int c1, uint32_t src) {
  asm volatile("cp.async.bulk.tensor.2d.global.shared::cta.bulk_group [%0, {%2,%3}], [%1];" ::"l"(m), "r"(src), "r"(c0), "r"(c1) : "memory");
}
__device__ __forceinline__ void bulk_load(uint32_t dst, const void* src, uint32_t bytes, uint32_t bar) {
  asm volatile("cp.async.bulk.shared::cluster.global.mbarrier::complete_tx::bytes [%0], [%1], %2, [%3];" ::"r"(dst), "l"(src), "r"(bytes), "r"(bar) : "memory");
}
__device__ __forceinline__ void prefetch_map(const CUtensorMap* m) { asm volatile("prefetch.tensormap [%0];" ::"l"(m) : "memory"); }
__device__ __forceinline__ void bulk_commit() { asm volatile("cp.async.bulk.commit_group;" ::: "memory"); }
__device__ __forceinline__ void bulk_wait_read() { asm volatile("cp.async.bulk.wait_group.read 0;" ::: "memory"); }
__device__ __forceinline__ void fence_async_smem() { asm volatile("fence.proxy.async.shared::cta;" ::: "memory"); }
__device__ __forceinline__ void fence_async_all() { asm volatile("fence.proxy.async.global;" ::: "memory"); }
__device__ __forceinline__ void named_bar(int id, int n) { asm volatile("bar.sync %0, %1;" ::"r"(id), "r"(n) : "memory"); }
__device__ __forceinline__ bool bar_all(int id, bool v) {
  uint32_t r;
  asm volatile("{.reg .pred p, q; setp.ne.u32 p, %2, 0; bar.red.and.pred q, %1, 128, p; selp.u32 %0, 1, 0, q;}" : "=r"(r) : "r"(id), "r"((uint32_t)v) : "memory");
  return __all_sync(~0u, r);
}
__device__ __forceinline__ void cluster_wait() { asm volatile("barrier.cluster.wait.aligned;" ::: "memory"); }
__device__ __forceinline__ void wg_fence() { asm volatile("wgmma.fence.sync.aligned;" ::: "memory"); }
__device__ __forceinline__ void wg_commit() { asm volatile("wgmma.commit_group.sync.aligned;" ::: "memory"); }
template <int N> __device__ __forceinline__ void wg_wait() { asm volatile("wgmma.wait_group.sync.aligned %0;" ::"n"(N) : "memory"); }
template <int N> __device__ __forceinline__ void fence_regs(float (&a)[N]) {
#pragma unroll
  for (int i = 0; i < N; i++) asm volatile("" : "+f"(a[i])::"memory");
}
template <int N> __device__ __forceinline__ void fence_n(float* a) {
#pragma unroll
  for (int i = 0; i < N; i++) asm volatile("" : "+f"(a[i])::"memory");
}
__device__ __forceinline__ uint64_t mkdesc(uint32_t addr, uint32_t lbo, uint32_t sbo, uint32_t swz) {
  uint32_t lo = (addr >> 4) | ((lbo >> 4) << 16), hi = (sbo >> 4) | (swz << 30);
  return ((uint64_t)hi << 32) | lo;
}
__device__ __forceinline__ void stmatrix_x4(uint32_t a, uint32_t r0, uint32_t r1, uint32_t r2, uint32_t r3) {
  asm volatile("stmatrix.sync.aligned.m8n8.x4.shared.b16 [%0], {%1,%2,%3,%4};" ::"r"(a), "r"(r0), "r"(r1), "r"(r2), "r"(r3) : "memory");
}
__device__ __forceinline__ void stmatrix_x4_t(uint32_t a, uint32_t r0, uint32_t r1, uint32_t r2, uint32_t r3) {
  asm volatile("stmatrix.sync.aligned.m8n8.x4.trans.shared.b16 [%0], {%1,%2,%3,%4};" ::"r"(a), "r"(r0), "r"(r1), "r"(r2), "r"(r3) : "memory");
}
__device__ __forceinline__ void ldmatrix_x4_t(uint32_t* r, uint32_t a) {
  asm volatile("ldmatrix.sync.aligned.m8n8.x4.trans.shared.b16 {%0,%1,%2,%3}, [%4];" : "=r"(r[0]), "=r"(r[1]), "=r"(r[2]), "=r"(r[3]) : "r"(a) : "memory");
}
__device__ __forceinline__ uint32_t lds32(uint32_t a) { uint32_t v; asm volatile("ld.shared.b32 %0, [%1];" : "=r"(v) : "r"(a) : "memory"); return v; }
__device__ __forceinline__ uint2 lds64(uint32_t a) { uint2 v; asm volatile("ld.shared.v2.b32 {%0,%1}, [%2];" : "=r"(v.x), "=r"(v.y) : "r"(a) : "memory"); return v; }
__device__ __forceinline__ uint4 lds128(uint32_t a) { uint4 v; asm volatile("ld.shared.v4.b32 {%0,%1,%2,%3}, [%4];" : "=r"(v.x), "=r"(v.y), "=r"(v.z), "=r"(v.w) : "r"(a) : "memory"); return v; }
__device__ __forceinline__ void sts32(uint32_t a, uint32_t v) { asm volatile("st.shared.b32 [%0], %1;" ::"r"(a), "r"(v) : "memory"); }
__device__ __forceinline__ void sts64(uint32_t a, uint32_t x, uint32_t y) { asm volatile("st.shared.v2.b32 [%0], {%1,%2};" ::"r"(a), "r"(x), "r"(y) : "memory"); }
__device__ __forceinline__ void sts128(uint32_t a, uint32_t x, uint32_t y, uint32_t z, uint32_t w) { asm volatile("st.shared.v4.b32 [%0], {%1,%2,%3,%4};" ::"r"(a), "r"(x), "r"(y), "r"(z), "r"(w) : "memory"); }
__device__ __forceinline__ uint4 ld_relaxed128(const void* p) { uint4 v; asm volatile("ld.relaxed.gpu.global.v4.u32 {%0,%1,%2,%3}, [%4];" : "=r"(v.x), "=r"(v.y), "=r"(v.z), "=r"(v.w) : "l"(p) : "memory"); return v; }
__device__ __forceinline__ uint2 ld_relaxed64(const void* p) { uint2 v; asm volatile("ld.relaxed.gpu.global.v2.u32 {%0,%1}, [%2];" : "=r"(v.x), "=r"(v.y) : "l"(p) : "memory"); return v; }
__device__ __forceinline__ uint32_t ld_relaxed32(const void* p) { uint32_t v; asm volatile("ld.relaxed.gpu.global.u32 %0, [%1];" : "=r"(v) : "l"(p) : "memory"); return v; }
__device__ __forceinline__ void st_relaxed128(void* p, uint32_t x, uint32_t y, uint32_t z, uint32_t w) { asm volatile("st.relaxed.gpu.global.v4.u32 [%0], {%1,%2,%3,%4};" ::"l"(p), "r"(x), "r"(y), "r"(z), "r"(w) : "memory"); }
__device__ __forceinline__ void st_relaxed32(void* p, uint32_t x) { asm volatile("st.relaxed.gpu.global.u32 [%0], %1;" ::"l"(p), "r"(x) : "memory"); }
__device__ __forceinline__ void red_hint(unsigned* p) { asm volatile("red.relaxed.gpu.global.add.u32 [%0], 1;" ::"l"(p) : "memory"); }
__device__ __forceinline__ void publish(uint32_t* p, uint32_t x) { asm volatile("{.reg .b32 t; atom.relaxed.gpu.global.exch.b32 t, [%0], %1;}" ::"l"(p), "r"(x) : "memory"); }
__device__ __forceinline__ uint32_t ldg32(const void* p) { uint32_t v; asm volatile("ld.global.nc.L1::no_allocate.b32 %0, [%1];" : "=r"(v) : "l"(p)); return v; }
__device__ __forceinline__ uint32_t pack_bf16(float lo, float hi) { uint32_t r; asm("cvt.rn.bf16x2.f32 %0, %1, %2;" : "=r"(r) : "f"(hi), "f"(lo)); return r; }
__device__ __forceinline__ float bf_lo(uint32_t v) { return __uint_as_float(v << 16); }
__device__ __forceinline__ float bf_hi(uint32_t v) { return __uint_as_float(v & 0xFFFF0000u); }
__device__ __forceinline__ uint32_t bmul2(uint32_t a, uint32_t b) { uint32_t r; asm("mul.rn.bf16x2 %0, %1, %2;" : "=r"(r) : "r"(a), "r"(b)); return r; }
__device__ __forceinline__ uint32_t badd2(uint32_t a, uint32_t b) { uint32_t r; asm("add.rn.bf16x2 %0, %1, %2;" : "=r"(r) : "r"(a), "r"(b)); return r; }
__device__ __forceinline__ uint32_t bfma2(uint32_t a, uint32_t b, uint32_t c) { uint32_t r; asm("fma.rn.bf16x2 %0, %1, %2, %3;" : "=r"(r) : "r"(a), "r"(b), "r"(c)); return r; }
__device__ __forceinline__ uint32_t set_tag(uint32_t x, uint32_t mask, uint32_t e) { uint32_t r; asm("lop3.b32 %0, %1, %2, %3, 0xB8;" : "=r"(r) : "r"(x), "r"(mask), "r"(e)); return r; }
__device__ __forceinline__ uint32_t opaque(uint32_t x) { asm volatile("" : "+r"(x)); return x; }
__device__ __forceinline__ float rbf(float x) { return __bfloat162float(__float2bfloat16(x)); }
__device__ __forceinline__ float silu_f(float x) {
  float e, r;
  asm("ex2.approx.ftz.f32 %0, %1;" : "=f"(e) : "f"(x * -1.4426950408889634f));
  asm("rcp.approx.ftz.f32 %0, %1;" : "=f"(r) : "f"(1.f + e));
  return x * r;
}
__device__ __forceinline__ float silu2(float x) {
  float t;
  asm("tanh.approx.f32 %0, %1;" : "=f"(t) : "f"(x));
  return fmaf(x, t, x);
}
__device__ __forceinline__ void pin(int off, uint32_t x) { asm volatile("{.reg .pred p; setp.lt.s32 p, %0, 0; @p st.shared.b32 [%0], %1;}" ::"r"(off), "r"(x) : "memory"); }
__device__ __forceinline__ void pin4(int off, const uint32_t* x) { asm volatile("{.reg .pred p; setp.lt.s32 p, %0, 0; @p st.shared.v4.b32 [%0], {%1,%2,%3,%4};}" ::"r"(off), "r"(x[0]), "r"(x[1]), "r"(x[2]), "r"(x[3]) : "memory"); }
__device__ __forceinline__ void split(int x, int n) { asm volatile("{.reg .pred p; setp.eq.s32 p, %0, %1; @p trap;}" ::"r"(x), "r"(~n) : "memory"); }
__device__ __forceinline__ void ln_final(float s, float q, float& m, float& sd) {
  m = s * (1.f / D_);
  asm("sqrt.approx.f32 %0, %1;" : "=f"(sd) : "f"(rbf(rbf(fmaxf(fmaf(-m, m, q * (1.f / D_)), 0.f)) + 1e-5f)));
  sd = rbf(sd);
}
__device__ __forceinline__ float rcpf(float x) { float r; asm("rcp.approx.f32 %0, %1;" : "=f"(r) : "f"(x)); return r; }

__device__ __forceinline__ void wg_rs16_0(float* d, const uint32_t* a, uint64_t db, int sc) {
  asm volatile("{.reg .pred p; setp.ne.b32 p, %13, 0; wgmma.mma_async.sync.aligned.m64n16k16.f32.bf16.bf16 {%0,%1,%2,%3,%4,%5,%6,%7}, {%8,%9,%10,%11}, %12, p, 1, 1, 0;}"
    : "+f"(d[0]),"+f"(d[1]),"+f"(d[2]),"+f"(d[3]),"+f"(d[4]),"+f"(d[5]),"+f"(d[6]),"+f"(d[7]) : "r"(a[0]),"r"(a[1]),"r"(a[2]),"r"(a[3]),"l"(db),"r"(sc));
}
__device__ __forceinline__ void wg_rs32_0(float* d, const uint32_t* a, uint64_t db, int sc) {
  asm volatile("{.reg .pred p; setp.ne.b32 p, %21, 0; wgmma.mma_async.sync.aligned.m64n32k16.f32.bf16.bf16 {%0,%1,%2,%3,%4,%5,%6,%7,%8,%9,%10,%11,%12,%13,%14,%15}, {%16,%17,%18,%19}, %20, p, 1, 1, 0;}"
    : "+f"(d[0]),"+f"(d[1]),"+f"(d[2]),"+f"(d[3]),"+f"(d[4]),"+f"(d[5]),"+f"(d[6]),"+f"(d[7]),"+f"(d[8]),"+f"(d[9]),"+f"(d[10]),"+f"(d[11]),"+f"(d[12]),"+f"(d[13]),"+f"(d[14]),"+f"(d[15]) : "r"(a[0]),"r"(a[1]),"r"(a[2]),"r"(a[3]),"l"(db),"r"(sc));
}
__device__ __forceinline__ void wg_rs48_0(float* d, const uint32_t* a, uint64_t db, int sc) {
  asm volatile("{.reg .pred p; setp.ne.b32 p, %29, 0; wgmma.mma_async.sync.aligned.m64n48k16.f32.bf16.bf16 {%0,%1,%2,%3,%4,%5,%6,%7,%8,%9,%10,%11,%12,%13,%14,%15,%16,%17,%18,%19,%20,%21,%22,%23}, {%24,%25,%26,%27}, %28, p, 1, 1, 0;}"
    : "+f"(d[0]),"+f"(d[1]),"+f"(d[2]),"+f"(d[3]),"+f"(d[4]),"+f"(d[5]),"+f"(d[6]),"+f"(d[7]),"+f"(d[8]),"+f"(d[9]),"+f"(d[10]),"+f"(d[11]),"+f"(d[12]),"+f"(d[13]),"+f"(d[14]),"+f"(d[15]),"+f"(d[16]),"+f"(d[17]),"+f"(d[18]),"+f"(d[19]),"+f"(d[20]),"+f"(d[21]),"+f"(d[22]),"+f"(d[23]) : "r"(a[0]),"r"(a[1]),"r"(a[2]),"r"(a[3]),"l"(db),"r"(sc));
}
__device__ __forceinline__ void wg_rs64_0(float* d, const uint32_t* a, uint64_t db, int sc) {
  asm volatile("{.reg .pred p; setp.ne.b32 p, %37, 0; wgmma.mma_async.sync.aligned.m64n64k16.f32.bf16.bf16 {%0,%1,%2,%3,%4,%5,%6,%7,%8,%9,%10,%11,%12,%13,%14,%15,%16,%17,%18,%19,%20,%21,%22,%23,%24,%25,%26,%27,%28,%29,%30,%31}, {%32,%33,%34,%35}, %36, p, 1, 1, 0;}"
    : "+f"(d[0]),"+f"(d[1]),"+f"(d[2]),"+f"(d[3]),"+f"(d[4]),"+f"(d[5]),"+f"(d[6]),"+f"(d[7]),"+f"(d[8]),"+f"(d[9]),"+f"(d[10]),"+f"(d[11]),"+f"(d[12]),"+f"(d[13]),"+f"(d[14]),"+f"(d[15]),"+f"(d[16]),"+f"(d[17]),"+f"(d[18]),"+f"(d[19]),"+f"(d[20]),"+f"(d[21]),"+f"(d[22]),"+f"(d[23]),"+f"(d[24]),"+f"(d[25]),"+f"(d[26]),"+f"(d[27]),"+f"(d[28]),"+f"(d[29]),"+f"(d[30]),"+f"(d[31]) : "r"(a[0]),"r"(a[1]),"r"(a[2]),"r"(a[3]),"l"(db),"r"(sc));
}
__device__ __forceinline__ void wg_rs80_0(float* d, const uint32_t* a, uint64_t db, int sc) {
  asm volatile("{.reg .pred p; setp.ne.b32 p, %45, 0; wgmma.mma_async.sync.aligned.m64n80k16.f32.bf16.bf16 {%0,%1,%2,%3,%4,%5,%6,%7,%8,%9,%10,%11,%12,%13,%14,%15,%16,%17,%18,%19,%20,%21,%22,%23,%24,%25,%26,%27,%28,%29,%30,%31,%32,%33,%34,%35,%36,%37,%38,%39}, {%40,%41,%42,%43}, %44, p, 1, 1, 0;}"
    : "+f"(d[0]),"+f"(d[1]),"+f"(d[2]),"+f"(d[3]),"+f"(d[4]),"+f"(d[5]),"+f"(d[6]),"+f"(d[7]),"+f"(d[8]),"+f"(d[9]),"+f"(d[10]),"+f"(d[11]),"+f"(d[12]),"+f"(d[13]),"+f"(d[14]),"+f"(d[15]),"+f"(d[16]),"+f"(d[17]),"+f"(d[18]),"+f"(d[19]),"+f"(d[20]),"+f"(d[21]),"+f"(d[22]),"+f"(d[23]),"+f"(d[24]),"+f"(d[25]),"+f"(d[26]),"+f"(d[27]),"+f"(d[28]),"+f"(d[29]),"+f"(d[30]),"+f"(d[31]),"+f"(d[32]),"+f"(d[33]),"+f"(d[34]),"+f"(d[35]),"+f"(d[36]),"+f"(d[37]),"+f"(d[38]),"+f"(d[39]) : "r"(a[0]),"r"(a[1]),"r"(a[2]),"r"(a[3]),"l"(db),"r"(sc));
}
__device__ __forceinline__ void wg_rs96_0(float* d, const uint32_t* a, uint64_t db, int sc) {
  asm volatile("{.reg .pred p; setp.ne.b32 p, %53, 0; wgmma.mma_async.sync.aligned.m64n96k16.f32.bf16.bf16 {%0,%1,%2,%3,%4,%5,%6,%7,%8,%9,%10,%11,%12,%13,%14,%15,%16,%17,%18,%19,%20,%21,%22,%23,%24,%25,%26,%27,%28,%29,%30,%31,%32,%33,%34,%35,%36,%37,%38,%39,%40,%41,%42,%43,%44,%45,%46,%47}, {%48,%49,%50,%51}, %52, p, 1, 1, 0;}"
    : "+f"(d[0]),"+f"(d[1]),"+f"(d[2]),"+f"(d[3]),"+f"(d[4]),"+f"(d[5]),"+f"(d[6]),"+f"(d[7]),"+f"(d[8]),"+f"(d[9]),"+f"(d[10]),"+f"(d[11]),"+f"(d[12]),"+f"(d[13]),"+f"(d[14]),"+f"(d[15]),"+f"(d[16]),"+f"(d[17]),"+f"(d[18]),"+f"(d[19]),"+f"(d[20]),"+f"(d[21]),"+f"(d[22]),"+f"(d[23]),"+f"(d[24]),"+f"(d[25]),"+f"(d[26]),"+f"(d[27]),"+f"(d[28]),"+f"(d[29]),"+f"(d[30]),"+f"(d[31]),"+f"(d[32]),"+f"(d[33]),"+f"(d[34]),"+f"(d[35]),"+f"(d[36]),"+f"(d[37]),"+f"(d[38]),"+f"(d[39]),"+f"(d[40]),"+f"(d[41]),"+f"(d[42]),"+f"(d[43]),"+f"(d[44]),"+f"(d[45]),"+f"(d[46]),"+f"(d[47]) : "r"(a[0]),"r"(a[1]),"r"(a[2]),"r"(a[3]),"l"(db),"r"(sc));
}
__device__ __forceinline__ void wg_rs112_0(float* d, const uint32_t* a, uint64_t db, int sc) {
  asm volatile("{.reg .pred p; setp.ne.b32 p, %61, 0; wgmma.mma_async.sync.aligned.m64n112k16.f32.bf16.bf16 {%0,%1,%2,%3,%4,%5,%6,%7,%8,%9,%10,%11,%12,%13,%14,%15,%16,%17,%18,%19,%20,%21,%22,%23,%24,%25,%26,%27,%28,%29,%30,%31,%32,%33,%34,%35,%36,%37,%38,%39,%40,%41,%42,%43,%44,%45,%46,%47,%48,%49,%50,%51,%52,%53,%54,%55}, {%56,%57,%58,%59}, %60, p, 1, 1, 0;}"
    : "+f"(d[0]),"+f"(d[1]),"+f"(d[2]),"+f"(d[3]),"+f"(d[4]),"+f"(d[5]),"+f"(d[6]),"+f"(d[7]),"+f"(d[8]),"+f"(d[9]),"+f"(d[10]),"+f"(d[11]),"+f"(d[12]),"+f"(d[13]),"+f"(d[14]),"+f"(d[15]),"+f"(d[16]),"+f"(d[17]),"+f"(d[18]),"+f"(d[19]),"+f"(d[20]),"+f"(d[21]),"+f"(d[22]),"+f"(d[23]),"+f"(d[24]),"+f"(d[25]),"+f"(d[26]),"+f"(d[27]),"+f"(d[28]),"+f"(d[29]),"+f"(d[30]),"+f"(d[31]),"+f"(d[32]),"+f"(d[33]),"+f"(d[34]),"+f"(d[35]),"+f"(d[36]),"+f"(d[37]),"+f"(d[38]),"+f"(d[39]),"+f"(d[40]),"+f"(d[41]),"+f"(d[42]),"+f"(d[43]),"+f"(d[44]),"+f"(d[45]),"+f"(d[46]),"+f"(d[47]),"+f"(d[48]),"+f"(d[49]),"+f"(d[50]),"+f"(d[51]),"+f"(d[52]),"+f"(d[53]),"+f"(d[54]),"+f"(d[55]) : "r"(a[0]),"r"(a[1]),"r"(a[2]),"r"(a[3]),"l"(db),"r"(sc));
}
__device__ __forceinline__ void wg_rs128_0(float* d, const uint32_t* a, uint64_t db, int sc) {
  asm volatile("{.reg .pred p; setp.ne.b32 p, %69, 0; wgmma.mma_async.sync.aligned.m64n128k16.f32.bf16.bf16 {%0,%1,%2,%3,%4,%5,%6,%7,%8,%9,%10,%11,%12,%13,%14,%15,%16,%17,%18,%19,%20,%21,%22,%23,%24,%25,%26,%27,%28,%29,%30,%31,%32,%33,%34,%35,%36,%37,%38,%39,%40,%41,%42,%43,%44,%45,%46,%47,%48,%49,%50,%51,%52,%53,%54,%55,%56,%57,%58,%59,%60,%61,%62,%63}, {%64,%65,%66,%67}, %68, p, 1, 1, 0;}"
    : "+f"(d[0]),"+f"(d[1]),"+f"(d[2]),"+f"(d[3]),"+f"(d[4]),"+f"(d[5]),"+f"(d[6]),"+f"(d[7]),"+f"(d[8]),"+f"(d[9]),"+f"(d[10]),"+f"(d[11]),"+f"(d[12]),"+f"(d[13]),"+f"(d[14]),"+f"(d[15]),"+f"(d[16]),"+f"(d[17]),"+f"(d[18]),"+f"(d[19]),"+f"(d[20]),"+f"(d[21]),"+f"(d[22]),"+f"(d[23]),"+f"(d[24]),"+f"(d[25]),"+f"(d[26]),"+f"(d[27]),"+f"(d[28]),"+f"(d[29]),"+f"(d[30]),"+f"(d[31]),"+f"(d[32]),"+f"(d[33]),"+f"(d[34]),"+f"(d[35]),"+f"(d[36]),"+f"(d[37]),"+f"(d[38]),"+f"(d[39]),"+f"(d[40]),"+f"(d[41]),"+f"(d[42]),"+f"(d[43]),"+f"(d[44]),"+f"(d[45]),"+f"(d[46]),"+f"(d[47]),"+f"(d[48]),"+f"(d[49]),"+f"(d[50]),"+f"(d[51]),"+f"(d[52]),"+f"(d[53]),"+f"(d[54]),"+f"(d[55]),"+f"(d[56]),"+f"(d[57]),"+f"(d[58]),"+f"(d[59]),"+f"(d[60]),"+f"(d[61]),"+f"(d[62]),"+f"(d[63]) : "r"(a[0]),"r"(a[1]),"r"(a[2]),"r"(a[3]),"l"(db),"r"(sc));
}
__device__ __forceinline__ void wg_rs144_0(float* d, const uint32_t* a, uint64_t db, int sc) {
  asm volatile("{.reg .pred p; setp.ne.b32 p, %77, 0; wgmma.mma_async.sync.aligned.m64n144k16.f32.bf16.bf16 {%0,%1,%2,%3,%4,%5,%6,%7,%8,%9,%10,%11,%12,%13,%14,%15,%16,%17,%18,%19,%20,%21,%22,%23,%24,%25,%26,%27,%28,%29,%30,%31,%32,%33,%34,%35,%36,%37,%38,%39,%40,%41,%42,%43,%44,%45,%46,%47,%48,%49,%50,%51,%52,%53,%54,%55,%56,%57,%58,%59,%60,%61,%62,%63,%64,%65,%66,%67,%68,%69,%70,%71}, {%72,%73,%74,%75}, %76, p, 1, 1, 0;}"
    : "+f"(d[0]),"+f"(d[1]),"+f"(d[2]),"+f"(d[3]),"+f"(d[4]),"+f"(d[5]),"+f"(d[6]),"+f"(d[7]),"+f"(d[8]),"+f"(d[9]),"+f"(d[10]),"+f"(d[11]),"+f"(d[12]),"+f"(d[13]),"+f"(d[14]),"+f"(d[15]),"+f"(d[16]),"+f"(d[17]),"+f"(d[18]),"+f"(d[19]),"+f"(d[20]),"+f"(d[21]),"+f"(d[22]),"+f"(d[23]),"+f"(d[24]),"+f"(d[25]),"+f"(d[26]),"+f"(d[27]),"+f"(d[28]),"+f"(d[29]),"+f"(d[30]),"+f"(d[31]),"+f"(d[32]),"+f"(d[33]),"+f"(d[34]),"+f"(d[35]),"+f"(d[36]),"+f"(d[37]),"+f"(d[38]),"+f"(d[39]),"+f"(d[40]),"+f"(d[41]),"+f"(d[42]),"+f"(d[43]),"+f"(d[44]),"+f"(d[45]),"+f"(d[46]),"+f"(d[47]),"+f"(d[48]),"+f"(d[49]),"+f"(d[50]),"+f"(d[51]),"+f"(d[52]),"+f"(d[53]),"+f"(d[54]),"+f"(d[55]),"+f"(d[56]),"+f"(d[57]),"+f"(d[58]),"+f"(d[59]),"+f"(d[60]),"+f"(d[61]),"+f"(d[62]),"+f"(d[63]),"+f"(d[64]),"+f"(d[65]),"+f"(d[66]),"+f"(d[67]),"+f"(d[68]),"+f"(d[69]),"+f"(d[70]),"+f"(d[71]) : "r"(a[0]),"r"(a[1]),"r"(a[2]),"r"(a[3]),"l"(db),"r"(sc));
}
__device__ __forceinline__ void wg_rs160_0(float* d, const uint32_t* a, uint64_t db, int sc) {
  asm volatile("{.reg .pred p; setp.ne.b32 p, %85, 0; wgmma.mma_async.sync.aligned.m64n160k16.f32.bf16.bf16 {%0,%1,%2,%3,%4,%5,%6,%7,%8,%9,%10,%11,%12,%13,%14,%15,%16,%17,%18,%19,%20,%21,%22,%23,%24,%25,%26,%27,%28,%29,%30,%31,%32,%33,%34,%35,%36,%37,%38,%39,%40,%41,%42,%43,%44,%45,%46,%47,%48,%49,%50,%51,%52,%53,%54,%55,%56,%57,%58,%59,%60,%61,%62,%63,%64,%65,%66,%67,%68,%69,%70,%71,%72,%73,%74,%75,%76,%77,%78,%79}, {%80,%81,%82,%83}, %84, p, 1, 1, 0;}"
    : "+f"(d[0]),"+f"(d[1]),"+f"(d[2]),"+f"(d[3]),"+f"(d[4]),"+f"(d[5]),"+f"(d[6]),"+f"(d[7]),"+f"(d[8]),"+f"(d[9]),"+f"(d[10]),"+f"(d[11]),"+f"(d[12]),"+f"(d[13]),"+f"(d[14]),"+f"(d[15]),"+f"(d[16]),"+f"(d[17]),"+f"(d[18]),"+f"(d[19]),"+f"(d[20]),"+f"(d[21]),"+f"(d[22]),"+f"(d[23]),"+f"(d[24]),"+f"(d[25]),"+f"(d[26]),"+f"(d[27]),"+f"(d[28]),"+f"(d[29]),"+f"(d[30]),"+f"(d[31]),"+f"(d[32]),"+f"(d[33]),"+f"(d[34]),"+f"(d[35]),"+f"(d[36]),"+f"(d[37]),"+f"(d[38]),"+f"(d[39]),"+f"(d[40]),"+f"(d[41]),"+f"(d[42]),"+f"(d[43]),"+f"(d[44]),"+f"(d[45]),"+f"(d[46]),"+f"(d[47]),"+f"(d[48]),"+f"(d[49]),"+f"(d[50]),"+f"(d[51]),"+f"(d[52]),"+f"(d[53]),"+f"(d[54]),"+f"(d[55]),"+f"(d[56]),"+f"(d[57]),"+f"(d[58]),"+f"(d[59]),"+f"(d[60]),"+f"(d[61]),"+f"(d[62]),"+f"(d[63]),"+f"(d[64]),"+f"(d[65]),"+f"(d[66]),"+f"(d[67]),"+f"(d[68]),"+f"(d[69]),"+f"(d[70]),"+f"(d[71]),"+f"(d[72]),"+f"(d[73]),"+f"(d[74]),"+f"(d[75]),"+f"(d[76]),"+f"(d[77]),"+f"(d[78]),"+f"(d[79]) : "r"(a[0]),"r"(a[1]),"r"(a[2]),"r"(a[3]),"l"(db),"r"(sc));
}
__device__ __forceinline__ void wg_rs176_0(float* d, const uint32_t* a, uint64_t db, int sc) {
  asm volatile("{.reg .pred p; setp.ne.b32 p, %93, 0; wgmma.mma_async.sync.aligned.m64n176k16.f32.bf16.bf16 {%0,%1,%2,%3,%4,%5,%6,%7,%8,%9,%10,%11,%12,%13,%14,%15,%16,%17,%18,%19,%20,%21,%22,%23,%24,%25,%26,%27,%28,%29,%30,%31,%32,%33,%34,%35,%36,%37,%38,%39,%40,%41,%42,%43,%44,%45,%46,%47,%48,%49,%50,%51,%52,%53,%54,%55,%56,%57,%58,%59,%60,%61,%62,%63,%64,%65,%66,%67,%68,%69,%70,%71,%72,%73,%74,%75,%76,%77,%78,%79,%80,%81,%82,%83,%84,%85,%86,%87}, {%88,%89,%90,%91}, %92, p, 1, 1, 0;}"
    : "+f"(d[0]),"+f"(d[1]),"+f"(d[2]),"+f"(d[3]),"+f"(d[4]),"+f"(d[5]),"+f"(d[6]),"+f"(d[7]),"+f"(d[8]),"+f"(d[9]),"+f"(d[10]),"+f"(d[11]),"+f"(d[12]),"+f"(d[13]),"+f"(d[14]),"+f"(d[15]),"+f"(d[16]),"+f"(d[17]),"+f"(d[18]),"+f"(d[19]),"+f"(d[20]),"+f"(d[21]),"+f"(d[22]),"+f"(d[23]),"+f"(d[24]),"+f"(d[25]),"+f"(d[26]),"+f"(d[27]),"+f"(d[28]),"+f"(d[29]),"+f"(d[30]),"+f"(d[31]),"+f"(d[32]),"+f"(d[33]),"+f"(d[34]),"+f"(d[35]),"+f"(d[36]),"+f"(d[37]),"+f"(d[38]),"+f"(d[39]),"+f"(d[40]),"+f"(d[41]),"+f"(d[42]),"+f"(d[43]),"+f"(d[44]),"+f"(d[45]),"+f"(d[46]),"+f"(d[47]),"+f"(d[48]),"+f"(d[49]),"+f"(d[50]),"+f"(d[51]),"+f"(d[52]),"+f"(d[53]),"+f"(d[54]),"+f"(d[55]),"+f"(d[56]),"+f"(d[57]),"+f"(d[58]),"+f"(d[59]),"+f"(d[60]),"+f"(d[61]),"+f"(d[62]),"+f"(d[63]),"+f"(d[64]),"+f"(d[65]),"+f"(d[66]),"+f"(d[67]),"+f"(d[68]),"+f"(d[69]),"+f"(d[70]),"+f"(d[71]),"+f"(d[72]),"+f"(d[73]),"+f"(d[74]),"+f"(d[75]),"+f"(d[76]),"+f"(d[77]),"+f"(d[78]),"+f"(d[79]),"+f"(d[80]),"+f"(d[81]),"+f"(d[82]),"+f"(d[83]),"+f"(d[84]),"+f"(d[85]),"+f"(d[86]),"+f"(d[87]) : "r"(a[0]),"r"(a[1]),"r"(a[2]),"r"(a[3]),"l"(db),"r"(sc));
}
__device__ __forceinline__ void wg_rs192_0(float* d, const uint32_t* a, uint64_t db, int sc) {
  asm volatile("{.reg .pred p; setp.ne.b32 p, %101, 0; wgmma.mma_async.sync.aligned.m64n192k16.f32.bf16.bf16 {%0,%1,%2,%3,%4,%5,%6,%7,%8,%9,%10,%11,%12,%13,%14,%15,%16,%17,%18,%19,%20,%21,%22,%23,%24,%25,%26,%27,%28,%29,%30,%31,%32,%33,%34,%35,%36,%37,%38,%39,%40,%41,%42,%43,%44,%45,%46,%47,%48,%49,%50,%51,%52,%53,%54,%55,%56,%57,%58,%59,%60,%61,%62,%63,%64,%65,%66,%67,%68,%69,%70,%71,%72,%73,%74,%75,%76,%77,%78,%79,%80,%81,%82,%83,%84,%85,%86,%87,%88,%89,%90,%91,%92,%93,%94,%95}, {%96,%97,%98,%99}, %100, p, 1, 1, 0;}"
    : "+f"(d[0]),"+f"(d[1]),"+f"(d[2]),"+f"(d[3]),"+f"(d[4]),"+f"(d[5]),"+f"(d[6]),"+f"(d[7]),"+f"(d[8]),"+f"(d[9]),"+f"(d[10]),"+f"(d[11]),"+f"(d[12]),"+f"(d[13]),"+f"(d[14]),"+f"(d[15]),"+f"(d[16]),"+f"(d[17]),"+f"(d[18]),"+f"(d[19]),"+f"(d[20]),"+f"(d[21]),"+f"(d[22]),"+f"(d[23]),"+f"(d[24]),"+f"(d[25]),"+f"(d[26]),"+f"(d[27]),"+f"(d[28]),"+f"(d[29]),"+f"(d[30]),"+f"(d[31]),"+f"(d[32]),"+f"(d[33]),"+f"(d[34]),"+f"(d[35]),"+f"(d[36]),"+f"(d[37]),"+f"(d[38]),"+f"(d[39]),"+f"(d[40]),"+f"(d[41]),"+f"(d[42]),"+f"(d[43]),"+f"(d[44]),"+f"(d[45]),"+f"(d[46]),"+f"(d[47]),"+f"(d[48]),"+f"(d[49]),"+f"(d[50]),"+f"(d[51]),"+f"(d[52]),"+f"(d[53]),"+f"(d[54]),"+f"(d[55]),"+f"(d[56]),"+f"(d[57]),"+f"(d[58]),"+f"(d[59]),"+f"(d[60]),"+f"(d[61]),"+f"(d[62]),"+f"(d[63]),"+f"(d[64]),"+f"(d[65]),"+f"(d[66]),"+f"(d[67]),"+f"(d[68]),"+f"(d[69]),"+f"(d[70]),"+f"(d[71]),"+f"(d[72]),"+f"(d[73]),"+f"(d[74]),"+f"(d[75]),"+f"(d[76]),"+f"(d[77]),"+f"(d[78]),"+f"(d[79]),"+f"(d[80]),"+f"(d[81]),"+f"(d[82]),"+f"(d[83]),"+f"(d[84]),"+f"(d[85]),"+f"(d[86]),"+f"(d[87]),"+f"(d[88]),"+f"(d[89]),"+f"(d[90]),"+f"(d[91]),"+f"(d[92]),"+f"(d[93]),"+f"(d[94]),"+f"(d[95]) : "r"(a[0]),"r"(a[1]),"r"(a[2]),"r"(a[3]),"l"(db),"r"(sc));
}
__device__ __forceinline__ void wg_ss192_11(float* d, uint64_t da, uint64_t db, int sc) {
  asm volatile("{.reg .pred p; setp.ne.b32 p, %98, 0; wgmma.mma_async.sync.aligned.m64n192k16.f32.bf16.bf16 {%0,%1,%2,%3,%4,%5,%6,%7,%8,%9,%10,%11,%12,%13,%14,%15,%16,%17,%18,%19,%20,%21,%22,%23,%24,%25,%26,%27,%28,%29,%30,%31,%32,%33,%34,%35,%36,%37,%38,%39,%40,%41,%42,%43,%44,%45,%46,%47,%48,%49,%50,%51,%52,%53,%54,%55,%56,%57,%58,%59,%60,%61,%62,%63,%64,%65,%66,%67,%68,%69,%70,%71,%72,%73,%74,%75,%76,%77,%78,%79,%80,%81,%82,%83,%84,%85,%86,%87,%88,%89,%90,%91,%92,%93,%94,%95}, %96, %97, p, 1, 1, 1, 1;}"
    : "+f"(d[0]),"+f"(d[1]),"+f"(d[2]),"+f"(d[3]),"+f"(d[4]),"+f"(d[5]),"+f"(d[6]),"+f"(d[7]),"+f"(d[8]),"+f"(d[9]),"+f"(d[10]),"+f"(d[11]),"+f"(d[12]),"+f"(d[13]),"+f"(d[14]),"+f"(d[15]),"+f"(d[16]),"+f"(d[17]),"+f"(d[18]),"+f"(d[19]),"+f"(d[20]),"+f"(d[21]),"+f"(d[22]),"+f"(d[23]),"+f"(d[24]),"+f"(d[25]),"+f"(d[26]),"+f"(d[27]),"+f"(d[28]),"+f"(d[29]),"+f"(d[30]),"+f"(d[31]),"+f"(d[32]),"+f"(d[33]),"+f"(d[34]),"+f"(d[35]),"+f"(d[36]),"+f"(d[37]),"+f"(d[38]),"+f"(d[39]),"+f"(d[40]),"+f"(d[41]),"+f"(d[42]),"+f"(d[43]),"+f"(d[44]),"+f"(d[45]),"+f"(d[46]),"+f"(d[47]),"+f"(d[48]),"+f"(d[49]),"+f"(d[50]),"+f"(d[51]),"+f"(d[52]),"+f"(d[53]),"+f"(d[54]),"+f"(d[55]),"+f"(d[56]),"+f"(d[57]),"+f"(d[58]),"+f"(d[59]),"+f"(d[60]),"+f"(d[61]),"+f"(d[62]),"+f"(d[63]),"+f"(d[64]),"+f"(d[65]),"+f"(d[66]),"+f"(d[67]),"+f"(d[68]),"+f"(d[69]),"+f"(d[70]),"+f"(d[71]),"+f"(d[72]),"+f"(d[73]),"+f"(d[74]),"+f"(d[75]),"+f"(d[76]),"+f"(d[77]),"+f"(d[78]),"+f"(d[79]),"+f"(d[80]),"+f"(d[81]),"+f"(d[82]),"+f"(d[83]),"+f"(d[84]),"+f"(d[85]),"+f"(d[86]),"+f"(d[87]),"+f"(d[88]),"+f"(d[89]),"+f"(d[90]),"+f"(d[91]),"+f"(d[92]),"+f"(d[93]),"+f"(d[94]),"+f"(d[95]) : "l"(da),"l"(db),"r"(sc));
}
__device__ __forceinline__ void wg_ss192_01(float* d, uint64_t da, uint64_t db, int sc) {
  asm volatile("{.reg .pred p; setp.ne.b32 p, %98, 0; wgmma.mma_async.sync.aligned.m64n192k16.f32.bf16.bf16 {%0,%1,%2,%3,%4,%5,%6,%7,%8,%9,%10,%11,%12,%13,%14,%15,%16,%17,%18,%19,%20,%21,%22,%23,%24,%25,%26,%27,%28,%29,%30,%31,%32,%33,%34,%35,%36,%37,%38,%39,%40,%41,%42,%43,%44,%45,%46,%47,%48,%49,%50,%51,%52,%53,%54,%55,%56,%57,%58,%59,%60,%61,%62,%63,%64,%65,%66,%67,%68,%69,%70,%71,%72,%73,%74,%75,%76,%77,%78,%79,%80,%81,%82,%83,%84,%85,%86,%87,%88,%89,%90,%91,%92,%93,%94,%95}, %96, %97, p, 1, 1, 0, 1;}"
    : "+f"(d[0]),"+f"(d[1]),"+f"(d[2]),"+f"(d[3]),"+f"(d[4]),"+f"(d[5]),"+f"(d[6]),"+f"(d[7]),"+f"(d[8]),"+f"(d[9]),"+f"(d[10]),"+f"(d[11]),"+f"(d[12]),"+f"(d[13]),"+f"(d[14]),"+f"(d[15]),"+f"(d[16]),"+f"(d[17]),"+f"(d[18]),"+f"(d[19]),"+f"(d[20]),"+f"(d[21]),"+f"(d[22]),"+f"(d[23]),"+f"(d[24]),"+f"(d[25]),"+f"(d[26]),"+f"(d[27]),"+f"(d[28]),"+f"(d[29]),"+f"(d[30]),"+f"(d[31]),"+f"(d[32]),"+f"(d[33]),"+f"(d[34]),"+f"(d[35]),"+f"(d[36]),"+f"(d[37]),"+f"(d[38]),"+f"(d[39]),"+f"(d[40]),"+f"(d[41]),"+f"(d[42]),"+f"(d[43]),"+f"(d[44]),"+f"(d[45]),"+f"(d[46]),"+f"(d[47]),"+f"(d[48]),"+f"(d[49]),"+f"(d[50]),"+f"(d[51]),"+f"(d[52]),"+f"(d[53]),"+f"(d[54]),"+f"(d[55]),"+f"(d[56]),"+f"(d[57]),"+f"(d[58]),"+f"(d[59]),"+f"(d[60]),"+f"(d[61]),"+f"(d[62]),"+f"(d[63]),"+f"(d[64]),"+f"(d[65]),"+f"(d[66]),"+f"(d[67]),"+f"(d[68]),"+f"(d[69]),"+f"(d[70]),"+f"(d[71]),"+f"(d[72]),"+f"(d[73]),"+f"(d[74]),"+f"(d[75]),"+f"(d[76]),"+f"(d[77]),"+f"(d[78]),"+f"(d[79]),"+f"(d[80]),"+f"(d[81]),"+f"(d[82]),"+f"(d[83]),"+f"(d[84]),"+f"(d[85]),"+f"(d[86]),"+f"(d[87]),"+f"(d[88]),"+f"(d[89]),"+f"(d[90]),"+f"(d[91]),"+f"(d[92]),"+f"(d[93]),"+f"(d[94]),"+f"(d[95]) : "l"(da),"l"(db),"r"(sc));
}
__device__ __forceinline__ void wg_ss160_01(float* d, uint64_t da, uint64_t db, int sc) {
  asm volatile("{.reg .pred p; setp.ne.b32 p, %82, 0; wgmma.mma_async.sync.aligned.m64n160k16.f32.bf16.bf16 {%0,%1,%2,%3,%4,%5,%6,%7,%8,%9,%10,%11,%12,%13,%14,%15,%16,%17,%18,%19,%20,%21,%22,%23,%24,%25,%26,%27,%28,%29,%30,%31,%32,%33,%34,%35,%36,%37,%38,%39,%40,%41,%42,%43,%44,%45,%46,%47,%48,%49,%50,%51,%52,%53,%54,%55,%56,%57,%58,%59,%60,%61,%62,%63,%64,%65,%66,%67,%68,%69,%70,%71,%72,%73,%74,%75,%76,%77,%78,%79}, %80, %81, p, 1, 1, 0, 1;}"
    : "+f"(d[0]),"+f"(d[1]),"+f"(d[2]),"+f"(d[3]),"+f"(d[4]),"+f"(d[5]),"+f"(d[6]),"+f"(d[7]),"+f"(d[8]),"+f"(d[9]),"+f"(d[10]),"+f"(d[11]),"+f"(d[12]),"+f"(d[13]),"+f"(d[14]),"+f"(d[15]),"+f"(d[16]),"+f"(d[17]),"+f"(d[18]),"+f"(d[19]),"+f"(d[20]),"+f"(d[21]),"+f"(d[22]),"+f"(d[23]),"+f"(d[24]),"+f"(d[25]),"+f"(d[26]),"+f"(d[27]),"+f"(d[28]),"+f"(d[29]),"+f"(d[30]),"+f"(d[31]),"+f"(d[32]),"+f"(d[33]),"+f"(d[34]),"+f"(d[35]),"+f"(d[36]),"+f"(d[37]),"+f"(d[38]),"+f"(d[39]),"+f"(d[40]),"+f"(d[41]),"+f"(d[42]),"+f"(d[43]),"+f"(d[44]),"+f"(d[45]),"+f"(d[46]),"+f"(d[47]),"+f"(d[48]),"+f"(d[49]),"+f"(d[50]),"+f"(d[51]),"+f"(d[52]),"+f"(d[53]),"+f"(d[54]),"+f"(d[55]),"+f"(d[56]),"+f"(d[57]),"+f"(d[58]),"+f"(d[59]),"+f"(d[60]),"+f"(d[61]),"+f"(d[62]),"+f"(d[63]),"+f"(d[64]),"+f"(d[65]),"+f"(d[66]),"+f"(d[67]),"+f"(d[68]),"+f"(d[69]),"+f"(d[70]),"+f"(d[71]),"+f"(d[72]),"+f"(d[73]),"+f"(d[74]),"+f"(d[75]),"+f"(d[76]),"+f"(d[77]),"+f"(d[78]),"+f"(d[79]) : "l"(da),"l"(db),"r"(sc));
}
__device__ __forceinline__ void wg_ss96_01(float* d, uint64_t da, uint64_t db, int sc) {
  asm volatile("{.reg .pred p; setp.ne.b32 p, %50, 0; wgmma.mma_async.sync.aligned.m64n96k16.f32.bf16.bf16 {%0,%1,%2,%3,%4,%5,%6,%7,%8,%9,%10,%11,%12,%13,%14,%15,%16,%17,%18,%19,%20,%21,%22,%23,%24,%25,%26,%27,%28,%29,%30,%31,%32,%33,%34,%35,%36,%37,%38,%39,%40,%41,%42,%43,%44,%45,%46,%47}, %48, %49, p, 1, 1, 0, 1;}"
    : "+f"(d[0]),"+f"(d[1]),"+f"(d[2]),"+f"(d[3]),"+f"(d[4]),"+f"(d[5]),"+f"(d[6]),"+f"(d[7]),"+f"(d[8]),"+f"(d[9]),"+f"(d[10]),"+f"(d[11]),"+f"(d[12]),"+f"(d[13]),"+f"(d[14]),"+f"(d[15]),"+f"(d[16]),"+f"(d[17]),"+f"(d[18]),"+f"(d[19]),"+f"(d[20]),"+f"(d[21]),"+f"(d[22]),"+f"(d[23]),"+f"(d[24]),"+f"(d[25]),"+f"(d[26]),"+f"(d[27]),"+f"(d[28]),"+f"(d[29]),"+f"(d[30]),"+f"(d[31]),"+f"(d[32]),"+f"(d[33]),"+f"(d[34]),"+f"(d[35]),"+f"(d[36]),"+f"(d[37]),"+f"(d[38]),"+f"(d[39]),"+f"(d[40]),"+f"(d[41]),"+f"(d[42]),"+f"(d[43]),"+f"(d[44]),"+f"(d[45]),"+f"(d[46]),"+f"(d[47]) : "l"(da),"l"(db),"r"(sc));
}
__device__ __forceinline__ void wg_ss64_01(float* d, uint64_t da, uint64_t db, int sc) {
  asm volatile("{.reg .pred p; setp.ne.b32 p, %34, 0; wgmma.mma_async.sync.aligned.m64n64k16.f32.bf16.bf16 {%0,%1,%2,%3,%4,%5,%6,%7,%8,%9,%10,%11,%12,%13,%14,%15,%16,%17,%18,%19,%20,%21,%22,%23,%24,%25,%26,%27,%28,%29,%30,%31}, %32, %33, p, 1, 1, 0, 1;}"
    : "+f"(d[0]),"+f"(d[1]),"+f"(d[2]),"+f"(d[3]),"+f"(d[4]),"+f"(d[5]),"+f"(d[6]),"+f"(d[7]),"+f"(d[8]),"+f"(d[9]),"+f"(d[10]),"+f"(d[11]),"+f"(d[12]),"+f"(d[13]),"+f"(d[14]),"+f"(d[15]),"+f"(d[16]),"+f"(d[17]),"+f"(d[18]),"+f"(d[19]),"+f"(d[20]),"+f"(d[21]),"+f"(d[22]),"+f"(d[23]),"+f"(d[24]),"+f"(d[25]),"+f"(d[26]),"+f"(d[27]),"+f"(d[28]),"+f"(d[29]),"+f"(d[30]),"+f"(d[31]) : "l"(da),"l"(db),"r"(sc));
}
__device__ __forceinline__ void wg_rs160_1(float* d, const uint32_t* a, uint64_t db, int sc) {
  asm volatile("{.reg .pred p; setp.ne.b32 p, %85, 0; wgmma.mma_async.sync.aligned.m64n160k16.f32.bf16.bf16 {%0,%1,%2,%3,%4,%5,%6,%7,%8,%9,%10,%11,%12,%13,%14,%15,%16,%17,%18,%19,%20,%21,%22,%23,%24,%25,%26,%27,%28,%29,%30,%31,%32,%33,%34,%35,%36,%37,%38,%39,%40,%41,%42,%43,%44,%45,%46,%47,%48,%49,%50,%51,%52,%53,%54,%55,%56,%57,%58,%59,%60,%61,%62,%63,%64,%65,%66,%67,%68,%69,%70,%71,%72,%73,%74,%75,%76,%77,%78,%79}, {%80,%81,%82,%83}, %84, p, 1, 1, 1;}"
    : "+f"(d[0]),"+f"(d[1]),"+f"(d[2]),"+f"(d[3]),"+f"(d[4]),"+f"(d[5]),"+f"(d[6]),"+f"(d[7]),"+f"(d[8]),"+f"(d[9]),"+f"(d[10]),"+f"(d[11]),"+f"(d[12]),"+f"(d[13]),"+f"(d[14]),"+f"(d[15]),"+f"(d[16]),"+f"(d[17]),"+f"(d[18]),"+f"(d[19]),"+f"(d[20]),"+f"(d[21]),"+f"(d[22]),"+f"(d[23]),"+f"(d[24]),"+f"(d[25]),"+f"(d[26]),"+f"(d[27]),"+f"(d[28]),"+f"(d[29]),"+f"(d[30]),"+f"(d[31]),"+f"(d[32]),"+f"(d[33]),"+f"(d[34]),"+f"(d[35]),"+f"(d[36]),"+f"(d[37]),"+f"(d[38]),"+f"(d[39]),"+f"(d[40]),"+f"(d[41]),"+f"(d[42]),"+f"(d[43]),"+f"(d[44]),"+f"(d[45]),"+f"(d[46]),"+f"(d[47]),"+f"(d[48]),"+f"(d[49]),"+f"(d[50]),"+f"(d[51]),"+f"(d[52]),"+f"(d[53]),"+f"(d[54]),"+f"(d[55]),"+f"(d[56]),"+f"(d[57]),"+f"(d[58]),"+f"(d[59]),"+f"(d[60]),"+f"(d[61]),"+f"(d[62]),"+f"(d[63]),"+f"(d[64]),"+f"(d[65]),"+f"(d[66]),"+f"(d[67]),"+f"(d[68]),"+f"(d[69]),"+f"(d[70]),"+f"(d[71]),"+f"(d[72]),"+f"(d[73]),"+f"(d[74]),"+f"(d[75]),"+f"(d[76]),"+f"(d[77]),"+f"(d[78]),"+f"(d[79]) : "r"(a[0]),"r"(a[1]),"r"(a[2]),"r"(a[3]),"l"(db),"r"(sc));
}
__device__ __forceinline__ void wg_ss8_10(float* d, uint64_t da, uint64_t db, int sc) {
  asm volatile("{.reg .pred p; setp.ne.b32 p, %6, 0; wgmma.mma_async.sync.aligned.m64n8k16.f32.bf16.bf16 {%0,%1,%2,%3}, %4, %5, p, 1, 1, 1, 0;}"
    : "+f"(d[0]),"+f"(d[1]),"+f"(d[2]),"+f"(d[3]) : "l"(da),"l"(db),"r"(sc));
}

constexpr uint32_t DB = 1024;
constexpr int WSLOT = 24576, NW = 6, ASLOT = 8192, ARING = 4 * ASLOT;
constexpr int OFF_A = NW * WSLOT;
constexpr int OFF_PB = OFF_A + 2 * ARING;
constexpr int OFF_CV = OFF_PB + 16384, OFF_ST = OFF_CV + 768, OFF_TS = OFF_ST + 256, OFF_MODR = OFF_TS + 512, OFF_BAR = OFF_MODR + 80, SMEM_BYTES = OFF_BAR + 1168;
constexpr int OFF_BX = OFF_PB, OFF_AX = OFF_BX + 12288, OFF_RT = OFF_AX + 2048, OFF_GB = OFF_RT + 512, OFF_CO = OFF_CV;
constexpr int OFF_UV = 5 * WSLOT, OFF_UVE = OFF_PB, OFF_SX = OFF_A + ARING + 3 * ASLOT, OFF_X1 = 2 * WSLOT + ASLOT, OFF_XCH = WSLOT;
constexpr int OFF_Q = 0, KV_V = 4096, KV_H = 8192, F_E = 16, F_O = 4176, OFF_TAP = 168576, OFF_MR = OFF_A + 3 * ASLOT;
constexpr uint64_t pk5(int a, int b, int c, int d, int e) { return (uint64_t)(a / 128) | (uint64_t)(b / 128) << 12 | (uint64_t)(c / 128) << 24 | (uint64_t)(d / 128) << 36 | (uint64_t)(e / 128) << 48; }
constexpr uint64_t T_KV = pk5(20480, 30720, 40960, 180224, 190464), T_F = pk5(51200, 59648, 200192, 147456, 155904), T_X = pk5(208512, 164352, 68096, 208512, 164352),
                   T_P = pk5(131072, OFF_PB, 114688, 131072, OFF_PB);
__host__ __device__ __forceinline__ uint32_t tab(uint64_t t, int c) { return ((uint32_t)(t >> (12 * c)) & 0xFFF) << 7; }
enum { B_KV = 0, B_FRAW = 5, B_Q = 10, B_XR = 16, B_MR = B_XR + 5, B_QTOK, B_ST1, B_MODR, B_S3 = B_MODR + 5, B_FIN, B_FL = 32, B_PFULL = B_FL + 5, B_PEMPTY = B_PFULL + 5, B_FRDY = B_PEMPTY + 5,
       B_EXT = B_FRDY + 5, B_QTD, B_LAG, B_GB, B_UVD, B_TURN, B_FULL = 60, B_RETRY = B_FULL + 33, B_XFREE = B_RETRY + 9, B_BX, B_UVB, B_UVE, B_SX, B_EMPTY = 109 };
static_assert(B_MODR + 5 <= B_FL && B_UVD < B_FULL && B_SX + 2 == B_EMPTY - 1, "barrier groups");
#define BAR(i) (base + OFF_BAR + 8 * (i))

constexpr int NE = 18;
struct Maps { CUtensorMap km, v, q, kh, tap, wm, w1s, w3s, xs, w1, w3, w1e, w3e, x1s, x1b, w2a, w2b, outa, outb; };
struct Ptrs { const bf16 *ssmk, *c, *ssmd; Scratch* g; uint64_t prog, cprog[2]; int boff, te, pe, th, th2, zero; uint32_t xd, aw, cn, c0, fin, turn, mr2, m3, seq; float one; uint2 sched[NE]; uint32_t wdep[20], wt[5]; uint2 w2t[12]; int hid[3][9]; };

#define REGION_IDS int tid, lane, bid; \
  asm volatile("mov.u32 %0, %%tid.x;" : "=r"(tid)); asm volatile("mov.u32 %0, %%laneid;" : "=r"(lane)); asm volatile("mov.u32 %0, %%ctaid.x;" : "=r"(bid)); \
  const int i0 = tid & 127; (void)i0; (void)lane; (void)bid

__device__ __forceinline__ void ffn_role(int& h, int& j, int& r) {
  uint32_t b;
  asm volatile("mov.u32 %0, %%ctaid.x;" : "=r"(b));
  const uint32_t c = b >> 1, q = (c - 36) * 37 >> 8, e = c - 36 - 7 * q;
  h = b & 1;
  const uint32_t k = c < 4 ? 0 : c < 36 ? (c - 4) & 7 : e + 1, p = c < 4 ? c : c < 36 ? (c - 4) >> 3 : q, up = c - 4 >= 32;
  j = 2 * (k & 1) + up;
  r = 2 * (k & 6) + p;
}
__device__ __forceinline__ int fslice(int j, int e) { return e == 2 ? j ^ 1 : (~j & 2) + e; }
__device__ __forceinline__ int mod_ch(int p) { return p < 40 ? (p >> 3) * 128 + (p & 1) * 64 : 64 * (p < 50 ? p - 40 : p - 50); }
__device__ __forceinline__ int mod_col(int p) { return mod_ch(p) + 640 * (p < 40 ? 0x4210 >> (2 * (p & 6)) & 7 : p < 50 ? 3 : 5); }
__device__ __forceinline__ uint32_t mod_sum(uint2 v) { return pack_bf16(0.f, __uint_as_float(v.x) + __uint_as_float(v.y)); }

constexpr int NT = 3, LAG2 = 29, MG = 4, NP = 1, P0 = 0, ST = 1, NB = 0, PA = 2, O3 = 0, O0 = 1, OS = 2;
__device__ __forceinline__ int w_block(int up, int m) { return m == 1 ? 2 + 3 * up : 3 * (m >> 1) + up; }
__host__ __device__ constexpr int w2_at(int v) { return 8192 * (v ? 0x0613030008ull >> v % 5 * 8 & 255 : 15); }
__host__ __device__ constexpr int w2_step(int v) { return 8192 * (v ? 0x32113 >> v % 5 * 4 & 15 : 1); }
__host__ __device__ constexpr int hid_at(int m, int g) { return 8192 * ((g ? 0x0D07110F1816ull : 0x0A19101A1412ull) >> m % 6 * 8 & 255); }
__host__ __device__ constexpr uint32_t w2_desc(int v) { return (DB + w2_at(v)) >> 4 | w2_step(v) << 12; }
__device__ __forceinline__ int next_slot(int s) { return s >= 4 * WSLOT ? 0 : s + WSLOT; }

template <int U> __device__ __forceinline__ void cstep(float* acc, const uint32_t* A, uint64_t db) {
  const uint32_t* a = A + 4 * U;
  const uint64_t d = db + 16 * U;
  if (U == 4) { wg_rs64_0(acc + 96, A, db + 192, 0); wg_rs48_0(acc + 96, A + 4, db + 208, 1); wg_rs32_0(acc + 96, A + 8, db + 224, 1); wg_rs16_0(acc + 96, A + 12, db + 240, 1); }
  if (U <= 4) wg_rs192_0(acc, a, d, U);
  if (U == 5) wg_rs176_0(acc, a, d, 1);
  if (U == 6) wg_rs160_0(acc, a, d, 1);
  if (U == 7) wg_rs144_0(acc, a, d, 1);
  if (U == 8) wg_rs128_0(acc, a, d, 1);
  if (U == 9) wg_rs112_0(acc, a, d, 1);
  if (U == 10) wg_rs96_0(acc, a, d, 1);
  if (U == 11) wg_rs80_0(acc, a, d, 1);
  if (U == 12) wg_rs64_0(acc, a, d, 1);
  if (U == 13) wg_rs48_0(acc, a, d, 1);
  if (U == 14) wg_rs32_0(acc, a, d, 1);
  if (U == 15) wg_rs16_0(acc, a, d, 1);
}
template <int U0, int U1> __device__ __forceinline__ void csteps(float* acc, const uint32_t* A, uint64_t db) {
  cstep<U0>(acc, A, db);
  if constexpr (U0 > U1) csteps<U0 - 1, U1>(acc, A, db);
}
template <int U0, int U1> __device__ __forceinline__ void cload(uint32_t* A, uint32_t fa) {
  asm volatile("{ld.shared.b32 %0, [%4+%5]; ld.shared.b32 %1, [%4+%5+128]; ld.shared.b32 %2, [%4+%5+16]; ld.shared.b32 %3, [%4+%5+144];}"
               : "=r"(A[4 * U0]), "=r"(A[4 * U0 + 1]), "=r"(A[4 * U0 + 2]), "=r"(A[4 * U0 + 3]) : "r"(fa), "n"(256 * U0) : "memory");
  if constexpr (U0 > U1) cload<U0 - 1, U1>(A, fa);
}

__device__ __forceinline__ uint2 c_load(const bf16* c) {
  REGION_IDS;
  return make_uint2(ldg32(c + 320 * (bid & 1) + 2 * i0), ldg32(c + 320 * (bid & 1) + 256 + 2 * lane));
}
__device__ __forceinline__ void silu_vector(uint2 c, uint32_t base) {
  REGION_IDS;
  sts32(base + OFF_CV + 4 * i0, pack_bf16(silu_f(bf_lo(c.x)), silu_f(bf_hi(c.x))));
  sts32(base + OFF_CV + 512 + 4 * lane, pack_bf16(silu_f(bf_lo(c.y)), silu_f(bf_hi(c.y))));
  fence_async_smem();
}

__device__ __forceinline__ void mod_poll(Scratch* G, uint32_t base, int c, int n, uint32_t epoch) {
  REGION_IDS;
  const int e = 4 * c + (lane & (4 * n - 1));
  uint2 m;
  int it = 0;
#pragma unroll 1
  do m = ld_relaxed64(&G->modc[bid][8 + e]); while (__any_sync(~0u, ((m.x ^ epoch) | (m.y ^ epoch)) & 1) && ++it < SPIN_LIMIT);
  sts32(base + OFF_MODR + 4 * e, __byte_perm(badd2(mod_sum(m), (lane & 1) * 0x3F800000u), 0, 0x3232));
  __syncwarp();
  if (elect()) { mbar_arrive(BAR(B_MODR + c)); if (n > 1) mbar_arrive(BAR(B_MODR + c + 1)); }
}
__device__ __forceinline__ void row_stats(Scratch* G, uint32_t base, uint32_t epoch) {
  REGION_IDS;
  mbar_wait_cluster(BAR(B_ST1));
  if (lane < 8) red_hint(G->hint[5][lane]);
  const uint2 x = lds64(base + OFF_ST + 8 * (lane & 15)), y = lds64(base + OFF_ST + 128 + 8 * (lane & 15));
  float m, sd;
  ln_final(__uint_as_float(x.x) + __uint_as_float(y.x), __uint_as_float(x.y) + __uint_as_float(y.y), m, sd);
  sd = rbf(rcpf(sd));
  const uint32_t mr = pack_bf16(sd, -rbf(m) * sd), tg = lane & 7 ? 0 : lane & 8 ? 1 : 0x8000;
  const uint32_t o = __byte_perm(__shfl_sync(~0u, mr, 2 * lane & 14), __shfl_sync(~0u, mr, (2 * lane & 14) + 1), (lane & 8) ? 0x7632 : 0x5410);
  if (lane < 16) st_relaxed32(&G->st1[lane >> 3][8 * bid + (lane & 7)], (o & ~tg) | ((epoch & 1) * tg));
  if (elect()) mbar_arrive(BAR(B_FIN));
}
template <int B, int NEXT> __device__ __forceinline__ void strip(Scratch* G, const CUtensorMap* map, uint32_t base, int c, uint32_t epoch, uint32_t& ph, uint32_t& pre, float4& s) {
  REGION_IDS;
  int h, j, r, it = 0;
  ffn_role(h, j, r);
  const uint32_t buf = base + OFF_SX + 4096 * B, a = buf + 32 * lane;
#pragma unroll 1
  while (__any_sync(~0u, pre != 64 * epoch) && ++it < SPIN_LIMIT) pre = ld_relaxed32(G->xsh[c][(r & 6) + (j >> 1)]);
#pragma unroll 1
  for (it = 0; it < SPIN_LIMIT; it++) {
    if (elect()) { mbar_expect_tx(BAR(B_SX + B), 4096); tma2d(buf, map, 128 * r + 64 * h, D_ * (epoch & 1) + 128 * c + 32 * j, BAR(B_SX + B)); }
    mbar_wait(BAR(B_SX + B), ph);
    ph ^= 1;
    if (__all_sync(~0u, min(min(lds32(a), lds32(a + 1024)), min(lds32(a + 2048), lds32(a + 3072))))) break;
  }
  pre = 0;
  if (c == NEXT - 1 || c == NEXT - 2) pre = ld_relaxed32(G->xsh[c + 1][(r & 6) + (j >> 1)]);
#pragma unroll 1
  for (uint32_t o = buf + 4 * lane; o < buf + 4096; o += 1024) {
    uint32_t x[8];
#pragma unroll
    for (int i = 0; i < 8; i++) x[i] = lds32(o + 128 * i);
#pragma unroll
    for (int i = 0; i < 8; i++) { const float lo = bf_lo(x[i]), hi = bf_hi(x[i]); s.x += lo; s.y = fmaf(lo, lo, s.y); s.z += hi; s.w = fmaf(hi, hi, s.w); }
  }
}
__device__ __forceinline__ void planes(uint32_t a, uint4& y) {
  uint4 z = lds128(a + 4096);
  y.x = badd2(y.x, z.x); y.y = badd2(y.y, z.y); y.z = badd2(y.z, z.z); y.w = badd2(y.w, z.w);
  z = lds128(a + 8192);
  const uint4 m = lds128(a + 12288);
  y.x = badd2(y.x, badd2(z.x, m.x)); y.y = badd2(y.y, badd2(z.y, m.y)); y.z = badd2(y.z, badd2(z.z, m.z)); y.w = badd2(y.w, badd2(z.w, m.w));
}
__device__ __forceinline__ void mr_poll(Scratch* G, uint32_t base, uint32_t epoch) {
  int it = 0;
#pragma unroll 1
  while (__any_sync(~0u, ld_relaxed32(G->hint[5][4 * (blockIdx.x >> 6) + (blockIdx.x >> 3 & 3)]) != epoch << 7) && ++it < SPIN_LIMIT);
  if (elect()) { mbar_expect_tx(BAR(B_MR), 8192); bulk_load(base + OFF_MR, G->st1, 8192, BAR(B_MR)); mbar_arrive(BAR(B_QTOK)); }
}

__global__ void __cluster_dims__(2, 1, 1) __launch_bounds__(512, 1) k_fused(const __grid_constant__ Ptrs P, const __grid_constant__ Maps maps) {
  Scratch* const G = P.g;
  extern __shared__ __align__(1024) uint8_t smem_raw[];
  const uint32_t t_start = clock();
  const uint32_t base = __shfl_sync(~0u, smem_u32(smem_raw), 0);
  uint32_t t_iss = 0;
  if (threadIdx.x < 32 && blockIdx.x < 128) {
    mbar_init<1>(BAR(0), 1);
    if (elect()) {
      const int c0 = 64 * (blockIdx.x & 1), c1 = 2 * (blockIdx.x & 126);
      mbar_expect_tx(BAR(B_KV), 12288);
      tma3d(base + tab(T_KV, 0), &maps.km, c0, c1, 0, BAR(B_KV));
      tma3d(base + tab(T_KV, 0) + KV_V, &maps.v, c0, c1, 0, BAR(B_KV));
      tma3d(base + tab(T_KV, 0) + KV_H, &maps.kh, c0, c1 - 1, 5, BAR(B_KV));
      tma3d(base + OFF_TAP, &maps.tap, 0, blockIdx.x & 1, 0, BAR(B_KV));
    }
    if (P.boff) mbar_wait(BAR(0));
  }
  if ((base & 0xFFFFFFu) != DB) __trap();
  const int wid = __shfl_sync(~0u, threadIdx.x >> 5, 0), wg = wid >> 2, w = wid & 3;
  if (blockIdx.x + P.boff >= 128) {
    REGION_IDS;
    constexpr int nu = 30;
    auto tile = [&](int n) { return 2 * n + (blockIdx.x >> 1 & 1); };
    auto fetch = [&](int n, int b) {
      if (elect()) {
        mbar_expect_tx(BAR(n), 40960);
#pragma unroll
        for (int k = 0; k < 5; k++) tma3d(base + 40960 * b + 8192 * k, &maps.wm, mod_col(tile(n)), 320 * (blockIdx.x & 1) + 64 * k, 0, BAR(n));
      }
    };
    if (P.boff) __syncthreads();
    if (wid == 12) {
      mbar_init<4>(BAR(0), 1);
#pragma unroll 1
      for (int n = 0; n < 4; n++) fetch(n, n);
      mbar_init<26>(BAR(4), 1);
      mbar_init<60>(BAR(32), 4);
    }
    const uint32_t par = ~ld_relaxed32(G->hint[7][0]) >> 7 & 1;
    silu_vector(c_load(P.c), base);
    __syncthreads();
    if (wid == 12) {
      wait_clock(t_start + P.th);
#pragma unroll 1
      for (int n = 4, b = 4; n < nu; n++) {
        if (n >= 5) mbar_wait(BAR(27 + n));
        if (n == 8) wait_clock(t_start + P.th2);
        fetch(n, b);
        b = b == 4 ? 0 : b + 1;
      }
    } else if (wg < 2) {
      uint32_t cv[40];
#pragma unroll
      for (int k = 0; k < 40; k++) cv[k] = lds32(base + OFF_CV + 16 * k + 4 * (lane & 3));
      const uint32_t a0 = base + 128 * ((lane & 7) + (lane >> 4) * 8) + (((2 * w + (lane >> 3 & 1)) ^ (lane & 7)) << 4);
#pragma unroll 1
      for (int n = wg; n < nu; n += 2) {
        float d[16] = {};
        mbar_wait(BAR(n));
#pragma unroll
        for (int k0 = 0; k0 < 20; k0 += 10) {
          uint32_t a[40];
#pragma unroll
          for (int k = 0; k < 10; k++) ldmatrix_x4_t(a + 4 * k, a0 + 40960 * (n % 5) + 2048 * (k0 + k));
#pragma unroll
          for (int k = 0; k < 10; k++)
            asm("mma.sync.aligned.m16n8k16.row.col.f32.bf16.bf16.f32 {%0,%1,%2,%3}, {%4,%5,%6,%7}, {%8,%9}, {%0,%1,%2,%3};"
                : "+f"(d[4 * (k & 3)]), "+f"(d[4 * (k & 3) + 1]), "+f"(d[4 * (k & 3) + 2]), "+f"(d[4 * (k & 3) + 3])
                : "r"(a[4 * k]), "r"(a[4 * k + 1]), "r"(a[4 * k + 2]), "r"(a[4 * k + 3]), "r"(cv[2 * (k0 + k)]), "r"(cv[2 * (k0 + k) + 1]));
        }
        arrive1(BAR(32 + n));
        if (!(lane & 3)) {
          sts32(base + 204800 + 256 * n + 64 * w + lane, __float_as_uint(d[0] + d[4] + (d[8] + d[12])));
          sts32(base + 204800 + 256 * n + 64 * w + lane + 32, __float_as_uint(d[2] + d[6] + (d[10] + d[14])));
        }
        arrive1(BAR(62 + n));
      }
    } else if (wg == 2) {
#pragma unroll 1
      for (int n = w; n < nu; n += 4) {
        const int t = tile(n), ch = mod_ch(t) + lane;
        uint32_t* q = (uint32_t*)(t < 40 ? &G->modc[ch & 127][8 + (t >> 1)] : &G->modv[t >= 50][ch]) + (bid & 1);
        mbar_wait(BAR(62 + n));
        const uint32_t x = (lds32(base + 204800 + 256 * n + 4 * lane) & ~1u) | par, y = (lds32(base + 204928 + 256 * n + 4 * lane) & ~1u) | par;
        publish(q, x);
        publish(q + (t < 40 ? 2048 : 64), y);
        if (t < 40 && (t & 6) == 6) {
          q = (uint32_t*)&G->modv[2][ch] + (bid & 1);
          publish(q, x);
          publish(q + 64, y);
        }
      }
    }
    return;
  }
  if (wid < 15) mbar_init<4>(BAR(4 * wid + (wid == 0)), wid < 8 ? 1 : 4);
  asm volatile("fence.mbarrier_init.release.cluster; bar.sync 0, 512;" ::: "memory");
  asm volatile("barrier.cluster.arrive.relaxed.aligned;" ::: "memory");
  if (wid == 4) {
    const int c0 = 64 * (blockIdx.x & 1), c1 = 2 * (blockIdx.x & 126);
    wait_clock(t_start + P.te);
    if (elect()) { tma3d(base + tab(T_KV, 1), &maps.km, 128 + c0, c1, 0, BAR(B_KV + 1)); tma3d(base + tab(T_KV, 1) + KV_H, &maps.kh, 128 + c0, c1 - 1, 5, BAR(B_KV + 1)); }
    wait_clock(t_start + P.te + P.pe);
    if (elect()) tma3d(base + tab(T_KV, 1) + KV_V, &maps.v, 128 + c0, c1, 0, BAR(B_KV + 1));
    wait_clock(t_start + P.te + 2 * P.pe);
    if (elect()) bulk_load(base + tab(T_F, 0) + F_E, P.ssmk + blockIdx.x * S_, 4096, BAR(B_FRAW));
    wait_clock(t_start + P.te + 3 * P.pe);
    if (elect()) tma3d(base + OFF_Q, &maps.q, c0, c1, 0, BAR(B_Q));
  }
#define LAUNCHES const uint32_t launches = ld_relaxed32(G->hint[7][blockIdx.x >> 4])
#define EPOCH ((__shfl_sync(~0u, launches, 0) >> 7) + 1)
  if (wg == 3) {
    asm volatile("setmaxnreg.dec.sync.aligned.u32 24;");
    if (w == 1) {
      {
        LAUNCHES;
        REGION_IDS;
        const int c1 = 2 * (bid & 126);
#pragma unroll 1
        for (int e = 4; e < NE; e++) {
          const uint2 x = P.sched[e];
          const uint32_t kind = x.x >> 16 & 15, ch = x.x >> 13 & 0x380, dst = base + (x.y & 0x3FFFF), b = BAR(x.y >> 18);
          wait_clock(t_start + (x.x & 0xFFFF));
          if (kind < 3 && elect()) tma3d(dst, &maps.km + kind, ch + 64 * (bid & 1), c1, 0, b);
          if (kind == 0 && elect()) tma3d(dst + KV_H, &maps.kh, ch + 64 * (bid & 1), c1 - 1, 5, b);
          if (kind == 3 && elect()) bulk_load(dst, P.ssmk + (ch + bid) * S_, 4096, b);
        }
        if (P.mr2 == 2) mr_poll(G, base, EPOCH);
        mod_poll(G, base, 0, 1, EPOCH);
      }
      cluster_wait();
      int h, j, r;
      ffn_role(h, j, r);
      mbar_wait(BAR(B_QTD));
      mbar_wait(BAR(B_FL));
#pragma unroll 1
      for (int u = 0; u < 20; u++) {
        const uint32_t x = P.wdep[u], s = base + (x & ~8191u);
        if (u < 5) wait_clock(t_start + P.wt[u]);
        mbar_wait(BAR(opaque(x & 255)));
        if (elect()) {
          mbar_expect_tx(BAR(B_FULL + u), WSLOT + 4 * (x & 4096));
#pragma unroll
          for (int k = 0; k < 6; k++) tma3d(s + 4096 * w_block(k & 1, k >> 1), &maps.w1s + (k & 1), 0, 32 * u, 3 * (4 * h + j) + (k >> 1), BAR(B_FULL + u));
        }
      }
#pragma unroll 1
      for (int v = 0; v < 12; v++) {
        const int q = v * 11 >> 5, e = v - 3 * q, k32 = 24 * h + (q ? 6 * fslice(j, e) + 2 * q - 2 : 6 * j + 2 * e);
        const uint2 x = P.w2t[v];
        mbar_wait(BAR(x.y));
        if (elect()) {
          mbar_expect_tx(BAR(B_FULL + 20 + v), q ? WSLOT + 2 * ASLOT : WSLOT);
#pragma unroll
          for (int k = 0; k < 3; k++) tma5d(base - DB + 16 * ((x.x & 0xFFFF) + k * (x.x >> 16)), &maps.w2a + (q > 0), k < 2 ? 128 * j + 64 * k : 512 + 32 * (j & 2), k32, BAR(B_FULL + 20 + v));
        }
      }
    } else if (w == 0) {
      LAUNCHES;
      uint32_t epoch;
      {
        REGION_IDS;
        const unsigned* hp = G->hint[0][4 * (bid >> 6) + (bid >> 3 & 3)];
        uint32_t v = ld_relaxed32(hp + 256 * min(lane, 5));
        if (lane < 3) sts128(base + tab(T_X, lane) + 4096, 0, 0, 0, 0);
        if (lane && lane < B_Q + 5) mbar_expect_tx(BAR(lane), lane < B_FRAW ? 9728 : 4096);
        epoch = EPOCH;
        fence_async_smem();
        const uint32_t rdy = __ballot_sync(~0u, v == epoch << 6);
        uint32_t nx = 0, nm = 0;
#pragma unroll 1
        for (uint32_t seq = P.seq; seq; seq >>= 2) {
          int it = 0;
          if (seq & 1) {
            if (!(seq & 2)) mod_poll(G, base, nm, 1 + (seq == 13), epoch);
            nm++;
          } else if (seq & 2) {
            mr_poll(G, base, epoch);
          } else {
            if (!(rdy >> nx & 1)) {
#pragma unroll 1
              while (__any_sync(~0u, ld_relaxed32(hp + 256 * nx) != epoch << 6) && ++it < SPIN_LIMIT);
            }
            wait_clock(clock() + (P.xd >> 4 * nx & 15) * 64);
            if (nx >= 3) mbar_wait(BAR(B_PFULL - 3 + nx));
            if (elect()) { mbar_expect_tx(BAR(B_XR + nx), 4096); bulk_load(base + tab(T_X, nx), G->xr + (128 * nx + bid) * 256, 4096, BAR(B_XR + nx)); }
            nx++;
          }
        }
      }
      REGION_IDS;
      int h, j, r;
      ffn_role(h, j, r);
      mbar_wait(BAR(B_PFULL + 3));
      {
        float4 s = {};
        uint32_t ph = 0, pre = 0;
#pragma unroll 1
        for (int c = 2; c < 4; c++) strip<1, 3>(G, &maps.x1s, base, c, epoch, ph, pre, s);
        __syncwarp();
        sts128(base + OFF_SX + 4096 + 16 * lane, __float_as_uint(s.x), __float_as_uint(s.y), __float_as_uint(s.z), __float_as_uint(s.w));
        arrive1(BAR(B_S3));
      }
      ffn_role(h, j, r);
      cluster_wait();
      mbar_wait(BAR(B_UVD));
      asm volatile("fence.acq_rel.gpu;" ::: "memory");
      if (lane < 8) red_hint(G->hint[7][lane]);
      unsigned x;
      int it = 0;
#pragma unroll 1
      do { asm volatile("ld.acquire.gpu.global.u32 %0, [%1];" : "=r"(x) : "l"(G->hint[7][bid >> 4]) : "memory"); } while (__any_sync(~0u, x != 128 * epoch) && ++it < SPIN_LIMIT);
      fence_async_all();
      const int ch = D_ * (epoch & 1);
      mbar_wait(BAR(B_EXT));
      mbar_wait(BAR(B_EMPTY + 18));
      if (elect()) {
        mbar_expect_tx(BAR(B_FULL + 32), 20480);
#pragma unroll
        for (int k = 0; k < 4; k++) tma2d(base + (k < 3 ? OFF_X1 + k * WSLOT : OFF_SX), &maps.x1b, 128 * r + 64 * h, ch + 128 * j + 32 * (k ^ (j & 1)), BAR(B_FULL + 32));
        tma2d(base + OFF_SX + 4096, &maps.x1b, 128 * r + 64 * h, ch + 512 + 32 * j, BAR(B_FULL + 32));
        mbar_expect_tx(BAR(B_FULL), 8192); mbar_expect_tx(BAR(B_FULL + 1), 8192); mbar_expect_tx(BAR(B_FULL + 2), 4096);
      }
      mbar_wait(BAR(B_EMPTY + 27));
      if (elect()) mbar_arrive_remote(mapa(BAR(B_XFREE), h ^ 1));
    } else {
      LAUNCHES;
      uint32_t epoch;
      {
        REGION_IDS;
        uint32_t dv;
        asm volatile("ld.global.nc.u16 %0, [%1];" : "=r"(dv) : "l"(P.ssmd + 128 * (lane & 7) % D_ + bid));
        if (lane < 5) sts128(base + tab(T_F, lane) + (w & 1) * (F_O - 16), 0, 0, 0, 0);
        epoch = EPOCH;
        __syncwarp();
#pragma unroll 1
        for (int c = 0; c < 5; c++) {
          const float d = i0 == 64 ? bf_lo(dv) : 0.f;
          dv = __shfl_down_sync(~0u, dv, 1);
          const uint32_t a = base + tab(T_F, c) + 16 * (i0 - 64);
          mbar_wait(BAR(B_FRAW + c));
#pragma unroll
          for (int k = 0; k < 4; k++) {
            uint4 x = lds128(a + F_E + 1024 * k);
            const uint32_t pv = lds32(a + F_E - 4 + 1024 * k);
            if (k == 0) { x.x = pack_bf16(bf_lo(x.x) + d, bf_hi(x.x)); sts32(a + F_E, x.x); }
            sts128(a + F_O + 1024 * k, __byte_perm(pv, x.x, 0x5432), __byte_perm(x.x, x.y, 0x5432), __byte_perm(x.y, x.z, 0x5432), __byte_perm(x.z, x.w, 0x5432));
          }
          __syncwarp();
          if (elect()) mbar_arrive2(BAR(B_FRDY + c));
          if (c == 0 && w == P.fin) row_stats(G, base, epoch);
        }
      }
      REGION_IDS;
      int h, j, r;
      ffn_role(h, j, r);
      cluster_wait();
      if (w == 2) {
        uint32_t rdy = 0, s = 0;
        mbar_wait(BAR(B_QTD));
        mbar_wait(BAR(B_FL + 2));
#pragma unroll 1
        for (int n = 0; n < 10; n++) {
          if (n == P.cn) {
            mbar_wait(BAR(B_PEMPTY + 3));
            if (elect()) {
              tma3d(base + OFF_UV, &maps.w1 + (r & 1), 0, 40 * (r & 14), 3 * (4 * h + j), BAR(B_UVB));
              tma3d(base + OFF_UV + 12288, &maps.w1 + (r & 1), 0, 40 * (r & 14) + 32, 3 * (4 * h + j), BAR(B_UVB));
            }
            {
              const uint2* mp = &G->modv[lane & 4 ? 0 : 2][40 * (r & 14) + (lane & 24) + 2 * (lane & 3)];
              uint4 v[3];
              int it = 0;
#pragma unroll 1
              do {
                v[0] = ld_relaxed128(mp); v[1] = ld_relaxed128(mp + 32); v[2] = ld_relaxed128(mp + 64 - (lane & 16));
              } while (__any_sync(~0u, ((v[0].x ^ epoch) | (v[0].y ^ epoch) | (v[0].z ^ epoch) | (v[0].w ^ epoch) | (v[1].x ^ epoch) | (v[1].y ^ epoch) | (v[1].z ^ epoch) | (v[1].w ^ epoch) |
                                        (v[2].x ^ epoch) | (v[2].y ^ epoch) | (v[2].z ^ epoch) | (v[2].w ^ epoch)) & 1) && ++it < SPIN_LIMIT);
#pragma unroll
              for (int i = 0; i < 3; i++)
                sts32(base + OFF_CO + 128 * i + 4 * lane, badd2(pack_bf16(__uint_as_float(v[i].x) + __uint_as_float(v[i].y), __uint_as_float(v[i].z) + __uint_as_float(v[i].w)), lane & 4 ? 0 : 0x3F803F80u));
            }
            fence_async_smem();
            __syncwarp();
            if (elect()) mbar_expect_tx(BAR(B_UVB), WSLOT);
          }
          mbar_wait(BAR(n < 2 ? B_FL + 3 + n : n == 2 ? B_PFULL + 4 : B_EMPTY + 2 * n - 5));
#pragma unroll 1
          for (int it = 0; !(rdy >> n & 1) && it < SPIN_LIMIT; it++) rdy = __ballot_sync(~0u, ld_relaxed32(G->xsh[min(lane >> 1, n ? 4 : P.aw)][(r & 6) + (lane & 1)]) == 64 * epoch) & (n ? ~0u : (4u << 2 * P.aw) - 1);
          if (elect()) {
            tma2d(base + OFF_A + s, &maps.xs, 128 * r + 64 * h, 64 * n, BAR(B_FULL + 2 * n));
            tma2d(base + OFF_A + ARING + s, &maps.xs, 128 * r + 64 - 64 * h, 64 * n, BAR(B_FULL + 2 * n));
          }
          s = s == 2 * ASLOT ? 0 : s + ASLOT;
        }
      } else {
        if (P.m3 < 5) mod_poll(G, base, P.m3, 1, epoch);
        float4 s = {};
        uint32_t ph = 0, pre = 0;
        mbar_wait(BAR(B_FL + 2));
        mbar_wait(BAR(B_PFULL + 3));
#pragma unroll 1
        for (int c = 0; c < 5; c = c == 1 ? 4 : c + 1) {
          if (c == 4) {
            ffn_role(h, j, r);
            mbar_wait(BAR(B_PEMPTY + 4));
            if (elect()) {
              mbar_expect_tx(BAR(B_UVE), 6144);
              tma3d(base + OFF_UVE, &maps.w1e + (r & 1), 0, 40 * (r & 14) + 64, 3 * (4 * h + j), BAR(B_UVE));
            }
          }
          strip<0, 1>(G, &maps.x1s, base, c, epoch, ph, pre, s);
        }
        mbar_wait(BAR(B_S3));
        const uint4 y = lds128(base + OFF_SX + 4096 + 16 * lane);
        const float s0 = s.x + __uint_as_float(y.x), q0 = s.y + __uint_as_float(y.y), s1 = s.z + __uint_as_float(y.z), q1 = s.w + __uint_as_float(y.w);
        ffn_role(h, j, r);
        asm volatile("{.reg .b128 t, x; .reg .b64 a, b; mov.b64 a, {%1,%2}; mov.b64 b, {%3,%4}; mov.b128 x, {a,b}; atom.relaxed.gpu.global.exch.b128 t, [%0], x;}"
                     ::"l"(&G->st2[2 * r + h][j][4 * lane]), "r"((__float_as_uint(s0) & ~1u) | (epoch & 1)), "f"(q0), "r"((__float_as_uint(s1) & ~1u) | (epoch & 1)), "f"(q1) : "memory");
        uint4* z = G->x1[~epoch & 1] + 1280 * bid + lane;
#pragma unroll 1
        for (int k = 0; k < 40; k++) st_relaxed128(z + 32 * k, 0, 0, 0, 0);
      }
    }
  } else if (wg == 2) {
    asm volatile("setmaxnreg.dec.sync.aligned.u32 40;");
    mbar_init<12>(BAR(B_FULL + 12 * w), 1);
    mbar_init<9>(BAR(B_EMPTY - 1 + 9 * w), 8);
    asm volatile("fence.mbarrier_init.release.cluster;" ::: "memory");
    LAUNCHES;
    const uint32_t epoch = EPOCH;
    cluster_wait();
#pragma unroll 1
    for (uint64_t prog = P.prog; prog; prog >>= 4) {
      REGION_IDS;
      const int s = (prog & 7) - 1;
      if (!(prog & 8)) {
        const uint32_t a = base + tab(T_KV, s) + 128 * (lane & 3) + ((w ^ (lane & 3)) << 4) + 4 * (lane & 16) + (lane & 12), keep = ~(lane & 1), bit = epoch & lane & 1;
        uint4* dst = G->xr + (128 * s + 64 * (bid & 1) + 8 * w + 2 * (lane & 16) + (lane >> 1 & 6)) * 256 + 255 - 4 * (bid >> 1) - (lane & 3);
        mbar_wait(BAR(B_KV));
        mbar_wait(BAR(B_KV + s));
        const uint4 wv = lds128(base + OFF_TAP + 512 * s + 64 * w + 16 * (lane & 16) + 4 * (lane & 12));
        uint32_t kk[11], r[8];
#pragma unroll
        for (int k = 0; k < 11; k++) kk[k] = k < 3 ? lds32((a ^ (64 * (k & 1))) + KV_H + 512 * k) : lds32((a ^ (64 * (~k & 1))) + 512 * (k - 3));
        if (elect()) red_hint(G->hint[s][4 * (bid & 1) + w]);
#pragma unroll
        for (int k = 0; k < 8; k++) r[k] = lds32((a ^ (64 * (k & 1))) + KV_V + 512 * k);
        const uint32_t w0 = __byte_perm(wv.x, wv.z, 0x5410), w1 = __byte_perm(wv.x, wv.z, 0x7632),
                       w2 = __byte_perm(wv.y, wv.w, 0x5410), w3 = __byte_perm(wv.y, wv.w, 0x7632);
#pragma unroll
        for (int k = 0; k < 8; k++) r[k] = bmul2(bfma2(kk[k + 3], w0, bfma2(kk[k + 2], w1, bfma2(kk[k + 1], w2, bmul2(kk[k], w3)))), r[k]);
        st_relaxed128(dst, (__byte_perm(r[7], r[6], 0x5410) & keep) | bit, __byte_perm(r[5], r[4], 0x5410), __byte_perm(r[3], r[2], 0x5410), __byte_perm(r[1], r[0], 0x5410));
        st_relaxed128(dst + 256, (__byte_perm(r[7], r[6], 0x7632) & keep) | bit, __byte_perm(r[5], r[4], 0x7632), __byte_perm(r[3], r[2], 0x7632), __byte_perm(r[1], r[0], 0x7632));
      } else if (s == 5) {
        mbar_wait(BAR(B_PFULL));
#pragma unroll
        for (int hf = 0; hf < 2; hf++) {
          const uint32_t a = base + tab(T_P, 0) + 16 * i0 + 2048 * hf;
          uint4 y = lds128(a);
          planes(a, y);
          sts128(a, y.x, y.y, y.z, y.w);
        }
      } else if (s >= 0) {
        const int tr = 4 * (lane & 1) + (lane >> 1 & 3);
        const uint32_t a = base + OFF_Q + 4096 * s + 128 * ((lane & 24) + tr) + ((w ^ tr) << 4);
        uint4* dst = G->qt + (128 * s + 64 * (bid & 1) + 8 * w + (lane >> 2)) * 256 + 4 * (bid >> 1) + (lane & 3);
        mbar_wait(BAR(B_Q + s));
#pragma unroll
        for (int k = 0; k < 2; k++) {
          uint32_t x[4];
          ldmatrix_x4_t(x, a ^ (64 * k));
          st_relaxed128(dst + 8192 * k, set_tag(x[0], ~lane & 1, epoch), x[1], x[2], x[3]);
        }
      } else if (w == 3) {
        row_stats(G, base, epoch);
      }
    }
    arrive1(BAR(B_QTD));
    {
      REGION_IDS;
      const uint32_t tag = opaque(~lane & 1);
      const uint32_t io = 16 * i0;
      uint4* gp = (uint4*)((char*)(G->xs + 256 * blockIdx.x) + io);
      constexpr int QO = -D_ * 256;
      const uint32_t sa = base + io;
      uint4 q[2];
      if (w == 0 && P.mr2 == 1) mr_poll(G, base, epoch);
      mbar_wait(BAR(B_QTOK));
      q[0] = ld_relaxed128(gp + QO);
      q[1] = ld_relaxed128(gp + QO + 128);
#pragma unroll 1
      for (int it = 0; it < SPIN_LIMIT; it++) {
        mbar_wait(BAR(B_MR), it & 1);
        const uint32_t x = lds32(sa + 16 * i0 + OFF_MR), y = lds32(sa + 16 * i0 + OFF_MR + 4096);
        sts32(sa + 16 * i0 + OFF_MR, x & 0xFFFF7FFFu);
        if (bar_all(3, !(((x >> 15 ^ epoch) | (y ^ epoch)) & 1))) break;
        if (w == 0 && elect()) { fence_async_smem(); mbar_expect_tx(BAR(B_MR), 8192); bulk_load(base + OFF_MR, G->st1, 8192, BAR(B_MR)); }
      }
#pragma unroll 1
      for (int c = 0; c < 5; c++) {
        mbar_wait(BAR(B_MODR + c));
        uint4 co = lds128(base + OFF_MODR + 16 * c);
        co.x = bmul2(co.x, co.z); co.y = bmul2(co.y, co.z);
        mbar_wait(BAR(B_PFULL + c));
        const uint32_t pb = io + (base + tab(T_P, c));
        gp = (uint4*)((char*)(G->xs + 256 * blockIdx.x + 32768 * c) + io);
#pragma unroll
        for (int hf = 0; hf < 2; hf++) {
#pragma unroll 1
          for (int it = 0; __any_sync(~0u, set_tag(q[hf].x, tag, epoch) != q[hf].x) && it < SPIN_LIMIT; it++) {
            q[hf] = ld_relaxed128(gp + QO + 128 * hf);
          }
          uint4 y = lds128(pb + 2048 * hf);
          if (c) planes(pb + 2048 * hf, y);
          const uint4 z = lds128(sa + OFF_MR + 2048 * hf), m = lds128(sa + OFF_MR + 2048 * hf + 4096);
          y.x = bfma2(bfma2(bfma2(q[hf].x, z.x, m.x), co.y, co.x), y.x, q[hf].x);
          if (hf) {
            __syncwarp();
            asm volatile("{.reg .pred p; elect.sync _|p, 0xffffffff; @p red.relaxed.gpu.global.add.u32 [%0], 1; @p mbarrier.arrive.shared::cta.b64 _, [%1];}"
                         ::"l"(G->xsh[c][2 * w + (blockIdx.x >> 6)]), "r"(BAR(B_PEMPTY + c)), "r"(y.x) : "memory");
          }
          y.y = bfma2(bfma2(bfma2(q[hf].y, z.y, m.y), co.y, co.x), y.y, q[hf].y);
          y.z = bfma2(bfma2(bfma2(q[hf].z, z.z, m.z), co.y, co.x), y.z, q[hf].z);
          y.w = bfma2(bfma2(bfma2(q[hf].w, z.w, m.w), co.y, co.x), y.w, q[hf].w);
          st_relaxed128(gp + 128 * hf, set_tag(bmul2(y.x, co.w), tag, epoch), bmul2(y.y, co.w), bmul2(y.z, co.w), bmul2(y.w, co.w));
          asm volatile("{.reg .pred p; .reg .b32 t; setp.ne.u32 p, %5, 0; max.u32 t, %1, 1; @!p st.relaxed.gpu.global.v4.u32 [%0+%6], {t,%2,%3,%4}; @p st.relaxed.gpu.global.v4.u32 [%0+%7], {t,%2,%3,%4};}"
                       ::"l"(gp + 128 * hf), "r"(y.x), "r"(y.y), "r"(y.z), "r"(y.w), "r"(epoch & 1), "n"(D_ * 4096), "n"(D_ * 8192) : "memory");
          if (c < 4) q[hf] = ld_relaxed128(gp + QO + 32768 + 128 * hf);
        }
      }
    }
    int h, j, r;
    ffn_role(h, j, r);
    {
      REGION_IDS;
      mbar_wait(BAR(B_UVB));
      float d[12] = {};
      fence_regs(d);
      wg_fence();
#pragma unroll
      for (int k = 0; k < 15; k++) {
        if (k == 12) { wg_commit(); mbar_wait(BAR(B_UVE)); wg_fence(); }
        wg_ss8_10(d + 4 * (k % 3), mkdesc(DB + (k < 12 ? OFF_UV + 12288 * (k / 6) + 4096 * (k % 3) + 2048 * (k / 3 & 1) : OFF_UVE + 2048 * (k % 3)), 16, 1024, 1),
                  mkdesc(DB + OFF_CO + 64 * (k / 3), 32, 128, 0), 1);
      }
      wg_commit();
      const int row = (r & 14) + (lane >> 2 & 1);
      uint32_t* dst = &G->uv[4 * h + j][32 * row + 4 * ((2 * w ^ row) & 6) + (lane & 3)];
      const uint32_t tag = !(lane & 3);
      wg_wait<0>();
      fence_regs(d);
      if (elect()) { red_hint(G->hint[8][4 * h + j]); mbar_arrive(BAR(B_UVD)); }
      uint32_t x[6];
#pragma unroll
      for (int k = 0; k < 6; k++) asm volatile("movmatrix.sync.aligned.m8n8.trans.b16 %0, %1;" : "=r"(x[k]) : "r"(pack_bf16(d[2 * k], d[2 * k + 1])));
      if (lane < 8) {
#pragma unroll
        for (int k = 0; k < 6; k++) st_relaxed32(dst + 512 * w_block(r & 1, k >> 1) + ((4 * k ^ lane) & 4), set_tag(x[k], tag, epoch));
      }
    }
    {
      REGION_IDS;
      if (w == 0) {
        int it = 0;
#pragma unroll 1
        while (__any_sync(~0u, ld_relaxed32(G->hint[8][4 * h + j]) != 64 * epoch) && ++it < SPIN_LIMIT);
        if (elect()) { mbar_expect_tx(BAR(B_BX), 12288); bulk_load(base + OFF_BX, G->uv[4 * h + j], 12288, BAR(B_BX)); }
      }
      const uint32_t* sp = &G->st2[2 * r + (h ^ (w >> 1))][0][2 * (i0 & 63)];
      uint2 x[4];
      int it = 0;
#pragma unroll 1
      do {
#pragma unroll
        for (int k = 0; k < 4; k++) x[k] = ld_relaxed64(sp + 128 * k);
      } while (__any_sync(~0u, ((x[0].x ^ epoch) | (x[1].x ^ epoch) | (x[2].x ^ epoch) | (x[3].x ^ epoch)) & 1) && ++it < SPIN_LIMIT);
      float m, sd;
      ln_final((__uint_as_float(x[0].x) + __uint_as_float(x[1].x)) + (__uint_as_float(x[2].x) + __uint_as_float(x[3].x)),
               (__uint_as_float(x[0].y) + __uint_as_float(x[1].y)) + (__uint_as_float(x[2].y) + __uint_as_float(x[3].y)), m, sd);
      const uint32_t e = pack_bf16(-m, sd);
      sts128(base + OFF_AX + 16 * i0, e, e, e, e);
      sts32(base + OFF_RT + 4 * i0, __float_as_uint(rcpf(sd)));
      fence_async_smem();
#pragma unroll 1
      for (it = 0; it < SPIN_LIMIT; it++) {
        mbar_wait(BAR(B_BX), it & 1);
        uint32_t y = 0;
#pragma unroll
        for (int k = 0; k < 6; k++) y |= lds32(base + OFF_BX + 16 * i0 + 2048 * k) ^ epoch;
        if (bar_all(3, !(y & 1))) break;
        if (w == 0 && elect()) { mbar_expect_tx(BAR(B_BX), 12288); bulk_load(base + OFF_BX, G->uv[4 * h + j], 12288, BAR(B_BX)); }
      }
      arrive1(BAR(B_EXT));
      {
        uint2 g0, g1;
        int it = 0;
#pragma unroll 1
        do {
          g0 = ld_relaxed64(&G->modv[1][128 * j + i0]);
          g1 = ld_relaxed64(&G->modv[1][512 + 32 * j + lane]);
        } while (__any_sync(~0u, ((g0.x ^ epoch) | (g0.y ^ epoch) | (g1.x ^ epoch) | (g1.y ^ epoch)) & 1) && ++it < SPIN_LIMIT);
        const uint32_t ga = base + OFF_GB + 80 * (lane >> 1 & 3) + 2 * (lane & 1) + (lane >> 3) * 4;
        asm volatile("st.shared.u16 [%0], %1;" ::"r"(ga + 16 * (w ^ (j & 1))), "h"((uint16_t)(mod_sum(g0) >> 16)) : "memory");
        asm volatile("st.shared.u16 [%0], %1;" ::"r"(ga + 64), "h"((uint16_t)(mod_sum(g1) >> 16)) : "memory");
        arrive1(BAR(B_GB));
      }
      const int id = 16 * r + 4 * h + fslice(j, w);
      const unsigned* fp = &G->hhf[8 * id + 64 * (lane & 1)];
#pragma unroll 1
      for (int q = w == 3 ? 3 : 0; q < 3; q++) {
        const int m = 3 * q + w;
        const uint4* src = G->hh + id * 1536 + 512 * q;
        it = 0;
#pragma unroll 1
        while (__any_sync(~0u, ld_relaxed32(fp + q) != 4 * epoch) && ++it < SPIN_LIMIT);
        mbar_wait(BAR(P.hid[2][m]));
        if (elect()) {
          bulk_load(base + OFF_A + h * ARING + P.hid[h][m], src, ASLOT, BAR(B_FULL + 23 + m));
          bulk_load(base + OFF_A + ARING - h * ARING + P.hid[h ^ 1][m], src + 8 * 1536, ASLOT, BAR(B_FULL + 23 + m));
        }
      }
    }
  } else {
    asm volatile("setmaxnreg.inc.sync.aligned.u32 224;");
    LAUNCHES;
    uint32_t par = EPOCH & 1;
    cluster_wait();
    uint32_t ck = 0;
    {
      float acc[128];
      uint32_t A[64];
#pragma unroll
      for (int i = 0; i < 64; i++) A[i] = 0;
      int c = wg;
#pragma unroll 1
      for (uint64_t prog = P.cprog[wg]; prog; prog >>= 8) {
        REGION_IDS;
        const int s = prog & 7;
        if (s < 5) {
          const uint32_t a = base + tab(T_KV, s) + 128 * (lane & 3) + ((w ^ (lane & 3)) << 4) + 4 * (lane & 16) + (lane & 12), keep = ~(lane & 1), bit = par & lane;
          uint4* dst = G->xr + (128 * s + 64 * (bid & 1) + 8 * w + 2 * (lane & 16) + (lane >> 1 & 6)) * 256 + 255 - 4 * (bid >> 1) - (lane & 3);
          mbar_wait(BAR(B_KV));
          mbar_wait(BAR(B_KV + s));
          const uint4 wv = lds128(base + OFF_TAP + 512 * s + 64 * w + 16 * (lane & 16) + 4 * (lane & 12));
          uint32_t kk[11], r[8];
#pragma unroll
          for (int k = 0; k < 11; k++) kk[k] = k < 3 ? lds32((a ^ (64 * (k & 1))) + KV_H + 512 * k) : lds32((a ^ (64 * (~k & 1))) + 512 * (k - 3));
          if (elect()) red_hint(G->hint[s][4 * (bid & 1) + w]);
#pragma unroll
          for (int k = 0; k < 8; k++) r[k] = lds32((a ^ (64 * (k & 1))) + KV_V + 512 * k);
          const uint32_t w0 = __byte_perm(wv.x, wv.z, 0x5410), w1 = __byte_perm(wv.x, wv.z, 0x7632),
                         w2 = __byte_perm(wv.y, wv.w, 0x5410), w3 = __byte_perm(wv.y, wv.w, 0x7632);
#pragma unroll
          for (int k = 0; k < 8; k++) r[k] = bmul2(bfma2(kk[k + 3], w0, bfma2(kk[k + 2], w1, bfma2(kk[k + 1], w2, bmul2(kk[k], w3)))), r[k]);
          st_relaxed128(dst, (__byte_perm(r[7], r[6], 0x5410) & keep) | bit, __byte_perm(r[5], r[4], 0x5410), __byte_perm(r[3], r[2], 0x5410), __byte_perm(r[1], r[0], 0x5410));
          st_relaxed128(dst + 256, (__byte_perm(r[7], r[6], 0x7632) & keep) | bit, __byte_perm(r[5], r[4], 0x7632), __byte_perm(r[3], r[2], 0x7632), __byte_perm(r[1], r[0], 0x7632));
        }
        if (prog & 8) {
          float s0 = 0.f, s1 = 0.f, q0 = 0.f, q1 = 0.f;
          const uint32_t a = OFF_Q + 1024 * w + 128 * (lane & 7) + (((lane >> 3) ^ (lane & 7)) << 4);
          const uint32_t ra = mapa(base + OFF_ST + 128 * (bid & 1) + 64 * (lane & 1) + 16 * w + 8 * (lane >> 2), lane >> 1 & 1), rb = mapa(BAR(B_ST1), lane >> 1 & 1);
          if (w == 3 && elect()) mbar_expect_tx(BAR(B_ST1), 256);
#pragma unroll 1
          for (int k = 0; k < 5; k++) {
            mbar_wait(BAR(B_Q + k));
            const uint32_t o = opaque(base + 4096 * k);
            const uint4 x = lds128(o + a), y = lds128(o + (a ^ 64));
            const uint32_t e[8] = {x.x, x.y, x.z, x.w, y.x, y.y, y.z, y.w};
#pragma unroll
            for (int i = 0; i < 8; i++) { const float lo = bf_lo(e[i]), hi = bf_hi(e[i]); s0 += lo; s1 += hi; q0 = fmaf(lo, lo, q0); q1 = fmaf(hi, hi, q1); }
          }
          s0 += s1; q0 += q1;
          s0 += __shfl_xor_sync(~0u, s0, 8); q0 += __shfl_xor_sync(~0u, q0, 8);
          s0 += __shfl_xor_sync(~0u, s0, 16); q0 += __shfl_xor_sync(~0u, q0, 16);
          if (lane < 8) asm volatile("st.async.shared::cluster.mbarrier::complete_tx::bytes.v2.b32 [%0], {%1,%2}, [%3];" ::"r"(ra), "r"(__float_as_uint(s0)), "r"(__float_as_uint(q0)), "r"(rb) : "memory");
        }
        if (prog & 32) {
          const int L = 16 * w + (lane >> 2) + 2 * (lane & 3) - 7;
          const uint32_t fo = base + ((L & 1) ? F_O + 2 * (L + 1) : F_E + 2 * L);
          mbar_wait(BAR(B_FRDY + c));
          cload<0, 0>(A, fo + tab(T_F, c));
          cload<15, 1>(A, fo + tab(T_F, c));
          arrive1(BAR(B_FL + c));
        }
        if (!(prog & 64)) continue;
        uint32_t xo;
        if (P.turn >> c & 1) mbar_wait(BAR(B_TURN - 3 + c));
        if (c == 0) mbar_wait(BAR(P.c0));
#pragma unroll 1
        for (int it = 0; it < SPIN_LIMIT; it++) {
          xo = tab(T_X, opaque(c));
          mbar_wait(BAR(B_XR + c), it & 1);
          const uint32_t tag = lds32(base + xo + 32 * i0);
          wg_fence();
          csteps<0, 0>(acc, A, mkdesc(DB + xo, 16, 128, 0));
          csteps<15, 6>(acc, A, mkdesc(DB + xo, 16, 128, 0));
          wg_commit();
          if (bar_all(1 + wg, !((tag ^ par) & 1))) break;
          wg_wait<0>();
          if (w == 0 && elect()) { mbar_expect_tx(BAR(B_XR + c), 4096); bulk_load(base + xo, G->xr + (128 * c + bid) * 256, 4096, BAR(B_XR + c)); }
        }
        wg_fence();
        csteps<5, 1>(acc, A, mkdesc(DB + tab(T_X, opaque(c)), 16, 128, 0));
        wg_commit();
        if (c >= 2 && c < 4 && elect()) mbar_arrive(BAR(B_TURN - 2 + c));
        if (c >= 3) mbar_wait(BAR(B_PEMPTY + c - 3));
        wg_wait<0>();
        fence_regs(acc);
        ck = base + OFF_A + wg * ARING + lane * 128 + (((2 * w) ^ (lane & 7)) << 4);
        const uint32_t pb = base + tab(T_P, c) + 4096 * w;
#pragma unroll
        for (int k = 0; k < 8; k++) {
          uint32_t p[4];
#pragma unroll
          for (int e = 0; e < 4; e++) { const int i = 4 * k + e; p[e] = i < 31 ? pack_bf16(acc[4 * i] + acc[4 * i + 6], acc[4 * i + 1] + acc[4 * i + 7]) : pack_bf16(acc[124], acc[125]); }
          if (k == 0 && (lane & 3) < w) p[0] = 0;
          stmatrix_x4_t(k == 0 ? pb + 16 * ((255 - lane + 2 * w) & 255) : pb + 16 * (255 - lane + 2 * w) - 512 * k, p[0], p[1], p[2], p[3]);
        }
        arrive1(BAR(B_PFULL + c));
        c += 2;
      }
    }
    const uint32_t abd = DB + OFF_A + wg * ARING;
    auto a_tile = [&](int as, int n, bool first) {
#pragma unroll 1
      for (int it = 0; __any_sync(~0u, ((lds32(ck + as) ^ par) | (lds32(ck + as + (first ? 4096 : 256)) ^ par)) & 1) && it < SPIN_LIMIT; it++) {
        int h, j, r;
        ffn_role(h, j, r);
        if (elect()) {
          const uint32_t dst = base + OFF_A + wg * ARING + as;
          mbar_expect_tx(BAR(B_RETRY + wid), ASLOT);
          if (first) tma2d(dst, &maps.xs, 128 * r + 64 * (h ^ wg), 64 * n, BAR(B_RETRY + wid));
          else bulk_load(dst, G->hh + ((2 * r + (h ^ wg)) * 8 + 4 * h + fslice(j, n % 3)) * 1536 + (n / 3) * 512, ASLOT, BAR(B_RETRY + wid));
        }
        mbar_wait(BAR(B_RETRY + wid), par >> 1);
        par ^= 2;
      }
    };
    float acc[192];
    int ws = 0, as = 0;
#pragma unroll 1
    for (int u = 0; u < 20 - NT; u++) {
      mbar_wait(BAR(B_FULL + u));
      if (!(u & 1)) a_tile(as, u >> 1, true);
      wg_fence();
#pragma unroll
      for (int k = 0; k < 4; k++) wg_ss192_11(acc + 96 * (k & 1), mkdesc(abd + as + k / 2 * 2048, 16, 1024, 1), mkdesc(DB + ws + 12288 * (k & 1) + k / 2 * 2048, 4096, 1024, 1), u + k / 2);
      wg_commit();
      wg_wait<1>();
      if (elect()) mbar_arrive(BAR(B_EMPTY + u - 1));
      ws = next_slot(ws);
      as = as == 5 * ASLOT / 2 ? 0 : as + ASLOT / 2;
    }
    auto tail = [&](int v, int i) {
      const int u = 20 - NT + i / 2;
      if (i < 2 * NT) wg_ss192_11(acc + 96 * v, mkdesc(opaque(abd) + u % 6 * 4096 + (i & 1) * 2048, 16, 1024, 1), mkdesc(DB + u % 5 * WSLOT + (i & 1) * 2048 + 12288 * v, 4096, 1024, 1), 1);
      if (i == 2 * NT) wg_ss192_01(acc + 96 * v, mkdesc(DB + OFF_AX + 1024 * opaque(wg), 0, 128, 0), mkdesc(DB + OFF_BX + 6144 * v, 2048, 1024, 1), 1);
    };
#pragma unroll
    for (int u = 20 - NT; u <= 20; u++) {
      mbar_wait(BAR(u < 20 ? B_FULL + u : B_EXT));
      if (u == 16 || u == 18) a_tile(u % 6 * 4096, u >> 1, true);
      wg_fence();
      tail(0, 2 * (u + NT - 20));
      tail(0, 2 * (u + NT - 20) + 1);
      wg_commit();
      if (u == 20 - NT) { wg_wait<1>(); if (elect()) mbar_arrive(BAR(B_EMPTY + u - 1)); }
    }
    float o[80];
    uint32_t fr[3][16], bo;
    {
      int h, j, r;
      ffn_role(h, j, r);
      REGION_IDS;
      const float r0 = 0.5f * __uint_as_float(lds32(base + OFF_RT + 256 * wg + 64 * w + (lane & 28))), r1 = 0.5f * __uint_as_float(lds32(base + OFF_RT + 256 * wg + 64 * w + 32 + (lane & 28)));
      const int id = (2 * r + (h ^ wg)) * 8 + 4 * h + j;
      uint4* const hdst = G->hh + id * 1536 + 128 * w + (lane ^ lane >> 3);
      const uint32_t keep = ~(~lane & 1), bit = par & ~keep;
      bo = 1024 + ((j & 1) << 23);
      auto own = [&](int i) { wg_rs160_1(o, fr[i >> 2] + 4 * (i & 3), mkdesc(DB + (5 + i / 4) % 6 * WSLOT + (i & 3) * 2048, 8192, bo, 1), i); };
      auto gate = [&](float* g, int d) {
#pragma unroll
        for (int e = 0; e < 4; e++) { g[e] *= e < 2 ? r0 : r1; g[e + d] *= g[e]; asm("tanh.approx.f32 %0, %0;" : "+f"(g[e])); }
      };
      auto mix = [&](uint32_t* x, const float* g, int d) {
        x[0] = pack_bf16(fmaf(g[d], g[0], g[d]), fmaf(g[d + 1], g[1], g[d + 1]));
        x[1] = pack_bf16(fmaf(g[d + 2], g[2], g[d + 2]), fmaf(g[d + 3], g[3], g[d + 3]));
      };
      auto hint = [&](int v) { asm volatile("{.reg .pred p; setp.eq.u32 p, %1, 0; @p red.relaxed.gpu.global.add.u32 [%0], 1;}" ::"l"(&G->hhf[id * 8 + v]), "r"(lane) : "memory"); };
      auto put = [&](int v, int k) {
        uint32_t* x = fr[v] + 2 * k;
        const uint32_t t0 = (x[k / 2] & keep) | bit, t1 = (x[5 + k / 2] & keep) | bit;
        if (!v) { x[k / 2] = t0; x[5 + k / 2] = t1; }
        st_relaxed128(hdst + 512 * v + 8 * k, k ? x[0] : t0, k ? t0 : x[2], x[4], x[6]);
        st_relaxed128(hdst + 512 * v + 8 * k + 64, x[1], x[3], k ? x[5] : t1, k ? t1 : x[7]);
      };
      auto move = [&](uint32_t* x) {
#pragma unroll
        for (int k = 0; k < 16; k++) asm volatile("mul.rn.f32 %0, %0, %1;" : "+r"(x[k]) : "f"(P.one));
      };
      wg_fence();
#pragma unroll
      for (int i = 0; i < NP; i++) tail(1, i);
      if (NP) wg_commit();
      wg_wait<NP ? 1 : 0>();
#pragma unroll
      for (int k = 0; k < 96; k++) asm volatile("" : "+f"(acc[k])::"memory");
      if (elect()) mbar_arrive(BAR(B_EMPTY + 18));
      gate(acc + 28, 32);
#pragma unroll
      for (int g = 0; g < 8 + NB; g++) {
        const int k = 7 - g, i = (g - P0) / ST + NP;
        const bool mm = g >= P0 && (g - P0) % ST == 0;
        if (mm && i <= 7) split(P.zero, g);
        if (mm && i == 0) wg_fence();
        if (mm && i < 7) tail(1, i);
        if (mm && i == 6) wg_commit();
        if (g < 8) {
          if (k) gate(acc + 4 * k - 4, 32);
          mix(fr[0] + 2 * k, acc + 4 * k, 32);
          if (k == 4) hint(0);
          if (!(k & 3)) put(0, k);
          if (!k) move(fr[0]);
        } else {
#pragma unroll
          for (int e = 0; e < 4; e++) acc[96 + 4 * k + e] = silu2(acc[96 + 4 * k + e] * (e < 2 ? r0 : r1));
        }
      }
      static_assert(P0 + ST * (6 - NP) < 8 + NB, "all products are issued");
      split(P.zero, 14);
      wg_wait<0>();
#pragma unroll
      for (int k = 96; k < 192; k++) asm volatile("" : "+f"(acc[k])::"memory");
      if (elect()) mbar_arrive(BAR(B_EMPTY + 19));
#pragma unroll
      for (int k = 7 - NB; k >= 0; k--) gate(acc + 64 + 4 * k, 96);
      mbar_wait(BAR(B_FULL + 20));
      mbar_wait(BAR(B_FULL + 21));
#pragma unroll
      for (int k = 7; k >= 0; k--) {
        const float* g = acc + 64 + 4 * k;
        if (k < 8 - NB) mix(fr[1] + 2 * k, g, 96);
        else { fr[1][2 * k] = pack_bf16(g[0] * g[96], g[1] * g[97]); fr[1][2 * k + 1] = pack_bf16(g[2] * g[98], g[3] * g[99]); }
      }
#pragma unroll
      for (int k = 0; k < 4; k++) pin4(P.zero, fr[1] + 4 * k);
      if (PA) { put(1, 4); hint(1); }
      if (PA == 2) put(1, 0);
      if (PA) split(P.zero, 31);
      wg_fence();
      own(0);
      own(1);
      split(P.zero, 15);
      if (!PA) { put(1, 4); hint(1); }
      if (!O3) own(2);
      if (PA < 2) put(1, 0);
      if (!O3) { own(3); wg_commit(); }
      gate(acc + 124, 32);
#pragma unroll
      for (int g = 0; g < 8; g++) {
        const int k = 7 - g, i = (g - O0) / OS + (O3 ? 2 : 4);
        const bool mm = g >= O0 && (g - O0) % OS == 0 && i < 8;
        if (mm || g == 0) split(P.zero, 16 + k);
        if (mm) own(i);
        if (mm && (i == 3 || i == 5 || i == 7)) wg_commit();
        if (mm && i == 5) { wg_wait<1>(); if (elect()) mbar_arrive(BAR(B_EMPTY + 20)); }
        if (k) gate(acc + 92 + 4 * k, 32);
        mix(fr[2] + 2 * k, acc + 96 + 4 * k, 32);
        if (k == 1) hint(2);
        if (!(k & 3)) put(2, k);
      }
      static_assert(O0 + OS * (O3 ? 5 : 3) < 8, "all products are issued");
      mbar_wait(BAR(B_FULL + 22));
      wg_fence();
#pragma unroll
      for (int i = 8; i < 12; i++) own(i);
      wg_commit();
      wg_wait<1>();
      if (elect()) mbar_arrive(BAR(B_EMPTY + 21));
      ck = base + OFF_A + wg * ARING + 2048 * w + 516 * (lane >> 3) + 144 * (lane >> 2 & 1) + 32 * (lane & 3);
    }
    uint32_t x1[40];
    if (!wg) {
      REGION_IDS;
      const uint32_t xa = base + (lane >> 4) * 1024 + (lane & 7) * 128 + (((2 * w + ((lane >> 3) & 1)) ^ (lane & 7)) << 4);
      mbar_wait(BAR(B_FULL + 32));
#pragma unroll
      for (int k = 0; k < 10; k++) ldmatrix_x4_t(x1 + 4 * k, xa + (k < 6 ? OFF_X1 + k / 2 * WSLOT + (k & 1) * 2048 : OFF_SX + 2048 * (k - 6)));
    }
#pragma unroll 1
    for (int u = 23; u < (wg ? 32 : LAG2); u++) {
      as = P.hid[wg][u - 23];
      const uint64_t wd = mkdesc(0, 0, bo, 1) | P.w2t[u - 20].x;
      mbar_wait(BAR(B_FULL + u));
      a_tile(as, u - 23, false);
      wg_fence();
#pragma unroll
      for (int kk = 0; kk < 4; kk++) wg_ss160_01(o, mkdesc(abd + as + kk / 2 * 512 + (kk & 1) * 32, 16, 1024, 2), wd + kk * 128, 1);
      wg_commit();
      if (u == 31 && elect()) mbar_arrive(BAR(B_LAG));
      wg_wait<1>();
      if (elect()) mbar_arrive(BAR(B_EMPTY + u - 1));
    }
    int h, j, r;
    ffn_role(h, j, r);
    REGION_IDS;
    const uint32_t xb = base + OFF_XCH + 5120 * w;
    if (wg) {
      const uint32_t rdst = mapa(xb + 16 * lane, h ^ 1), rbar = mapa(BAR(B_FULL), h ^ 1);
      mbar_wait(BAR(B_XFREE));
      wg_wait<0>();
      fence_regs(o);
#pragma unroll
      for (int k = 0; k < 10; k++)
        asm volatile("st.async.shared::cluster.mbarrier::complete_tx::bytes.v4.b32 [%0], {%1,%2,%3,%4}, [%5];" ::"r"(rdst + 512 * k), "r"(pack_bf16(o[8 * k], o[8 * k + 1])),
                     "r"(pack_bf16(o[8 * k + 2], o[8 * k + 3])), "r"(pack_bf16(o[8 * k + 4], o[8 * k + 5])), "r"(pack_bf16(o[8 * k + 6], o[8 * k + 7])), "r"(rbar + 8 * (k / 4)) : "memory");
    } else {
      uint32_t gr[40];
      const float r0 = __uint_as_float(lds32(base + OFF_RT + 64 * w + (lane & 28))), r1 = __uint_as_float(lds32(base + OFF_RT + 64 * w + 32 + (lane & 28)));
      const uint32_t p0 = pack_bf16(r0, r0), p1 = pack_bf16(r1, r1), q0 = pack_bf16(r0 - bf_lo(p0), r0 - bf_lo(p0)), q1 = pack_bf16(r1 - bf_lo(p1), r1 - bf_lo(p1));
      mbar_wait(BAR(B_GB));
#pragma unroll
      for (int k = 0; k < 5; k++) {
        const uint4 g = lds128(base + OFF_GB + 80 * (lane & 3) + 16 * k);
        gr[8 * k] = g.x; gr[8 * k + 2] = g.y; gr[8 * k + 4] = g.z; gr[8 * k + 6] = g.w;
      }
      auto scale = [&](int k) {
#pragma unroll
        for (int e = 4 * k; e < 4 * k + 4; e += 2) { gr[e + 1] = bfma2(gr[e], p1, bmul2(gr[e], q1)); gr[e] = bfma2(gr[e], p0, bmul2(gr[e], q0)); }
      };
#pragma unroll
      for (int k = max(127 - 4 * LAG2, 0); k < 10; k++) scale(k);
      wg_wait<0>();
      if (elect()) mbar_arrive(BAR(B_EMPTY + LAG2 - 1));
#pragma unroll 1
      for (int u = LAG2; u < 32; u++) {
        mbar_wait(BAR(B_FULL + u));
        a_tile(P.hid[0][u - 23], u - 23, false);
      }
      auto da = [&](int i) { return mkdesc(DB + hid_at(i / 4 + LAG2 - 23, 0) + (i & 2) * 256 + (i & 1) * 32, 16, 1024, 2); };
      auto db = [&](int i, int b) { return mkdesc(DB + w2_at(i / 4 + LAG2 - 20) + b * w2_step(i / 4 + LAG2 - 20) + (i & 3) * 2048, w2_step(i / 4 + LAG2 - 20), bo, 1); };
      const int row = 128 * r + 64 * h + 16 * w;
      auto merge = [&](int e) {
        if (e % 4 == 0) mbar_wait_cluster(BAR(B_FULL + e / 4), 1);
        const uint4 p = lds128(xb + 16 * lane + 512 * e);
        x1[4 * e] = bfma2(gr[4 * e], p.x, x1[4 * e]); x1[4 * e + 1] = bfma2(gr[4 * e + 1], p.y, x1[4 * e + 1]);
        x1[4 * e + 2] = bfma2(gr[4 * e + 2], p.z, x1[4 * e + 2]); x1[4 * e + 3] = bfma2(gr[4 * e + 3], p.w, x1[4 * e + 3]);
      };
      auto out = [&](int k) {
        const float* v = o + 8 * k;
        uint32_t y[4];
#pragma unroll
        for (int e = 0; e < 4; e++) y[e] = bfma2(gr[4 * k + e], pack_bf16(v[2 * e], v[2 * e + 1]), x1[4 * k + e]);
        stmatrix_x4(k < 8 ? xb + 2048 * (k >> 2) + (lane & 15) * 128 + (((2 * (k & 3) + (lane >> 4)) ^ (lane & 7) ^ 4 * (j & 1)) << 4)
                          : xb + 4096 + (lane & 15) * 64 + (((2 * (k & 1) + (lane >> 4)) ^ (lane >> 1 & 3)) << 4), y[0], y[1], y[2], y[3]);
        if ((k & 3) == 3 || k == 9) {
          fence_async_smem();
          __syncwarp();
          if (lane == 0) tma2d_store(k < 8 ? &maps.outa : &maps.outb, k < 8 ? 128 * j + 64 * (k >> 2) : 512 + 32 * j, row, xb + 2048 * (k >> 2));
        }
      };
      constexpr int ND = 128 - 4 * LAG2;
      mbar_wait(BAR(B_LAG));
      wg_fence();
#pragma unroll
      for (int i = 0; i < ND; i++) {
        wg_ss160_01(o, da(i), db(i, 0), 1);
        if (i >= 1 && i <= 10) { scale(i - 1); split(P.zero, 32 + i); }
      }
      wg_commit();
#pragma unroll
      for (int e = 0; e < MG; e++) merge(e);
      __syncwarp();
      wg_wait<0>();
      fence_regs(o);
#pragma unroll
      for (int k = 0; k < 10; k++) {
        if (k >= MG && k % 4 == 0) {
#pragma unroll
          for (int e = k; e < min(k + 4, 10); e++) merge(e);
          __syncwarp();
        }
        out(k);
      }
      if (lane == 0) { bulk_commit(); bulk_wait_read(); }
    }
  }
}

typedef CUresult (*EncFn)(CUtensorMap*, CUtensorMapDataType, cuuint32_t, void*, const cuuint64_t*, const cuuint64_t*, const cuuint32_t*,
                          const cuuint32_t*, CUtensorMapInterleave, CUtensorMapSwizzle, CUtensorMapL2promotion, CUtensorMapFloatOOBfill);
static int enc_err = 0;
static void enc(EncFn fn, CUtensorMap* m, const void* p, int rank, const cuuint64_t* gd, const cuuint64_t* gs, const cuuint32_t* bd, CUtensorMapSwizzle sw) {
  cuuint32_t es[5] = {1, 1, 1, 1, 1};
  enc_err = 2 * enc_err + (fn(m, CU_TENSOR_MAP_DATA_TYPE_BFLOAT16, rank, (void*)p, gd, gs, bd, es, CU_TENSOR_MAP_INTERLEAVE_NONE, sw,
                              CU_TENSOR_MAP_L2_PROMOTION_L2_128B, CU_TENSOR_MAP_FLOAT_OOB_FILL_NONE) != CUDA_SUCCESS);
}

extern "C" void kernel_launch(void* const* d_in, const int* in_sizes, int n_in, void* d_out, int out_size) {
  const bf16 *q = (const bf16*)d_in[0], *k = (const bf16*)d_in[1], *v = (const bf16*)d_in[2], *shift = (const bf16*)d_in[3],
             *ssmk = (const bf16*)d_in[4], *ssmd = (const bf16*)d_in[5], *w1 = (const bf16*)d_in[7], *w3 = (const bf16*)d_in[8],
             *w2 = (const bf16*)d_in[9], *c = (const bf16*)d_in[10], *wmod = (const bf16*)d_in[11];
  EncFn fn = nullptr;
  cudaDriverEntryPointQueryResult qr;
  cudaGetDriverEntryPoint("cuTensorMapEncodeTiled", (void**)&fn, cudaEnableDefault, &qr);
  Scratch* pg;
  cudaGetSymbolAddress((void**)&pg, g_s);
  Maps maps;
  enc_err = 0;
  const CUtensorMapSwizzle S128 = CU_TENSOR_MAP_SWIZZLE_128B;
  { cuuint64_t gd[3] = {D_, S_ / 8, 8}, gs[2] = {D_ * 16, D_ * 2}; cuuint32_t b[3] = {64, 4, 8};
    enc(fn, &maps.km, k, 3, gd, gs, b, S128);
    enc(fn, &maps.v, v, 3, gd, gs, b, S128);
    enc(fn, &maps.q, q, 3, gd, gs, b, S128);
    b[2] = 3;
    enc(fn, &maps.kh, k, 3, gd, gs, b, S128); }
  { cuuint64_t gd[3] = {256, 2, 5}, gs[2] = {512, 1024}; cuuint32_t b[3] = {256, 1, 5};
    enc(fn, &maps.tap, shift, 3, gd, gs, b, CU_TENSOR_MAP_SWIZZLE_NONE); }
  { cuuint64_t gd[3] = {6 * D_, D_, 1}, gs[2] = {6 * D_ * 2, 6 * D_ * 2 * D_}; cuuint32_t b[3] = {64, 64, 1};
    enc(fn, &maps.wm, wmod, 3, gd, gs, b, S128); }
  { cuuint64_t gd[3] = {64, D_, F_ / 64}, gs[2] = {F_ * 2, 128}; cuuint32_t b[3] = {64, 32, 3};
    enc(fn, &maps.w1, w1, 3, gd, gs, b, S128);
    enc(fn, &maps.w3, w3, 3, gd, gs, b, S128);
    b[1] = 16;
    enc(fn, &maps.w1e, w1, 3, gd, gs, b, S128);
    enc(fn, &maps.w3e, w3, 3, gd, gs, b, S128);
    b[1] = 32; b[2] = 1;
    enc(fn, &maps.w1s, w1, 3, gd, gs, b, S128);
    enc(fn, &maps.w3s, w3, 3, gd, gs, b, S128); }
  { cuuint64_t gd[2] = {S_, D_}, gs[1] = {S_ * 2}; cuuint32_t b1[2] = {64, 64}, b2[2] = {64, 32};
    enc(fn, &maps.xs, pg->xs, 2, gd, gs, b1, S128);
    gd[1] = 2 * D_;
    enc(fn, &maps.x1b, pg->x1, 2, gd, gs, b2, S128);
    enc(fn, &maps.x1s, pg->x1, 2, gd, gs, b2, CU_TENSOR_MAP_SWIZZLE_NONE); }
  { cuuint64_t gd[5] = {D_, 2, 4, 4, 48}, gs[4] = {D_ * 2, D_ * 4, D_ * 16, D_ * 64}; cuuint32_t b[5] = {64, 2, 4, 4, 2};
    enc(fn, &maps.w2a, w2, 5, gd, gs, b, S128);
    gs[1] = D_ * 16; gs[2] = D_ * 4;
    enc(fn, &maps.w2b, w2, 5, gd, gs, b, S128); }
  { cuuint64_t gd[2] = {D_, S_}, gs[1] = {D_ * 2}; cuuint32_t b1[2] = {64, 16}, b2[2] = {32, 16};
    enc(fn, &maps.outa, d_out, 2, gd, gs, b1, S128);
    enc(fn, &maps.outb, d_out, 2, gd, gs, b2, CU_TENSOR_MAP_SWIZZLE_64B); }
  if (enc_err) return;
  cudaFuncSetAttribute(k_fused, cudaFuncAttributeMaxDynamicSharedMemorySize, SMEM_BYTES);
  cudaLaunchConfig_t cfg = {132, 512, SMEM_BYTES};
  cudaLaunchAttribute at = {cudaLaunchAttributeClusterDimension};
  at.val.clusterDim.x = 2; at.val.clusterDim.y = at.val.clusterDim.z = 1;
  cfg.attrs = &at; cfg.numAttrs = 1;
  int nc = 0;
  cudaOccupancyMaxActiveClusters(&nc, k_fused, &cfg);
  Ptrs P = {ssmk, c, ssmd, pg, 0xE48DCBA9ull, {0x676760, 0x64620F01}, 0, 700, 420, 5500, 0, 0, 0x20400, 0, 6, B_KV, 0, 0, 2, 1, 0x57C00, 1.f};
  const char* sched = "k10v14f04q04q14q24q34q44k24v24f14k34v34f24k44v44f34f44";
  int t = 700, pace = 440;
  for (int e = 0; e < NE; e++) {
    const char x = sched[3 * e];
    const int r = sched[3 * e + 1] - '0', kind = x == 'k' ? 0 : x == 'v' ? 1 : x == 'q' ? 2 : x == 'f' ? 3 : 4;
    t += (sched[3 * e + 2] - '0') * pace / 4;
    P.sched[e] = make_uint2(t | kind << 16 | r << 20, (kind < 2 ? tab(T_KV, r) + kind * KV_V : kind == 2 ? OFF_Q + 4096 * r : tab(T_F, r) + F_E) | (r + (kind < 2 ? B_KV : kind == 2 ? B_Q : B_FRAW)) << 18);
  }
  for (int u = 0; u < 5; u++) P.wt[u] = 11500 + 400 * u;
  const int dep[5] = {B_FL + 1, B_FL + 2, B_PFULL + 2, B_FL + 1, B_PEMPTY + 2};
  for (int u = 0; u < 20; u++) P.wdep[u] = u % 5 * WSLOT | (~u & 1) << 12 | (u < 5 ? dep[u] : B_EMPTY + u - 5);
  for (int v = 0; v < 12; v++) P.w2t[v] = make_uint2(w2_desc(v), v ? B_EMPTY + (v > 5 ? 15 + v : v > 3 ? 14 + v : v > 1 ? 16 : 15) : B_UVD);
  for (int m = 0; m < 9; m++) { P.hid[0][m] = hid_at(m, 0) - OFF_A; P.hid[1][m] = hid_at(m, 1) - OFF_A - ARING; P.hid[2][m] = B_EMPTY + 19 + (m > 2 ? m : m / 2); }
  if (nc < 66) { P.boff = 128; k_fused<<<4, 512, SMEM_BYTES, cudaStreamPerThread>>>(P, maps); P.boff = 0; }
  k_fused<<<nc < 66 ? 128 : 132, 512, SMEM_BYTES, cudaStreamPerThread>>>(P, maps);
}
```

```cpp
#include <cuda_runtime.h>
#include <cuda.h>
#include <cuda_bf16.h>
#include <stdint.h>
#include <stdlib.h>
#include <stdio.h>

typedef __nv_bfloat16 bf16;
constexpr int S_ = 2048, D_ = 640, F_ = 1536;

struct Scratch {
  uint32_t st1[2][1024];
  uint32_t st2[32][4][128];
  uint2 modc[128][32];
  uint2 modv[3][D_];
  uint32_t uv[8][3072];
  unsigned hint[9][8][32];
  unsigned xsh[5][8][32], hhf[256 * 8];
  uint4 xr[D_ * 256];
  uint4 qt[D_ * 256];
  uint4 xs[D_ * 256];
  uint4 x1[2][D_ * 256];
  uint4 hh[32 * 8 * 1536];
};
__device__ __align__(1024) Scratch g_s;

__device__ __forceinline__ uint32_t smem_u32(const void* p) { return (uint32_t)__cvta_generic_to_shared(p); }
__device__ __forceinline__ void mbar_expect_tx(uint32_t b, uint32_t n) { asm volatile("mbarrier.arrive.expect_tx.shared::cta.b64 _, [%0], %1;" ::"r"(b), "r"(n) : "memory"); }
__device__ __forceinline__ void mbar_arrive(uint32_t b) { asm volatile("mbarrier.arrive.shared::cta.b64 _, [%0];" ::"r"(b) : "memory"); }
__device__ __forceinline__ void mbar_arrive2(uint32_t b) { asm volatile("mbarrier.arrive.shared::cta.b64 _, [%0], 2;" ::"r"(b) : "memory"); }
__device__ __forceinline__ uint32_t mapa(uint32_t a, uint32_t cta) { uint32_t r; asm volatile("mapa.shared::cluster.u32 %0, %1, %2;" : "=r"(r) : "r"(a), "r"(cta)); return r; }
__device__ __forceinline__ void mbar_arrive_remote(uint32_t rb) { asm volatile("mbarrier.arrive.shared::cluster.b64 _, [%0];" ::"r"(rb) : "memory"); }
constexpr int SPIN_LIMIT = 1 << 16;
template <int N> __device__ __forceinline__ void mbar_init(uint32_t b, uint32_t count) {
#pragma unroll
  for (int i = 0; i < N; i++) asm volatile("mbarrier.init.shared::cta.b64 [%0], %1;" ::"r"(b + 8 * i), "r"(count) : "memory");
}
__device__ __forceinline__ bool elect() { uint32_t p; asm volatile("{.reg .pred q; elect.sync _|q, 0xffffffff; selp.u32 %0, 1, 0, q;}" : "=r"(p)); return p; }
__device__ __forceinline__ void arrive1(uint32_t b) { __syncwarp(); if (elect()) mbar_arrive(b); }
__device__ __forceinline__ bool mbar_test(uint32_t b) {
  uint32_t ok;
  asm volatile("{.reg .pred p; mbarrier.test_wait.parity.shared::cta.b64 p, [%1], 0; selp.u32 %0,1,0,p;}" : "=r"(ok) : "r"(b) : "memory");
  return ok;
}
#define WAIT_LOOP(sem) "{.reg .pred p; mov.u32 %0, 0; W: mbarrier.try_wait.parity" sem ".shared::cta.b64 p, [%1], %2; @p bra.uni D; add.u32 %0, %0, 1; setp.lt.u32 p, %0, %3; @p bra.uni W; D:}"
__device__ __forceinline__ void mbar_wait(uint32_t b, uint32_t ph = 0) {
  int it;
  asm volatile(WAIT_LOOP("") : "=&r"(it) : "r"(b), "r"(ph), "n"(SPIN_LIMIT) : "memory");
}
__device__ __forceinline__ void mbar_wait_cluster(uint32_t b, uint32_t ph = 0) {
  int it;
  asm volatile(WAIT_LOOP(".acquire.cluster") : "=&r"(it) : "r"(b), "r"(ph), "n"(SPIN_LIMIT) : "memory");
}
__device__ __forceinline__ void wait_clock(uint32_t t) {
  asm volatile("{.reg .pred p; .reg .s32 d; W: mov.u32 d, %%clock; sub.s32 d, d, %0; setp.lt.s32 p, d, 0; @p bra.uni W;}" ::"r"(t) : "memory");
}
__device__ __forceinline__ void tma2d(uint32_t dst, const CUtensorMap* m, int c0, int c1, uint32_t bar) {
  asm volatile("cp.async.bulk.tensor.2d.shared::cluster.global.mbarrier::complete_tx::bytes [%0], [%1, {%3,%4}], [%2];" ::"r"(dst), "l"(m), "r"(bar), "r"(c0), "r"(c1) : "memory");
}
__device__ __forceinline__ void tma3d(uint32_t dst, const CUtensorMap* m, int c0, int c1, int c2, uint32_t bar) {
  asm volatile("cp.async.bulk.tensor.3d.shared::cluster.global.mbarrier::complete_tx::bytes [%0], [%1, {%3,%4,%5}], [%2];" ::"r"(dst), "l"(m), "r"(bar), "r"(c0), "r"(c1), "r"(c2) : "memory");
}
__device__ __forceinline__ void tma5d(uint32_t dst, const CUtensorMap* m, int c0, int c4, uint32_t bar) {
  asm volatile("cp.async.bulk.tensor.5d.shared::cluster.global.mbarrier::complete_tx::bytes [%0], [%1, {%4,%3,%3,%3,%5}], [%2];" ::"r"(dst), "l"(m), "r"(bar), "r"(0), "r"(c0), "r"(c4) : "memory");
}
__device__ __forceinline__ void tma2d_store(const CUtensorMap* m, int c0, int c1, uint32_t src) {
  asm volatile("cp.async.bulk.tensor.2d.global.shared::cta.bulk_group [%0, {%2,%3}], [%1];" ::"l"(m), "r"(src), "r"(c0), "r"(c1) : "memory");
}
__device__ __forceinline__ void bulk_load(uint32_t dst, const void* src, uint32_t bytes, uint32_t bar) {
  asm volatile("cp.async.bulk.shared::cluster.global.mbarrier::complete_tx::bytes [%0], [%1], %2, [%3];" ::"r"(dst), "l"(src), "r"(bytes), "r"(bar) : "memory");
}
__device__ __forceinline__ void prefetch_map(const CUtensorMap* m) { asm volatile("prefetch.tensormap [%0];" ::"l"(m) : "memory"); }
__device__ __forceinline__ void bulk_commit() { asm volatile("cp.async.bulk.commit_group;" ::: "memory"); }
__device__ __forceinline__ void bulk_wait_read() { asm volatile("cp.async.bulk.wait_group.read 0;" ::: "memory"); }
__device__ __forceinline__ void fence_async_smem() { asm volatile("fence.proxy.async.shared::cta;" ::: "memory"); }
__device__ __forceinline__ void fence_async_all() { asm volatile("fence.proxy.async.global;" ::: "memory"); }
__device__ __forceinline__ void named_bar(int id, int n) { asm volatile("bar.sync %0, %1;" ::"r"(id), "r"(n) : "memory"); }
__device__ __forceinline__ bool bar_all(int id, bool v) {
  uint32_t r;
  asm volatile("{.reg .pred p, q; setp.ne.u32 p, %2, 0; bar.red.and.pred q, %1, 128, p; selp.u32 %0, 1, 0, q;}" : "=r"(r) : "r"(id), "r"((uint32_t)v) : "memory");
  return __all_sync(~0u, r);
}
__device__ __forceinline__ void cluster_wait() { asm volatile("barrier.cluster.wait.aligned;" ::: "memory"); }
__device__ __forceinline__ void wg_fence() { asm volatile("wgmma.fence.sync.aligned;" ::: "memory"); }
__device__ __forceinline__ void wg_commit() { asm volatile("wgmma.commit_group.sync.aligned;" ::: "memory"); }
template <int N> __device__ __forceinline__ void wg_wait() { asm volatile("wgmma.wait_group.sync.aligned %0;" ::"n"(N) : "memory"); }
template <int N> __device__ __forceinline__ void fence_regs(float (&a)[N]) {
#pragma unroll
  for (int i = 0; i < N; i++) asm volatile("" : "+f"(a[i])::"memory");
}
template <int N> __device__ __forceinline__ void fence_n(float* a) {
#pragma unroll
  for (int i = 0; i < N; i++) asm volatile("" : "+f"(a[i])::"memory");
}
__device__ __forceinline__ uint64_t mkdesc(uint32_t addr, uint32_t lbo, uint32_t sbo, uint32_t swz) {
  uint32_t lo = (addr >> 4) | ((lbo >> 4) << 16), hi = (sbo >> 4) | (swz << 30);
  return ((uint64_t)hi << 32) | lo;
}
__device__ __forceinline__ void stmatrix_x4(uint32_t a, uint32_t r0, uint32_t r1, uint32_t r2, uint32_t r3) {
  asm volatile("stmatrix.sync.aligned.m8n8.x4.shared.b16 [%0], {%1,%2,%3,%4};" ::"r"(a), "r"(r0), "r"(r1), "r"(r2), "r"(r3) : "memory");
}
__device__ __forceinline__ void stmatrix_x4_t(uint32_t a, uint32_t r0, uint32_t r1, uint32_t r2, uint32_t r3) {
  asm volatile("stmatrix.sync.aligned.m8n8.x4.trans.shared.b16 [%0], {%1,%2,%3,%4};" ::"r"(a), "r"(r0), "r"(r1), "r"(r2), "r"(r3) : "memory");
}
__device__ __forceinline__ void ldmatrix_x4_t(uint32_t* r, uint32_t a) {
  asm volatile("ldmatrix.sync.aligned.m8n8.x4.trans.shared.b16 {%0,%1,%2,%3}, [%4];" : "=r"(r[0]), "=r"(r[1]), "=r"(r[2]), "=r"(r[3]) : "r"(a) : "memory");
}
__device__ __forceinline__ uint32_t lds32(uint32_t a) { uint32_t v; asm volatile("ld.shared.b32 %0, [%1];" : "=r"(v) : "r"(a) : "memory"); return v; }
__device__ __forceinline__ uint2 lds64(uint32_t a) { uint2 v; asm volatile("ld.shared.v2.b32 {%0,%1}, [%2];" : "=r"(v.x), "=r"(v.y) : "r"(a) : "memory"); return v; }
__device__ __forceinline__ uint4 lds128(uint32_t a) { uint4 v; asm volatile("ld.shared.v4.b32 {%0,%1,%2,%3}, [%4];" : "=r"(v.x), "=r"(v.y), "=r"(v.z), "=r"(v.w) : "r"(a) : "memory"); return v; }
__device__ __forceinline__ void sts32(uint32_t a, uint32_t v) { asm volatile("st.shared.b32 [%0], %1;" ::"r"(a), "r"(v) : "memory"); }
__device__ __forceinline__ void sts64(uint32_t a, uint32_t x, uint32_t y) { asm volatile("st.shared.v2.b32 [%0], {%1,%2};" ::"r"(a), "r"(x), "r"(y) : "memory"); }
__device__ __forceinline__ void sts128(uint32_t a, uint32_t x, uint32_t y, uint32_t z, uint32_t w) { asm volatile("st.shared.v4.b32 [%0], {%1,%2,%3,%4};" ::"r"(a), "r"(x), "r"(y), "r"(z), "r"(w) : "memory"); }
__device__ __forceinline__ uint4 ld_relaxed128(const void* p) { uint4 v; asm volatile("ld.relaxed.gpu.global.v4.u32 {%0,%1,%2,%3}, [%4];" : "=r"(v.x), "=r"(v.y), "=r"(v.z), "=r"(v.w) : "l"(p) : "memory"); return v; }
__device__ __forceinline__ uint2 ld_relaxed64(const void* p) { uint2 v; asm volatile("ld.relaxed.gpu.global.v2.u32 {%0,%1}, [%2];" : "=r"(v.x), "=r"(v.y) : "l"(p) : "memory"); return v; }
__device__ __forceinline__ uint32_t ld_relaxed32(const void* p) { uint32_t v; asm volatile("ld.relaxed.gpu.global.u32 %0, [%1];" : "=r"(v) : "l"(p) : "memory"); return v; }
__device__ __forceinline__ void st_relaxed128(void* p, uint32_t x, uint32_t y, uint32_t z, uint32_t w) { asm volatile("st.relaxed.gpu.global.v4.u32 [%0], {%1,%2,%3,%4};" ::"l"(p), "r"(x), "r"(y), "r"(z), "r"(w) : "memory"); }
__device__ __forceinline__ void st_relaxed32(void* p, uint32_t x) { asm volatile("st.relaxed.gpu.global.u32 [%0], %1;" ::"l"(p), "r"(x) : "memory"); }
__device__ __forceinline__ void red_hint(unsigned* p) { asm volatile("red.relaxed.gpu.global.add.u32 [%0], 1;" ::"l"(p) : "memory"); }
__device__ __forceinline__ void publish(uint32_t* p, uint32_t x) { asm volatile("{.reg .b32 t; atom.relaxed.gpu.global.exch.b32 t, [%0], %1;}" ::"l"(p), "r"(x) : "memory"); }
__device__ __forceinline__ uint32_t ldg32(const void* p) { uint32_t v; asm volatile("ld.global.nc.L1::no_allocate.b32 %0, [%1];" : "=r"(v) : "l"(p)); return v; }
__device__ __forceinline__ uint32_t pack_bf16(float lo, float hi) { uint32_t r; asm("cvt.rn.bf16x2.f32 %0, %1, %2;" : "=r"(r) : "f"(hi), "f"(lo)); return r; }
__device__ __forceinline__ float bf_lo(uint32_t v) { return __uint_as_float(v << 16); }
__device__ __forceinline__ float bf_hi(uint32_t v) { return __uint_as_float(v & 0xFFFF0000u); }
__device__ __forceinline__ uint32_t bmul2(uint32_t a, uint32_t b) { uint32_t r; asm("mul.rn.bf16x2 %0, %1, %2;" : "=r"(r) : "r"(a), "r"(b)); return r; }
__device__ __forceinline__ uint32_t badd2(uint32_t a, uint32_t b) { uint32_t r; asm("add.rn.bf16x2 %0, %1, %2;" : "=r"(r) : "r"(a), "r"(b)); return r; }
__device__ __forceinline__ uint32_t bfma2(uint32_t a, uint32_t b, uint32_t c) { uint32_t r; asm("fma.rn.bf16x2 %0, %1, %2, %3;" : "=r"(r) : "r"(a), "r"(b), "r"(c)); return r; }
__device__ __forceinline__ uint32_t set_tag(uint32_t x, uint32_t mask, uint32_t e) { uint32_t r; asm("lop3.b32 %0, %1, %2, %3, 0xB8;" : "=r"(r) : "r"(x), "r"(mask), "r"(e)); return r; }
__device__ __forceinline__ uint32_t opaque(uint32_t x) { asm volatile("" : "+r"(x)); return x; }
__device__ __forceinline__ float rbf(float x) { return __bfloat162float(__float2bfloat16(x)); }
__device__ __forceinline__ float silu_f(float x) {
  float e, r;
  asm("ex2.approx.ftz.f32 %0, %1;" : "=f"(e) : "f"(x * -1.4426950408889634f));
  asm("rcp.approx.ftz.f32 %0, %1;" : "=f"(r) : "f"(1.f + e));
  return x * r;
}
__device__ __forceinline__ float silu2(float x) {
  float t;
  asm("tanh.approx.f32 %0, %1;" : "=f"(t) : "f"(x));
  return fmaf(x, t, x);
}
__device__ __forceinline__ void pin(int off, uint32_t x) { asm volatile("{.reg .pred p; setp.lt.s32 p, %0, 0; @p st.shared.b32 [%0], %1;}" ::"r"(off), "r"(x) : "memory"); }
__device__ __forceinline__ void pin4(int off, const uint32_t* x) { asm volatile("{.reg .pred p; setp.lt.s32 p, %0, 0; @p st.shared.v4.b32 [%0], {%1,%2,%3,%4};}" ::"r"(off), "r"(x[0]), "r"(x[1]), "r"(x[2]), "r"(x[3]) : "memory"); }
__device__ __forceinline__ void split(int x, int n) { asm volatile("{.reg .pred p; setp.eq.s32 p, %0, %1; @p trap;}" ::"r"(x), "r"(~n) : "memory"); }
__device__ __forceinline__ void ln_final(float s, float q, float& m, float& sd) {
  m = s * (1.f / D_);
  asm("sqrt.approx.f32 %0, %1;" : "=f"(sd) : "f"(rbf(rbf(fmaxf(fmaf(-m, m, q * (1.f / D_)), 0.f)) + 1e-5f)));
  sd = rbf(sd);
}
__device__ __forceinline__ float rcpf(float x) { float r; asm("rcp.approx.f32 %0, %1;" : "=f"(r) : "f"(x)); return r; }

__device__ __forceinline__ void wg_rs16_0(float* d, const uint32_t* a, uint64_t db, int sc) {
  asm volatile("{.reg .pred p; setp.ne.b32 p, %13, 0; wgmma.mma_async.sync.aligned.m64n16k16.f32.bf16.bf16 {%0,%1,%2,%3,%4,%5,%6,%7}, {%8,%9,%10,%11}, %12, p, 1, 1, 0;}"
    : "+f"(d[0]),"+f"(d[1]),"+f"(d[2]),"+f"(d[3]),"+f"(d[4]),"+f"(d[5]),"+f"(d[6]),"+f"(d[7]) : "r"(a[0]),"r"(a[1]),"r"(a[2]),"r"(a[3]),"l"(db),"r"(sc));
}
__device__ __forceinline__ void wg_rs32_0(float* d, const uint32_t* a, uint64_t db, int sc) {
  asm volatile("{.reg .pred p; setp.ne.b32 p, %21, 0; wgmma.mma_async.sync.aligned.m64n32k16.f32.bf16.bf16 {%0,%1,%2,%3,%4,%5,%6,%7,%8,%9,%10,%11,%12,%13,%14,%15}, {%16,%17,%18,%19}, %20, p, 1, 1, 0;}"
    : "+f"(d[0]),"+f"(d[1]),"+f"(d[2]),"+f"(d[3]),"+f"(d[4]),"+f"(d[5]),"+f"(d[6]),"+f"(d[7]),"+f"(d[8]),"+f"(d[9]),"+f"(d[10]),"+f"(d[11]),"+f"(d[12]),"+f"(d[13]),"+f"(d[14]),"+f"(d[15]) : "r"(a[0]),"r"(a[1]),"r"(a[2]),"r"(a[3]),"l"(db),"r"(sc));
}
__device__ __forceinline__ void wg_rs48_0(float* d, const uint32_t* a, uint64_t db, int sc) {
  asm volatile("{.reg .pred p; setp.ne.b32 p, %29, 0; wgmma.mma_async.sync.aligned.m64n48k16.f32.bf16.bf16 {%0,%1,%2,%3,%4,%5,%6,%7,%8,%9,%10,%11,%12,%13,%14,%15,%16,%17,%18,%19,%20,%21,%22,%23}, {%24,%25,%26,%27}, %28, p, 1, 1, 0;}"
    : "+f"(d[0]),"+f"(d[1]),"+f"(d[2]),"+f"(d[3]),"+f"(d[4]),"+f"(d[5]),"+f"(d[6]),"+f"(d[7]),"+f"(d[8]),"+f"(d[9]),"+f"(d[10]),"+f"(d[11]),"+f"(d[12]),"+f"(d[13]),"+f"(d[14]),"+f"(d[15]),"+f"(d[16]),"+f"(d[17]),"+f"(d[18]),"+f"(d[19]),"+f"(d[20]),"+f"(d[21]),"+f"(d[22]),"+f"(d[23]) : "r"(a[0]),"r"(a[1]),"r"(a[2]),"r"(a[3]),"l"(db),"r"(sc));
}
__device__ __forceinline__ void wg_rs64_0(float* d, const uint32_t* a, uint64_t db, int sc) {
  asm volatile("{.reg .pred p; setp.ne.b32 p, %37, 0; wgmma.mma_async.sync.aligned.m64n64k16.f32.bf16.bf16 {%0,%1,%2,%3,%4,%5,%6,%7,%8,%9,%10,%11,%12,%13,%14,%15,%16,%17,%18,%19,%20,%21,%22,%23,%24,%25,%26,%27,%28,%29,%30,%31}, {%32,%33,%34,%35}, %36, p, 1, 1, 0;}"
    : "+f"(d[0]),"+f"(d[1]),"+f"(d[2]),"+f"(d[3]),"+f"(d[4]),"+f"(d[5]),"+f"(d[6]),"+f"(d[7]),"+f"(d[8]),"+f"(d[9]),"+f"(d[10]),"+f"(d[11]),"+f"(d[12]),"+f"(d[13]),"+f"(d[14]),"+f"(d[15]),"+f"(d[16]),"+f"(d[17]),"+f"(d[18]),"+f"(d[19]),"+f"(d[20]),"+f"(d[21]),"+f"(d[22]),"+f"(d[23]),"+f"(d[24]),"+f"(d[25]),"+f"(d[26]),"+f"(d[27]),"+f"(d[28]),"+f"(d[29]),"+f"(d[30]),"+f"(d[31]) : "r"(a[0]),"r"(a[1]),"r"(a[2]),"r"(a[3]),"l"(db),"r"(sc));
}
__device__ __forceinline__ void wg_rs80_0(float* d, const uint32_t* a, uint64_t db, int sc) {
  asm volatile("{.reg .pred p; setp.ne.b32 p, %45, 0; wgmma.mma_async.sync.aligned.m64n80k16.f32.bf16.bf16 {%0,%1,%2,%3,%4,%5,%6,%7,%8,%9,%10,%11,%12,%13,%14,%15,%16,%17,%18,%19,%20,%21,%22,%23,%24,%25,%26,%27,%28,%29,%30,%31,%32,%33,%34,%35,%36,%37,%38,%39}, {%40,%41,%42,%43}, %44, p, 1, 1, 0;}"
    : "+f"(d[0]),"+f"(d[1]),"+f"(d[2]),"+f"(d[3]),"+f"(d[4]),"+f"(d[5]),"+f"(d[6]),"+f"(d[7]),"+f"(d[8]),"+f"(d[9]),"+f"(d[10]),"+f"(d[11]),"+f"(d[12]),"+f"(d[13]),"+f"(d[14]),"+f"(d[15]),"+f"(d[16]),"+f"(d[17]),"+f"(d[18]),"+f"(d[19]),"+f"(d[20]),"+f"(d[21]),"+f"(d[22]),"+f"(d[23]),"+f"(d[24]),"+f"(d[25]),"+f"(d[26]),"+f"(d[27]),"+f"(d[28]),"+f"(d[29]),"+f"(d[30]),"+f"(d[31]),"+f"(d[32]),"+f"(d[33]),"+f"(d[34]),"+f"(d[35]),"+f"(d[36]),"+f"(d[37]),"+f"(d[38]),"+f"(d[39]) : "r"(a[0]),"r"(a[1]),"r"(a[2]),"r"(a[3]),"l"(db),"r"(sc));
}
__device__ __forceinline__ void wg_rs96_0(float* d, const uint32_t* a, uint64_t db, int sc) {
  asm volatile("{.reg .pred p; setp.ne.b32 p, %53, 0; wgmma.mma_async.sync.aligned.m64n96k16.f32.bf16.bf16 {%0,%1,%2,%3,%4,%5,%6,%7,%8,%9,%10,%11,%12,%13,%14,%15,%16,%17,%18,%19,%20,%21,%22,%23,%24,%25,%26,%27,%28,%29,%30,%31,%32,%33,%34,%35,%36,%37,%38,%39,%40,%41,%42,%43,%44,%45,%46,%47}, {%48,%49,%50,%51}, %52, p, 1, 1, 0;}"
    : "+f"(d[0]),"+f"(d[1]),"+f"(d[2]),"+f"(d[3]),"+f"(d[4]),"+f"(d[5]),"+f"(d[6]),"+f"(d[7]),"+f"(d[8]),"+f"(d[9]),"+f"(d[10]),"+f"(d[11]),"+f"(d[12]),"+f"(d[13]),"+f"(d[14]),"+f"(d[15]),"+f"(d[16]),"+f"(d[17]),"+f"(d[18]),"+f"(d[19]),"+f"(d[20]),"+f"(d[21]),"+f"(d[22]),"+f"(d[23]),"+f"(d[24]),"+f"(d[25]),"+f"(d[26]),"+f"(d[27]),"+f"(d[28]),"+f"(d[29]),"+f"(d[30]),"+f"(d[31]),"+f"(d[32]),"+f"(d[33]),"+f"(d[34]),"+f"(d[35]),"+f"(d[36]),"+f"(d[37]),"+f"(d[38]),"+f"(d[39]),"+f"(d[40]),"+f"(d[41]),"+f"(d[42]),"+f"(d[43]),"+f"(d[44]),"+f"(d[45]),"+f"(d[46]),"+f"(d[47]) : "r"(a[0]),"r"(a[1]),"r"(a[2]),"r"(a[3]),"l"(db),"r"(sc));
}
__device__ __forceinline__ void wg_rs112_0(float* d, const uint32_t* a, uint64_t db, int sc) {
  asm volatile("{.reg .pred p; setp.ne.b32 p, %61, 0; wgmma.mma_async.sync.aligned.m64n112k16.f32.bf16.bf16 {%0,%1,%2,%3,%4,%5,%6,%7,%8,%9,%10,%11,%12,%13,%14,%15,%16,%17,%18,%19,%20,%21,%22,%23,%24,%25,%26,%27,%28,%29,%30,%31,%32,%33,%34,%35,%36,%37,%38,%39,%40,%41,%42,%43,%44,%45,%46,%47,%48,%49,%50,%51,%52,%53,%54,%55}, {%56,%57,%58,%59}, %60, p, 1, 1, 0;}"
    : "+f"(d[0]),"+f"(d[1]),"+f"(d[2]),"+f"(d[3]),"+f"(d[4]),"+f"(d[5]),"+f"(d[6]),"+f"(d[7]),"+f"(d[8]),"+f"(d[9]),"+f"(d[10]),"+f"(d[11]),"+f"(d[12]),"+f"(d[13]),"+f"(d[14]),"+f"(d[15]),"+f"(d[16]),"+f"(d[17]),"+f"(d[18]),"+f"(d[19]),"+f"(d[20]),"+f"(d[21]),"+f"(d[22]),"+f"(d[23]),"+f"(d[24]),"+f"(d[25]),"+f"(d[26]),"+f"(d[27]),"+f"(d[28]),"+f"(d[29]),"+f"(d[30]),"+f"(d[31]),"+f"(d[32]),"+f"(d[33]),"+f"(d[34]),"+f"(d[35]),"+f"(d[36]),"+f"(d[37]),"+f"(d[38]),"+f"(d[39]),"+f"(d[40]),"+f"(d[41]),"+f"(d[42]),"+f"(d[43]),"+f"(d[44]),"+f"(d[45]),"+f"(d[46]),"+f"(d[47]),"+f"(d[48]),"+f"(d[49]),"+f"(d[50]),"+f"(d[51]),"+f"(d[52]),"+f"(d[53]),"+f"(d[54]),"+f"(d[55]) : "r"(a[0]),"r"(a[1]),"r"(a[2]),"r"(a[3]),"l"(db),"r"(sc));
}
__device__ __forceinline__ void wg_rs128_0(float* d, const uint32_t* a, uint64_t db, int sc) {
  asm volatile("{.reg .pred p; setp.ne.b32 p, %69, 0; wgmma.mma_async.sync.aligned.m64n128k16.f32.bf16.bf16 {%0,%1,%2,%3,%4,%5,%6,%7,%8,%9,%10,%11,%12,%13,%14,%15,%16,%17,%18,%19,%20,%21,%22,%23,%24,%25,%26,%27,%28,%29,%30,%31,%32,%33,%34,%35,%36,%37,%38,%39,%40,%41,%42,%43,%44,%45,%46,%47,%48,%49,%50,%51,%52,%53,%54,%55,%56,%57,%58,%59,%60,%61,%62,%63}, {%64,%65,%66,%67}, %68, p, 1, 1, 0;}"
    : "+f"(d[0]),"+f"(d[1]),"+f"(d[2]),"+f"(d[3]),"+f"(d[4]),"+f"(d[5]),"+f"(d[6]),"+f"(d[7]),"+f"(d[8]),"+f"(d[9]),"+f"(d[10]),"+f"(d[11]),"+f"(d[12]),"+f"(d[13]),"+f"(d[14]),"+f"(d[15]),"+f"(d[16]),"+f"(d[17]),"+f"(d[18]),"+f"(d[19]),"+f"(d[20]),"+f"(d[21]),"+f"(d[22]),"+f"(d[23]),"+f"(d[24]),"+f"(d[25]),"+f"(d[26]),"+f"(d[27]),"+f"(d[28]),"+f"(d[29]),"+f"(d[30]),"+f"(d[31]),"+f"(d[32]),"+f"(d[33]),"+f"(d[34]),"+f"(d[35]),"+f"(d[36]),"+f"(d[37]),"+f"(d[38]),"+f"(d[39]),"+f"(d[40]),"+f"(d[41]),"+f"(d[42]),"+f"(d[43]),"+f"(d[44]),"+f"(d[45]),"+f"(d[46]),"+f"(d[47]),"+f"(d[48]),"+f"(d[49]),"+f"(d[50]),"+f"(d[51]),"+f"(d[52]),"+f"(d[53]),"+f"(d[54]),"+f"(d[55]),"+f"(d[56]),"+f"(d[57]),"+f"(d[58]),"+f"(d[59]),"+f"(d[60]),"+f"(d[61]),"+f"(d[62]),"+f"(d[63]) : "r"(a[0]),"r"(a[1]),"r"(a[2]),"r"(a[3]),"l"(db),"r"(sc));
}
__device__ __forceinline__ void wg_rs144_0(float* d, const uint32_t* a, uint64_t db, int sc) {
  asm volatile("{.reg .pred p; setp.ne.b32 p, %77, 0; wgmma.mma_async.sync.aligned.m64n144k16.f32.bf16.bf16 {%0,%1,%2,%3,%4,%5,%6,%7,%8,%9,%10,%11,%12,%13,%14,%15,%16,%17,%18,%19,%20,%21,%22,%23,%24,%25,%26,%27,%28,%29,%30,%31,%32,%33,%34,%35,%36,%37,%38,%39,%40,%41,%42,%43,%44,%45,%46,%47,%48,%49,%50,%51,%52,%53,%54,%55,%56,%57,%58,%59,%60,%61,%62,%63,%64,%65,%66,%67,%68,%69,%70,%71}, {%72,%73,%74,%75}, %76, p, 1, 1, 0;}"
    : "+f"(d[0]),"+f"(d[1]),"+f"(d[2]),"+f"(d[3]),"+f"(d[4]),"+f"(d[5]),"+f"(d[6]),"+f"(d[7]),"+f"(d[8]),"+f"(d[9]),"+f"(d[10]),"+f"(d[11]),"+f"(d[12]),"+f"(d[13]),"+f"(d[14]),"+f"(d[15]),"+f"(d[16]),"+f"(d[17]),"+f"(d[18]),"+f"(d[19]),"+f"(d[20]),"+f"(d[21]),"+f"(d[22]),"+f"(d[23]),"+f"(d[24]),"+f"(d[25]),"+f"(d[26]),"+f"(d[27]),"+f"(d[28]),"+f"(d[29]),"+f"(d[30]),"+f"(d[31]),"+f"(d[32]),"+f"(d[33]),"+f"(d[34]),"+f"(d[35]),"+f"(d[36]),"+f"(d[37]),"+f"(d[38]),"+f"(d[39]),"+f"(d[40]),"+f"(d[41]),"+f"(d[42]),"+f"(d[43]),"+f"(d[44]),"+f"(d[45]),"+f"(d[46]),"+f"(d[47]),"+f"(d[48]),"+f"(d[49]),"+f"(d[50]),"+f"(d[51]),"+f"(d[52]),"+f"(d[53]),"+f"(d[54]),"+f"(d[55]),"+f"(d[56]),"+f"(d[57]),"+f"(d[58]),"+f"(d[59]),"+f"(d[60]),"+f"(d[61]),"+f"(d[62]),"+f"(d[63]),"+f"(d[64]),"+f"(d[65]),"+f"(d[66]),"+f"(d[67]),"+f"(d[68]),"+f"(d[69]),"+f"(d[70]),"+f"(d[71]) : "r"(a[0]),"r"(a[1]),"r"(a[2]),"r"(a[3]),"l"(db),"r"(sc));
}
__device__ __forceinline__ void wg_rs160_0(float* d, const uint32_t* a, uint64_t db, int sc) {
  asm volatile("{.reg .pred p; setp.ne.b32 p, %85, 0; wgmma.mma_async.sync.aligned.m64n160k16.f32.bf16.bf16 {%0,%1,%2,%3,%4,%5,%6,%7,%8,%9,%10,%11,%12,%13,%14,%15,%16,%17,%18,%19,%20,%21,%22,%23,%24,%25,%26,%27,%28,%29,%30,%31,%32,%33,%34,%35,%36,%37,%38,%39,%40,%41,%42,%43,%44,%45,%46,%47,%48,%49,%50,%51,%52,%53,%54,%55,%56,%57,%58,%59,%60,%61,%62,%63,%64,%65,%66,%67,%68,%69,%70,%71,%72,%73,%74,%75,%76,%77,%78,%79}, {%80,%81,%82,%83}, %84, p, 1, 1, 0;}"
    : "+f"(d[0]),"+f"(d[1]),"+f"(d[2]),"+f"(d[3]),"+f"(d[4]),"+f"(d[5]),"+f"(d[6]),"+f"(d[7]),"+f"(d[8]),"+f"(d[9]),"+f"(d[10]),"+f"(d[11]),"+f"(d[12]),"+f"(d[13]),"+f"(d[14]),"+f"(d[15]),"+f"(d[16]),"+f"(d[17]),"+f"(d[18]),"+f"(d[19]),"+f"(d[20]),"+f"(d[21]),"+f"(d[22]),"+f"(d[23]),"+f"(d[24]),"+f"(d[25]),"+f"(d[26]),"+f"(d[27]),"+f"(d[28]),"+f"(d[29]),"+f"(d[30]),"+f"(d[31]),"+f"(d[32]),"+f"(d[33]),"+f"(d[34]),"+f"(d[35]),"+f"(d[36]),"+f"(d[37]),"+f"(d[38]),"+f"(d[39]),"+f"(d[40]),"+f"(d[41]),"+f"(d[42]),"+f"(d[43]),"+f"(d[44]),"+f"(d[45]),"+f"(d[46]),"+f"(d[47]),"+f"(d[48]),"+f"(d[49]),"+f"(d[50]),"+f"(d[51]),"+f"(d[52]),"+f"(d[53]),"+f"(d[54]),"+f"(d[55]),"+f"(d[56]),"+f"(d[57]),"+f"(d[58]),"+f"(d[59]),"+f"(d[60]),"+f"(d[61]),"+f"(d[62]),"+f"(d[63]),"+f"(d[64]),"+f"(d[65]),"+f"(d[66]),"+f"(d[67]),"+f"(d[68]),"+f"(d[69]),"+f"(d[70]),"+f"(d[71]),"+f"(d[72]),"+f"(d[73]),"+f"(d[74]),"+f"(d[75]),"+f"(d[76]),"+f"(d[77]),"+f"(d[78]),"+f"(d[79]) : "r"(a[0]),"r"(a[1]),"r"(a[2]),"r"(a[3]),"l"(db),"r"(sc));
}
__device__ __forceinline__ void wg_rs176_0(float* d, const uint32_t* a, uint64_t db, int sc) {
  asm volatile("{.reg .pred p; setp.ne.b32 p, %93, 0; wgmma.mma_async.sync.aligned.m64n176k16.f32.bf16.bf16 {%0,%1,%2,%3,%4,%5,%6,%7,%8,%9,%10,%11,%12,%13,%14,%15,%16,%17,%18,%19,%20,%21,%22,%23,%24,%25,%26,%27,%28,%29,%30,%31,%32,%33,%34,%35,%36,%37,%38,%39,%40,%41,%42,%43,%44,%45,%46,%47,%48,%49,%50,%51,%52,%53,%54,%55,%56,%57,%58,%59,%60,%61,%62,%63,%64,%65,%66,%67,%68,%69,%70,%71,%72,%73,%74,%75,%76,%77,%78,%79,%80,%81,%82,%83,%84,%85,%86,%87}, {%88,%89,%90,%91}, %92, p, 1, 1, 0;}"
    : "+f"(d[0]),"+f"(d[1]),"+f"(d[2]),"+f"(d[3]),"+f"(d[4]),"+f"(d[5]),"+f"(d[6]),"+f"(d[7]),"+f"(d[8]),"+f"(d[9]),"+f"(d[10]),"+f"(d[11]),"+f"(d[12]),"+f"(d[13]),"+f"(d[14]),"+f"(d[15]),"+f"(d[16]),"+f"(d[17]),"+f"(d[18]),"+f"(d[19]),"+f"(d[20]),"+f"(d[21]),"+f"(d[22]),"+f"(d[23]),"+f"(d[24]),"+f"(d[25]),"+f"(d[26]),"+f"(d[27]),"+f"(d[28]),"+f"(d[29]),"+f"(d[30]),"+f"(d[31]),"+f"(d[32]),"+f"(d[33]),"+f"(d[34]),"+f"(d[35]),"+f"(d[36]),"+f"(d[37]),"+f"(d[38]),"+f"(d[39]),"+f"(d[40]),"+f"(d[41]),"+f"(d[42]),"+f"(d[43]),"+f"(d[44]),"+f"(d[45]),"+f"(d[46]),"+f"(d[47]),"+f"(d[48]),"+f"(d[49]),"+f"(d[50]),"+f"(d[51]),"+f"(d[52]),"+f"(d[53]),"+f"(d[54]),"+f"(d[55]),"+f"(d[56]),"+f"(d[57]),"+f"(d[58]),"+f"(d[59]),"+f"(d[60]),"+f"(d[61]),"+f"(d[62]),"+f"(d[63]),"+f"(d[64]),"+f"(d[65]),"+f"(d[66]),"+f"(d[67]),"+f"(d[68]),"+f"(d[69]),"+f"(d[70]),"+f"(d[71]),"+f"(d[72]),"+f"(d[73]),"+f"(d[74]),"+f"(d[75]),"+f"(d[76]),"+f"(d[77]),"+f"(d[78]),"+f"(d[79]),"+f"(d[80]),"+f"(d[81]),"+f"(d[82]),"+f"(d[83]),"+f"(d[84]),"+f"(d[85]),"+f"(d[86]),"+f"(d[87]) : "r"(a[0]),"r"(a[1]),"r"(a[2]),"r"(a[3]),"l"(db),"r"(sc));
}
__device__ __forceinline__ void wg_rs192_0(float* d, const uint32_t* a, uint64_t db, int sc) {
  asm volatile("{.reg .pred p; setp.ne.b32 p, %101, 0; wgmma.mma_async.sync.aligned.m64n192k16.f32.bf16.bf16 {%0,%1,%2,%3,%4,%5,%6,%7,%8,%9,%10,%11,%12,%13,%14,%15,%16,%17,%18,%19,%20,%21,%22,%23,%24,%25,%26,%27,%28,%29,%30,%31,%32,%33,%34,%35,%36,%37,%38,%39,%40,%41,%42,%43,%44,%45,%46,%47,%48,%49,%50,%51,%52,%53,%54,%55,%56,%57,%58,%59,%60,%61,%62,%63,%64,%65,%66,%67,%68,%69,%70,%71,%72,%73,%74,%75,%76,%77,%78,%79,%80,%81,%82,%83,%84,%85,%86,%87,%88,%89,%90,%91,%92,%93,%94,%95}, {%96,%97,%98,%99}, %100, p, 1, 1, 0;}"
    : "+f"(d[0]),"+f"(d[1]),"+f"(d[2]),"+f"(d[3]),"+f"(d[4]),"+f"(d[5]),"+f"(d[6]),"+f"(d[7]),"+f"(d[8]),"+f"(d[9]),"+f"(d[10]),"+f"(d[11]),"+f"(d[12]),"+f"(d[13]),"+f"(d[14]),"+f"(d[15]),"+f"(d[16]),"+f"(d[17]),"+f"(d[18]),"+f"(d[19]),"+f"(d[20]),"+f"(d[21]),"+f"(d[22]),"+f"(d[23]),"+f"(d[24]),"+f"(d[25]),"+f"(d[26]),"+f"(d[27]),"+f"(d[28]),"+f"(d[29]),"+f"(d[30]),"+f"(d[31]),"+f"(d[32]),"+f"(d[33]),"+f"(d[34]),"+f"(d[35]),"+f"(d[36]),"+f"(d[37]),"+f"(d[38]),"+f"(d[39]),"+f"(d[40]),"+f"(d[41]),"+f"(d[42]),"+f"(d[43]),"+f"(d[44]),"+f"(d[45]),"+f"(d[46]),"+f"(d[47]),"+f"(d[48]),"+f"(d[49]),"+f"(d[50]),"+f"(d[51]),"+f"(d[52]),"+f"(d[53]),"+f"(d[54]),"+f"(d[55]),"+f"(d[56]),"+f"(d[57]),"+f"(d[58]),"+f"(d[59]),"+f"(d[60]),"+f"(d[61]),"+f"(d[62]),"+f"(d[63]),"+f"(d[64]),"+f"(d[65]),"+f"(d[66]),"+f"(d[67]),"+f"(d[68]),"+f"(d[69]),"+f"(d[70]),"+f"(d[71]),"+f"(d[72]),"+f"(d[73]),"+f"(d[74]),"+f"(d[75]),"+f"(d[76]),"+f"(d[77]),"+f"(d[78]),"+f"(d[79]),"+f"(d[80]),"+f"(d[81]),"+f"(d[82]),"+f"(d[83]),"+f"(d[84]),"+f"(d[85]),"+f"(d[86]),"+f"(d[87]),"+f"(d[88]),"+f"(d[89]),"+f"(d[90]),"+f"(d[91]),"+f"(d[92]),"+f"(d[93]),"+f"(d[94]),"+f"(d[95]) : "r"(a[0]),"r"(a[1]),"r"(a[2]),"r"(a[3]),"l"(db),"r"(sc));
}
__device__ __forceinline__ void wg_ss192_11(float* d, uint64_t da, uint64_t db, int sc) {
  asm volatile("{.reg .pred p; setp.ne.b32 p, %98, 0; wgmma.mma_async.sync.aligned.m64n192k16.f32.bf16.bf16 {%0,%1,%2,%3,%4,%5,%6,%7,%8,%9,%10,%11,%12,%13,%14,%15,%16,%17,%18,%19,%20,%21,%22,%23,%24,%25,%26,%27,%28,%29,%30,%31,%32,%33,%34,%35,%36,%37,%38,%39,%40,%41,%42,%43,%44,%45,%46,%47,%48,%49,%50,%51,%52,%53,%54,%55,%56,%57,%58,%59,%60,%61,%62,%63,%64,%65,%66,%67,%68,%69,%70,%71,%72,%73,%74,%75,%76,%77,%78,%79,%80,%81,%82,%83,%84,%85,%86,%87,%88,%89,%90,%91,%92,%93,%94,%95}, %96, %97, p, 1, 1, 1, 1;}"
    : "+f"(d[0]),"+f"(d[1]),"+f"(d[2]),"+f"(d[3]),"+f"(d[4]),"+f"(d[5]),"+f"(d[6]),"+f"(d[7]),"+f"(d[8]),"+f"(d[9]),"+f"(d[10]),"+f"(d[11]),"+f"(d[12]),"+f"(d[13]),"+f"(d[14]),"+f"(d[15]),"+f"(d[16]),"+f"(d[17]),"+f"(d[18]),"+f"(d[19]),"+f"(d[20]),"+f"(d[21]),"+f"(d[22]),"+f"(d[23]),"+f"(d[24]),"+f"(d[25]),"+f"(d[26]),"+f"(d[27]),"+f"(d[28]),"+f"(d[29]),"+f"(d[30]),"+f"(d[31]),"+f"(d[32]),"+f"(d[33]),"+f"(d[34]),"+f"(d[35]),"+f"(d[36]),"+f"(d[37]),"+f"(d[38]),"+f"(d[39]),"+f"(d[40]),"+f"(d[41]),"+f"(d[42]),"+f"(d[43]),"+f"(d[44]),"+f"(d[45]),"+f"(d[46]),"+f"(d[47]),"+f"(d[48]),"+f"(d[49]),"+f"(d[50]),"+f"(d[51]),"+f"(d[52]),"+f"(d[53]),"+f"(d[54]),"+f"(d[55]),"+f"(d[56]),"+f"(d[57]),"+f"(d[58]),"+f"(d[59]),"+f"(d[60]),"+f"(d[61]),"+f"(d[62]),"+f"(d[63]),"+f"(d[64]),"+f"(d[65]),"+f"(d[66]),"+f"(d[67]),"+f"(d[68]),"+f"(d[69]),"+f"(d[70]),"+f"(d[71]),"+f"(d[72]),"+f"(d[73]),"+f"(d[74]),"+f"(d[75]),"+f"(d[76]),"+f"(d[77]),"+f"(d[78]),"+f"(d[79]),"+f"(d[80]),"+f"(d[81]),"+f"(d[82]),"+f"(d[83]),"+f"(d[84]),"+f"(d[85]),"+f"(d[86]),"+f"(d[87]),"+f"(d[88]),"+f"(d[89]),"+f"(d[90]),"+f"(d[91]),"+f"(d[92]),"+f"(d[93]),"+f"(d[94]),"+f"(d[95]) : "l"(da),"l"(db),"r"(sc));
}
__device__ __forceinline__ void wg_ss192_01(float* d, uint64_t da, uint64_t db, int sc) {
  asm volatile("{.reg .pred p; setp.ne.b32 p, %98, 0; wgmma.mma_async.sync.aligned.m64n192k16.f32.bf16.bf16 {%0,%1,%2,%3,%4,%5,%6,%7,%8,%9,%10,%11,%12,%13,%14,%15,%16,%17,%18,%19,%20,%21,%22,%23,%24,%25,%26,%27,%28,%29,%30,%31,%32,%33,%34,%35,%36,%37,%38,%39,%40,%41,%42,%43,%44,%45,%46,%47,%48,%49,%50,%51,%52,%53,%54,%55,%56,%57,%58,%59,%60,%61,%62,%63,%64,%65,%66,%67,%68,%69,%70,%71,%72,%73,%74,%75,%76,%77,%78,%79,%80,%81,%82,%83,%84,%85,%86,%87,%88,%89,%90,%91,%92,%93,%94,%95}, %96, %97, p, 1, 1, 0, 1;}"
    : "+f"(d[0]),"+f"(d[1]),"+f"(d[2]),"+f"(d[3]),"+f"(d[4]),"+f"(d[5]),"+f"(d[6]),"+f"(d[7]),"+f"(d[8]),"+f"(d[9]),"+f"(d[10]),"+f"(d[11]),"+f"(d[12]),"+f"(d[13]),"+f"(d[14]),"+f"(d[15]),"+f"(d[16]),"+f"(d[17]),"+f"(d[18]),"+f"(d[19]),"+f"(d[20]),"+f"(d[21]),"+f"(d[22]),"+f"(d[23]),"+f"(d[24]),"+f"(d[25]),"+f"(d[26]),"+f"(d[27]),"+f"(d[28]),"+f"(d[29]),"+f"(d[30]),"+f"(d[31]),"+f"(d[32]),"+f"(d[33]),"+f"(d[34]),"+f"(d[35]),"+f"(d[36]),"+f"(d[37]),"+f"(d[38]),"+f"(d[39]),"+f"(d[40]),"+f"(d[41]),"+f"(d[42]),"+f"(d[43]),"+f"(d[44]),"+f"(d[45]),"+f"(d[46]),"+f"(d[47]),"+f"(d[48]),"+f"(d[49]),"+f"(d[50]),"+f"(d[51]),"+f"(d[52]),"+f"(d[53]),"+f"(d[54]),"+f"(d[55]),"+f"(d[56]),"+f"(d[57]),"+f"(d[58]),"+f"(d[59]),"+f"(d[60]),"+f"(d[61]),"+f"(d[62]),"+f"(d[63]),"+f"(d[64]),"+f"(d[65]),"+f"(d[66]),"+f"(d[67]),"+f"(d[68]),"+f"(d[69]),"+f"(d[70]),"+f"(d[71]),"+f"(d[72]),"+f"(d[73]),"+f"(d[74]),"+f"(d[75]),"+f"(d[76]),"+f"(d[77]),"+f"(d[78]),"+f"(d[79]),"+f"(d[80]),"+f"(d[81]),"+f"(d[82]),"+f"(d[83]),"+f"(d[84]),"+f"(d[85]),"+f"(d[86]),"+f"(d[87]),"+f"(d[88]),"+f"(d[89]),"+f"(d[90]),"+f"(d[91]),"+f"(d[92]),"+f"(d[93]),"+f"(d[94]),"+f"(d[95]) : "l"(da),"l"(db),"r"(sc));
}
__device__ __forceinline__ void wg_ss160_01(float* d, uint64_t da, uint64_t db, int sc) {
  asm volatile("{.reg .pred p; setp.ne.b32 p, %82, 0; wgmma.mma_async.sync.aligned.m64n160k16.f32.bf16.bf16 {%0,%1,%2,%3,%4,%5,%6,%7,%8,%9,%10,%11,%12,%13,%14,%15,%16,%17,%18,%19,%20,%21,%22,%23,%24,%25,%26,%27,%28,%29,%30,%31,%32,%33,%34,%35,%36,%37,%38,%39,%40,%41,%42,%43,%44,%45,%46,%47,%48,%49,%50,%51,%52,%53,%54,%55,%56,%57,%58,%59,%60,%61,%62,%63,%64,%65,%66,%67,%68,%69,%70,%71,%72,%73,%74,%75,%76,%77,%78,%79}, %80, %81, p, 1, 1, 0, 1;}"
    : "+f"(d[0]),"+f"(d[1]),"+f"(d[2]),"+f"(d[3]),"+f"(d[4]),"+f"(d[5]),"+f"(d[6]),"+f"(d[7]),"+f"(d[8]),"+f"(d[9]),"+f"(d[10]),"+f"(d[11]),"+f"(d[12]),"+f"(d[13]),"+f"(d[14]),"+f"(d[15]),"+f"(d[16]),"+f"(d[17]),"+f"(d[18]),"+f"(d[19]),"+f"(d[20]),"+f"(d[21]),"+f"(d[22]),"+f"(d[23]),"+f"(d[24]),"+f"(d[25]),"+f"(d[26]),"+f"(d[27]),"+f"(d[28]),"+f"(d[29]),"+f"(d[30]),"+f"(d[31]),"+f"(d[32]),"+f"(d[33]),"+f"(d[34]),"+f"(d[35]),"+f"(d[36]),"+f"(d[37]),"+f"(d[38]),"+f"(d[39]),"+f"(d[40]),"+f"(d[41]),"+f"(d[42]),"+f"(d[43]),"+f"(d[44]),"+f"(d[45]),"+f"(d[46]),"+f"(d[47]),"+f"(d[48]),"+f"(d[49]),"+f"(d[50]),"+f"(d[51]),"+f"(d[52]),"+f"(d[53]),"+f"(d[54]),"+f"(d[55]),"+f"(d[56]),"+f"(d[57]),"+f"(d[58]),"+f"(d[59]),"+f"(d[60]),"+f"(d[61]),"+f"(d[62]),"+f"(d[63]),"+f"(d[64]),"+f"(d[65]),"+f"(d[66]),"+f"(d[67]),"+f"(d[68]),"+f"(d[69]),"+f"(d[70]),"+f"(d[71]),"+f"(d[72]),"+f"(d[73]),"+f"(d[74]),"+f"(d[75]),"+f"(d[76]),"+f"(d[77]),"+f"(d[78]),"+f"(d[79]) : "l"(da),"l"(db),"r"(sc));
}
__device__ __forceinline__ void wg_ss96_01(float* d, uint64_t da, uint64_t db, int sc) {
  asm volatile("{.reg .pred p; setp.ne.b32 p, %50, 0; wgmma.mma_async.sync.aligned.m64n96k16.f32.bf16.bf16 {%0,%1,%2,%3,%4,%5,%6,%7,%8,%9,%10,%11,%12,%13,%14,%15,%16,%17,%18,%19,%20,%21,%22,%23,%24,%25,%26,%27,%28,%29,%30,%31,%32,%33,%34,%35,%36,%37,%38,%39,%40,%41,%42,%43,%44,%45,%46,%47}, %48, %49, p, 1, 1, 0, 1;}"
    : "+f"(d[0]),"+f"(d[1]),"+f"(d[2]),"+f"(d[3]),"+f"(d[4]),"+f"(d[5]),"+f"(d[6]),"+f"(d[7]),"+f"(d[8]),"+f"(d[9]),"+f"(d[10]),"+f"(d[11]),"+f"(d[12]),"+f"(d[13]),"+f"(d[14]),"+f"(d[15]),"+f"(d[16]),"+f"(d[17]),"+f"(d[18]),"+f"(d[19]),"+f"(d[20]),"+f"(d[21]),"+f"(d[22]),"+f"(d[23]),"+f"(d[24]),"+f"(d[25]),"+f"(d[26]),"+f"(d[27]),"+f"(d[28]),"+f"(d[29]),"+f"(d[30]),"+f"(d[31]),"+f"(d[32]),"+f"(d[33]),"+f"(d[34]),"+f"(d[35]),"+f"(d[36]),"+f"(d[37]),"+f"(d[38]),"+f"(d[39]),"+f"(d[40]),"+f"(d[41]),"+f"(d[42]),"+f"(d[43]),"+f"(d[44]),"+f"(d[45]),"+f"(d[46]),"+f"(d[47]) : "l"(da),"l"(db),"r"(sc));
}
__device__ __forceinline__ void wg_ss64_01(float* d, uint64_t da, uint64_t db, int sc) {
  asm volatile("{.reg .pred p; setp.ne.b32 p, %34, 0; wgmma.mma_async.sync.aligned.m64n64k16.f32.bf16.bf16 {%0,%1,%2,%3,%4,%5,%6,%7,%8,%9,%10,%11,%12,%13,%14,%15,%16,%17,%18,%19,%20,%21,%22,%23,%24,%25,%26,%27,%28,%29,%30,%31}, %32, %33, p, 1, 1, 0, 1;}"
    : "+f"(d[0]),"+f"(d[1]),"+f"(d[2]),"+f"(d[3]),"+f"(d[4]),"+f"(d[5]),"+f"(d[6]),"+f"(d[7]),"+f"(d[8]),"+f"(d[9]),"+f"(d[10]),"+f"(d[11]),"+f"(d[12]),"+f"(d[13]),"+f"(d[14]),"+f"(d[15]),"+f"(d[16]),"+f"(d[17]),"+f"(d[18]),"+f"(d[19]),"+f"(d[20]),"+f"(d[21]),"+f"(d[22]),"+f"(d[23]),"+f"(d[24]),"+f"(d[25]),"+f"(d[26]),"+f"(d[27]),"+f"(d[28]),"+f"(d[29]),"+f"(d[30]),"+f"(d[31]) : "l"(da),"l"(db),"r"(sc));
}
__device__ __forceinline__ void wg_rs160_1(float* d, const uint32_t* a, uint64_t db, int sc) {
  asm volatile("{.reg .pred p; setp.ne.b32 p, %85, 0; wgmma.mma_async.sync.aligned.m64n160k16.f32.bf16.bf16 {%0,%1,%2,%3,%4,%5,%6,%7,%8,%9,%10,%11,%12,%13,%14,%15,%16,%17,%18,%19,%20,%21,%22,%23,%24,%25,%26,%27,%28,%29,%30,%31,%32,%33,%34,%35,%36,%37,%38,%39,%40,%41,%42,%43,%44,%45,%46,%47,%48,%49,%50,%51,%52,%53,%54,%55,%56,%57,%58,%59,%60,%61,%62,%63,%64,%65,%66,%67,%68,%69,%70,%71,%72,%73,%74,%75,%76,%77,%78,%79}, {%80,%81,%82,%83}, %84, p, 1, 1, 1;}"
    : "+f"(d[0]),"+f"(d[1]),"+f"(d[2]),"+f"(d[3]),"+f"(d[4]),"+f"(d[5]),"+f"(d[6]),"+f"(d[7]),"+f"(d[8]),"+f"(d[9]),"+f"(d[10]),"+f"(d[11]),"+f"(d[12]),"+f"(d[13]),"+f"(d[14]),"+f"(d[15]),"+f"(d[16]),"+f"(d[17]),"+f"(d[18]),"+f"(d[19]),"+f"(d[20]),"+f"(d[21]),"+f"(d[22]),"+f"(d[23]),"+f"(d[24]),"+f"(d[25]),"+f"(d[26]),"+f"(d[27]),"+f"(d[28]),"+f"(d[29]),"+f"(d[30]),"+f"(d[31]),"+f"(d[32]),"+f"(d[33]),"+f"(d[34]),"+f"(d[35]),"+f"(d[36]),"+f"(d[37]),"+f"(d[38]),"+f"(d[39]),"+f"(d[40]),"+f"(d[41]),"+f"(d[42]),"+f"(d[43]),"+f"(d[44]),"+f"(d[45]),"+f"(d[46]),"+f"(d[47]),"+f"(d[48]),"+f"(d[49]),"+f"(d[50]),"+f"(d[51]),"+f"(d[52]),"+f"(d[53]),"+f"(d[54]),"+f"(d[55]),"+f"(d[56]),"+f"(d[57]),"+f"(d[58]),"+f"(d[59]),"+f"(d[60]),"+f"(d[61]),"+f"(d[62]),"+f"(d[63]),"+f"(d[64]),"+f"(d[65]),"+f"(d[66]),"+f"(d[67]),"+f"(d[68]),"+f"(d[69]),"+f"(d[70]),"+f"(d[71]),"+f"(d[72]),"+f"(d[73]),"+f"(d[74]),"+f"(d[75]),"+f"(d[76]),"+f"(d[77]),"+f"(d[78]),"+f"(d[79]) : "r"(a[0]),"r"(a[1]),"r"(a[2]),"r"(a[3]),"l"(db),"r"(sc));
}
__device__ __forceinline__ void wg_ss8_10(float* d, uint64_t da, uint64_t db, int sc) {
  asm volatile("{.reg .pred p; setp.ne.b32 p, %6, 0; wgmma.mma_async.sync.aligned.m64n8k16.f32.bf16.bf16 {%0,%1,%2,%3}, %4, %5, p, 1, 1, 1, 0;}"
    : "+f"(d[0]),"+f"(d[1]),"+f"(d[2]),"+f"(d[3]) : "l"(da),"l"(db),"r"(sc));
}

constexpr uint32_t DB = 1024;
constexpr int WSLOT = 24576, NW = 6, ASLOT = 8192, ARING = 4 * ASLOT;
constexpr int OFF_A = NW * WSLOT;
constexpr int OFF_PB = OFF_A + 2 * ARING;
constexpr int OFF_CV = OFF_PB + 16384, OFF_ST = OFF_CV + 768, OFF_TS = OFF_ST + 256, OFF_MODR = OFF_TS + 512, OFF_BAR = OFF_MODR + 80, SMEM_BYTES = OFF_BAR + 1168;
constexpr int OFF_BX = OFF_PB, OFF_AX = OFF_BX + 12288, OFF_RT = OFF_AX + 2048, OFF_GB = OFF_RT + 512, OFF_CO = OFF_CV;
constexpr int OFF_UV = 5 * WSLOT, OFF_UVE = OFF_PB, OFF_SX = OFF_A + ARING + 3 * ASLOT, OFF_X1 = 2 * WSLOT + ASLOT, OFF_XCH = WSLOT;
constexpr int OFF_Q = 0, KV_V = 4096, KV_H = 8192, F_E = 16, F_O = 4176, OFF_TAP = 168576, OFF_MR = OFF_A + 3 * ASLOT;
constexpr uint64_t pk5(int a, int b, int c, int d, int e) { return (uint64_t)(a / 128) | (uint64_t)(b / 128) << 12 | (uint64_t)(c / 128) << 24 | (uint64_t)(d / 128) << 36 | (uint64_t)(e / 128) << 48; }
constexpr uint64_t T_KV = pk5(20480, 30720, 40960, 180224, 190464), T_F = pk5(51200, 59648, 200192, 147456, 155904), T_X = pk5(208512, 164352, 68096, 208512, 164352),
                   T_P = pk5(131072, OFF_PB, 114688, 131072, OFF_PB);
__host__ __device__ __forceinline__ uint32_t tab(uint64_t t, int c) { return ((uint32_t)(t >> (12 * c)) & 0xFFF) << 7; }
enum { B_KV = 0, B_FRAW = 5, B_Q = 10, B_XR = 16, B_MR = B_XR + 5, B_QTOK, B_ST1, B_MODR, B_S3 = B_MODR + 5, B_FIN, B_FL = 32, B_PFULL = B_FL + 5, B_PEMPTY = B_PFULL + 5, B_FRDY = B_PEMPTY + 5,
       B_EXT = B_FRDY + 5, B_QTD, B_LAG, B_GB, B_UVD, B_TURN, B_FULL = 60, B_RETRY = B_FULL + 33, B_XFREE = B_RETRY + 9, B_BX, B_UVB, B_UVE, B_SX, B_EMPTY = 109 };
static_assert(B_MODR + 5 <= B_FL && B_UVD < B_FULL && B_SX + 2 == B_EMPTY - 1, "barrier groups");
#define BAR(i) (base + OFF_BAR + 8 * (i))

constexpr int NE = 18;
struct Maps { CUtensorMap km, v, q, kh, tap, wm, w1s, w3s, xs, w1, w3, w1e, w3e, x1s, x1b, w2a, w2b, outa, outb; };
struct Ptrs { const bf16 *ssmk, *c, *ssmd; Scratch* g; uint64_t prog, cprog[2]; int boff, te, pe, th, th2, zero; uint32_t xd, aw, cn, c0, fin, turn, mr2, m3, seq; float one; uint2 sched[NE]; uint32_t wdep[20], wt[32]; uint2 w2t[12]; int hid[3][9]; };

#define REGION_IDS int tid, lane, bid; \
  asm volatile("mov.u32 %0, %%tid.x;" : "=r"(tid)); asm volatile("mov.u32 %0, %%laneid;" : "=r"(lane)); asm volatile("mov.u32 %0, %%ctaid.x;" : "=r"(bid)); \
  const int i0 = tid & 127; (void)i0; (void)lane; (void)bid

__device__ __forceinline__ void ffn_role(int& h, int& j, int& r) {
  uint32_t b;
  asm volatile("mov.u32 %0, %%ctaid.x;" : "=r"(b));
  const uint32_t c = b >> 1, q = (c - 36) * 37 >> 8, e = c - 36 - 7 * q;
  h = b & 1;
  const uint32_t k = c < 4 ? 0 : c < 36 ? (c - 4) & 7 : e + 1, p = c < 4 ? c : c < 36 ? (c - 4) >> 3 : q, up = c - 4 >= 32;
  j = 2 * (k & 1) + up;
  r = 2 * (k & 6) + p;
}
__device__ __forceinline__ int fslice(int j, int e) { return e == 2 ? j ^ 1 : (~j & 2) + e; }
__device__ __forceinline__ int mod_ch(int p) { return p < 40 ? (p >> 3) * 128 + (p & 1) * 64 : 64 * (p < 50 ? p - 40 : p - 50); }
__device__ __forceinline__ int mod_col(int p) { return mod_ch(p) + 640 * (p < 40 ? 0x4210 >> (2 * (p & 6)) & 7 : p < 50 ? 3 : 5); }
__device__ __forceinline__ uint32_t mod_sum(uint2 v) { return pack_bf16(0.f, __uint_as_float(v.x) + __uint_as_float(v.y)); }

constexpr int NT = 3, LAG2 = 29, MG = 4, NP = 1, P0 = 0, ST = 1, NB = 0, PA = 2, O3 = 0, O0 = 1, OS = 2;
__device__ __forceinline__ int w_block(int up, int m) { return m == 1 ? 2 + 3 * up : 3 * (m >> 1) + up; }
__host__ __device__ constexpr int w2_at(int v) { return 8192 * (v ? 0x0613030008ull >> v % 5 * 8 & 255 : 15); }
__host__ __device__ constexpr int w2_step(int v) { return 8192 * (v ? 0x32113 >> v % 5 * 4 & 15 : 1); }
__host__ __device__ constexpr int hid_at(int m, int g) { return 8192 * ((g ? 0x0D07110F1816ull : 0x0A19101A1412ull) >> m % 6 * 8 & 255); }
__host__ __device__ constexpr uint32_t w2_desc(int v) { return (DB + w2_at(v)) >> 4 | w2_step(v) << 12; }
__device__ __forceinline__ int next_slot(int s) { return s >= 4 * WSLOT ? 0 : s + WSLOT; }

template <int U> __device__ __forceinline__ void cstep(float* acc, const uint32_t* A, uint64_t db) {
  const uint32_t* a = A + 4 * U;
  const uint64_t d = db + 16 * U;
  if (U == 4) { wg_rs64_0(acc + 96, A, db + 192, 0); wg_rs48_0(acc + 96, A + 4, db + 208, 1); wg_rs32_0(acc + 96, A + 8, db + 224, 1); wg_rs16_0(acc + 96, A + 12, db + 240, 1); }
  if (U <= 4) wg_rs192_0(acc, a, d, U);
  if (U == 5) wg_rs176_0(acc, a, d, 1);
  if (U == 6) wg_rs160_0(acc, a, d, 1);
  if (U == 7) wg_rs144_0(acc, a, d, 1);
  if (U == 8) wg_rs128_0(acc, a, d, 1);
  if (U == 9) wg_rs112_0(acc, a, d, 1);
  if (U == 10) wg_rs96_0(acc, a, d, 1);
  if (U == 11) wg_rs80_0(acc, a, d, 1);
  if (U == 12) wg_rs64_0(acc, a, d, 1);
  if (U == 13) wg_rs48_0(acc, a, d, 1);
  if (U == 14) wg_rs32_0(acc, a, d, 1);
  if (U == 15) wg_rs16_0(acc, a, d, 1);
}
template <int U0, int U1> __device__ __forceinline__ void csteps(float* acc, const uint32_t* A, uint64_t db) {
  cstep<U0>(acc, A, db);
  if constexpr (U0 > U1) csteps<U0 - 1, U1>(acc, A, db);
}
template <int U0, int U1> __device__ __forceinline__ void cload(uint32_t* A, uint32_t fa) {
  asm volatile("{ld.shared.b32 %0, [%4+%5]; ld.shared.b32 %1, [%4+%5+128]; ld.shared.b32 %2, [%4+%5+16]; ld.shared.b32 %3, [%4+%5+144];}"
               : "=r"(A[4 * U0]), "=r"(A[4 * U0 + 1]), "=r"(A[4 * U0 + 2]), "=r"(A[4 * U0 + 3]) : "r"(fa), "n"(256 * U0) : "memory");
  if constexpr (U0 > U1) cload<U0 - 1, U1>(A, fa);
}

__device__ __forceinline__ uint2 c_load(const bf16* c) {
  REGION_IDS;
  return make_uint2(ldg32(c + 320 * (bid & 1) + 2 * i0), ldg32(c + 320 * (bid & 1) + 256 + 2 * lane));
}
__device__ __forceinline__ void silu_vector(uint2 c, uint32_t base) {
  REGION_IDS;
  sts32(base + OFF_CV + 4 * i0, pack_bf16(silu_f(bf_lo(c.x)), silu_f(bf_hi(c.x))));
  sts32(base + OFF_CV + 512 + 4 * lane, pack_bf16(silu_f(bf_lo(c.y)), silu_f(bf_hi(c.y))));
  fence_async_smem();
}

__device__ __forceinline__ void mod_poll(Scratch* G, uint32_t base, int c, int n, uint32_t epoch) {
  REGION_IDS;
  const int e = 4 * c + (lane & (4 * n - 1));
  uint2 m;
  int it = 0;
#pragma unroll 1
  do m = ld_relaxed64(&G->modc[bid][8 + e]); while (__any_sync(~0u, ((m.x ^ epoch) | (m.y ^ epoch)) & 1) && ++it < SPIN_LIMIT);
  sts32(base + OFF_MODR + 4 * e, __byte_perm(badd2(mod_sum(m), (lane & 1) * 0x3F800000u), 0, 0x3232));
  __syncwarp();
  if (elect()) { mbar_arrive(BAR(B_MODR + c)); if (n > 1) mbar_arrive(BAR(B_MODR + c + 1)); }
}
__device__ __forceinline__ void row_stats(Scratch* G, uint32_t base, uint32_t epoch) {
  REGION_IDS;
  mbar_wait_cluster(BAR(B_ST1));
  if (lane < 8) red_hint(G->hint[5][lane]);
  const uint2 x = lds64(base + OFF_ST + 8 * (lane & 15)), y = lds64(base + OFF_ST + 128 + 8 * (lane & 15));
  float m, sd;
  ln_final(__uint_as_float(x.x) + __uint_as_float(y.x), __uint_as_float(x.y) + __uint_as_float(y.y), m, sd);
  sd = rbf(rcpf(sd));
  const uint32_t mr = pack_bf16(sd, -rbf(m) * sd), tg = lane & 7 ? 0 : lane & 8 ? 1 : 0x8000;
  const uint32_t o = __byte_perm(__shfl_sync(~0u, mr, 2 * lane & 14), __shfl_sync(~0u, mr, (2 * lane & 14) + 1), (lane & 8) ? 0x7632 : 0x5410);
  if (lane < 16) st_relaxed32(&G->st1[lane >> 3][8 * bid + (lane & 7)], (o & ~tg) | ((epoch & 1) * tg));
  if (elect()) mbar_arrive(BAR(B_FIN));
}
template <int B, int NEXT> __device__ __forceinline__ void strip(Scratch* G, const CUtensorMap* map, uint32_t base, int c, uint32_t epoch, uint32_t& ph, uint32_t& pre, float4& s) {
  REGION_IDS;
  int h, j, r, it = 0;
  ffn_role(h, j, r);
  const uint32_t buf = base + OFF_SX + 4096 * B, a = buf + 32 * lane;
  if (c < 2) { mbar_wait(BAR(B_FULL + 4 * c + (j & 2))); pre = 64 * epoch; }
#pragma unroll 1
  while (__any_sync(~0u, pre != 64 * epoch) && ++it < SPIN_LIMIT) pre = ld_relaxed32(G->xsh[c][(r & 6) + (j >> 1)]);
#pragma unroll 1
  for (it = 0; it < SPIN_LIMIT; it++) {
    if (elect()) { mbar_expect_tx(BAR(B_SX + B), 4096); tma2d(buf, map, 128 * r + 64 * h, D_ * (epoch & 1) + 128 * c + 32 * j, BAR(B_SX + B)); }
    mbar_wait(BAR(B_SX + B), ph);
    ph ^= 1;
    if (__all_sync(~0u, min(min(lds32(a), lds32(a + 1024)), min(lds32(a + 2048), lds32(a + 3072))))) break;
  }
  pre = 0;
  if ((c == NEXT - 1 || c == NEXT - 2) && c >= 1) pre = ld_relaxed32(G->xsh[c + 1][(r & 6) + (j >> 1)]);
#pragma unroll 1
  for (uint32_t o = buf + 4 * lane; o < buf + 4096; o += 1024) {
    uint32_t x[8];
#pragma unroll
    for (int i = 0; i < 8; i++) x[i] = lds32(o + 128 * i);
#pragma unroll
    for (int i = 0; i < 8; i++) { const float lo = bf_lo(x[i]), hi = bf_hi(x[i]); s.x += lo; s.y = fmaf(lo, lo, s.y); s.z += hi; s.w = fmaf(hi, hi, s.w); }
  }
}
__device__ __forceinline__ void planes(uint32_t a, uint4& y) {
  uint4 z = lds128(a + 4096);
  y.x = badd2(y.x, z.x); y.y = badd2(y.y, z.y); y.z = badd2(y.z, z.z); y.w = badd2(y.w, z.w);
  z = lds128(a + 8192);
  const uint4 m = lds128(a + 12288);
  y.x = badd2(y.x, badd2(z.x, m.x)); y.y = badd2(y.y, badd2(z.y, m.y)); y.z = badd2(y.z, badd2(z.z, m.z)); y.w = badd2(y.w, badd2(z.w, m.w));
}
__device__ __forceinline__ void mr_poll(Scratch* G, uint32_t base, uint32_t epoch) {
  int it = 0;
#pragma unroll 1
  while (__any_sync(~0u, ld_relaxed32(G->hint[5][4 * (blockIdx.x >> 6) + (blockIdx.x >> 3 & 3)]) != epoch << 7) && ++it < SPIN_LIMIT);
  if (elect()) { mbar_expect_tx(BAR(B_MR), 8192); bulk_load(base + OFF_MR, G->st1, 8192, BAR(B_MR)); mbar_arrive(BAR(B_QTOK)); }
}

__global__ void __cluster_dims__(2, 1, 1) __launch_bounds__(512, 1) k_fused(const __grid_constant__ Ptrs P, const __grid_constant__ Maps maps) {
  Scratch* const G = P.g;
  extern __shared__ __align__(1024) uint8_t smem_raw[];
  const uint32_t t_start = clock();
  const uint32_t base = __shfl_sync(~0u, smem_u32(smem_raw), 0);
  uint32_t t_iss = 0;
  if (threadIdx.x < 32 && blockIdx.x < 128) {
    mbar_init<1>(BAR(0), 1);
    if (elect()) {
      const int c0 = 64 * (blockIdx.x & 1), c1 = 2 * (blockIdx.x & 126);
      mbar_expect_tx(BAR(B_KV), 12288);
      tma3d(base + tab(T_KV, 0), &maps.km, c0, c1, 0, BAR(B_KV));
      tma3d(base + tab(T_KV, 0) + KV_V, &maps.v, c0, c1, 0, BAR(B_KV));
      tma3d(base + tab(T_KV, 0) + KV_H, &maps.kh, c0, c1 - 1, 5, BAR(B_KV));
      tma3d(base + OFF_TAP, &maps.tap, 0, blockIdx.x & 1, 0, BAR(B_KV));
    }
    if (P.boff) mbar_wait(BAR(0));
  }
  if ((base & 0xFFFFFFu) != DB) __trap();
  const int wid = __shfl_sync(~0u, threadIdx.x >> 5, 0), wg = wid >> 2, w = wid & 3;
  if (blockIdx.x + P.boff >= 128) {
    REGION_IDS;
    constexpr int nu = 30;
    auto tile = [&](int n) { return 2 * n + (blockIdx.x >> 1 & 1); };
    auto fetch = [&](int n, int b) {
      if (elect()) {
        mbar_expect_tx(BAR(n), 40960);
#pragma unroll
        for (int k = 0; k < 5; k++) tma3d(base + 40960 * b + 8192 * k, &maps.wm, mod_col(tile(n)), 320 * (blockIdx.x & 1) + 64 * k, 0, BAR(n));
      }
    };
    if (P.boff) __syncthreads();
    if (wid == 12) {
      mbar_init<4>(BAR(0), 1);
#pragma unroll 1
      for (int n = 0; n < 4; n++) fetch(n, n);
      mbar_init<26>(BAR(4), 1);
      mbar_init<60>(BAR(32), 4);
    }
    const uint32_t par = ~ld_relaxed32(G->hint[7][0]) >> 7 & 1;
    silu_vector(c_load(P.c), base);
    __syncthreads();
    if (wid == 12) {
      wait_clock(t_start + P.th);
#pragma unroll 1
      for (int n = 4, b = 4; n < nu; n++) {
        if (n >= 5) mbar_wait(BAR(27 + n));
        if (n == 8) wait_clock(t_start + P.th2);
        fetch(n, b);
        b = b == 4 ? 0 : b + 1;
      }
    } else if (wg < 2) {
      uint32_t cv[40];
#pragma unroll
      for (int k = 0; k < 40; k++) cv[k] = lds32(base + OFF_CV + 16 * k + 4 * (lane & 3));
      const uint32_t a0 = base + 128 * ((lane & 7) + (lane >> 4) * 8) + (((2 * w + (lane >> 3 & 1)) ^ (lane & 7)) << 4);
#pragma unroll 1
      for (int n = wg; n < nu; n += 2) {
        float d[16] = {};
        mbar_wait(BAR(n));
#pragma unroll
        for (int k0 = 0; k0 < 20; k0 += 10) {
          uint32_t a[40];
#pragma unroll
          for (int k = 0; k < 10; k++) ldmatrix_x4_t(a + 4 * k, a0 + 40960 * (n % 5) + 2048 * (k0 + k));
#pragma unroll
          for (int k = 0; k < 10; k++)
            asm("mma.sync.aligned.m16n8k16.row.col.f32.bf16.bf16.f32 {%0,%1,%2,%3}, {%4,%5,%6,%7}, {%8,%9}, {%0,%1,%2,%3};"
                : "+f"(d[4 * (k & 3)]), "+f"(d[4 * (k & 3) + 1]), "+f"(d[4 * (k & 3) + 2]), "+f"(d[4 * (k & 3) + 3])
                : "r"(a[4 * k]), "r"(a[4 * k + 1]), "r"(a[4 * k + 2]), "r"(a[4 * k + 3]), "r"(cv[2 * (k0 + k)]), "r"(cv[2 * (k0 + k) + 1]));
        }
        arrive1(BAR(32 + n));
        if (!(lane & 3)) {
          sts32(base + 204800 + 256 * n + 64 * w + lane, __float_as_uint(d[0] + d[4] + (d[8] + d[12])));
          sts32(base + 204800 + 256 * n + 64 * w + lane + 32, __float_as_uint(d[2] + d[6] + (d[10] + d[14])));
        }
        arrive1(BAR(62 + n));
      }
    } else if (wg == 2) {
#pragma unroll 1
      for (int n = w; n < nu; n += 4) {
        const int t = tile(n), ch = mod_ch(t) + lane;
        uint32_t* q = (uint32_t*)(t < 40 ? &G->modc[ch & 127][8 + (t >> 1)] : &G->modv[t >= 50][ch]) + (bid & 1);
        mbar_wait(BAR(62 + n));
        const uint32_t x = (lds32(base + 204800 + 256 * n + 4 * lane) & ~1u) | par, y = (lds32(base + 204928 + 256 * n + 4 * lane) & ~1u) | par;
        publish(q, x);
        publish(q + (t < 40 ? 2048 : 64), y);
        if (t < 40 && (t & 6) == 6) {
          q = (uint32_t*)&G->modv[2][ch] + (bid & 1);
          publish(q, x);
          publish(q + 64, y);
        }
      }
    }
    return;
  }
  if (wid < 15) mbar_init<4>(BAR(4 * wid + (wid == 0)), wid < 8 ? 1 : 4);
  asm volatile("fence.mbarrier_init.release.cluster; bar.sync 0, 512;" ::: "memory");
  asm volatile("barrier.cluster.arrive.relaxed.aligned;" ::: "memory");
  if (wid == 4) {
    const int c0 = 64 * (blockIdx.x & 1), c1 = 2 * (blockIdx.x & 126);
    wait_clock(t_start + P.te);
    if (elect()) { tma3d(base + tab(T_KV, 1), &maps.km, 128 + c0, c1, 0, BAR(B_KV + 1)); tma3d(base + tab(T_KV, 1) + KV_H, &maps.kh, 128 + c0, c1 - 1, 5, BAR(B_KV + 1)); }
    wait_clock(t_start + P.te + P.pe);
    if (elect()) tma3d(base + tab(T_KV, 1) + KV_V, &maps.v, 128 + c0, c1, 0, BAR(B_KV + 1));
    wait_clock(t_start + P.te + 2 * P.pe);
    if (elect()) bulk_load(base + tab(T_F, 0) + F_E, P.ssmk + blockIdx.x * S_, 4096, BAR(B_FRAW));
    wait_clock(t_start + P.te + 3 * P.pe);
    if (elect()) tma3d(base + OFF_Q, &maps.q, c0, c1, 0, BAR(B_Q));
  }
#define LAUNCHES const uint32_t launches = ld_relaxed32(G->hint[7][blockIdx.x >> 4])
#define EPOCH ((__shfl_sync(~0u, launches, 0) >> 7) + 1)
  if (wg == 3) {
    asm volatile("setmaxnreg.dec.sync.aligned.u32 24;");
    if (w == 1) {
      {
        LAUNCHES;
        REGION_IDS;
        const int c1 = 2 * (bid & 126);
#pragma unroll 1
        for (int e = 4; e < NE; e++) {
          const uint2 x = P.sched[e];
          const uint32_t kind = x.x >> 16 & 15, ch = x.x >> 13 & 0x380, dst = base + (x.y & 0x3FFFF), b = BAR(x.y >> 18);
          wait_clock(t_start + (x.x & 0xFFFF));
          if (kind < 3 && elect()) tma3d(dst, &maps.km + kind, ch + 64 * (bid & 1), c1, 0, b);
          if (kind == 0 && elect()) tma3d(dst + KV_H, &maps.kh, ch + 64 * (bid & 1), c1 - 1, 5, b);
          if (kind == 3 && elect()) bulk_load(dst, P.ssmk + (ch + bid) * S_, 4096, b);
        }
        if (P.mr2 == 2) mr_poll(G, base, EPOCH);
        mod_poll(G, base, 0, 1, EPOCH);
      }
      cluster_wait();
      int h, j, r;
      ffn_role(h, j, r);
      mbar_wait(BAR(B_QTD));
      mbar_wait(BAR(B_FL));
#pragma unroll 1
      for (int u = 0; u < 20; u++) {
        const uint32_t x = P.wdep[u], s = base + (x & ~8191u);
        wait_clock(t_start + P.wt[u]);
        mbar_wait(BAR(opaque(x & 255)));
        if (elect()) {
          mbar_expect_tx(BAR(B_FULL + u), WSLOT + 4 * (x & 4096));
#pragma unroll
          for (int k = 0; k < 6; k++) tma3d(s + 4096 * w_block(k & 1, k >> 1), &maps.w1s + (k & 1), 0, 32 * u, 3 * (4 * h + j) + (k >> 1), BAR(B_FULL + u));
        }
      }
#pragma unroll 1
      for (int v = 0; v < 12; v++) {
        const int q = v * 11 >> 5, e = v - 3 * q, k32 = 24 * h + (q ? 6 * fslice(j, e) + 2 * q - 2 : 6 * j + 2 * e);
        const uint2 x = P.w2t[v];
        wait_clock(t_start + P.wt[20 + v]);
        mbar_wait(BAR(x.y));
        if (elect()) {
          mbar_expect_tx(BAR(B_FULL + 20 + v), q ? WSLOT + 2 * ASLOT : WSLOT);
#pragma unroll
          for (int k = 0; k < 3; k++) tma5d(base - DB + 16 * ((x.x & 0xFFFF) + k * (x.x >> 16)), &maps.w2a + (q > 0), k < 2 ? 128 * j + 64 * k : 512 + 32 * (j & 2), k32, BAR(B_FULL + 20 + v));
        }
      }
    } else if (w == 0) {
      LAUNCHES;
      uint32_t epoch;
      {
        REGION_IDS;
        const unsigned* hp = G->hint[0][4 * (bid >> 6) + (bid >> 3 & 3)];
        uint32_t v = ld_relaxed32(hp + 256 * min(lane, 5));
        if (lane < 3) sts128(base + tab(T_X, lane) + 4096, 0, 0, 0, 0);
        if (lane && lane < B_Q + 5) mbar_expect_tx(BAR(lane), lane < B_FRAW ? 9728 : 4096);
        epoch = EPOCH;
        fence_async_smem();
        const uint32_t rdy = __ballot_sync(~0u, v == epoch << 6);
        uint32_t nx = 0, nm = 0;
#pragma unroll 1
        for (uint32_t seq = P.seq; seq; seq >>= 2) {
          int it = 0;
          if (seq & 1) {
            if (!(seq & 2)) mod_poll(G, base, nm, 1 + (seq == 13), epoch);
            nm++;
          } else if (seq & 2) {
            mr_poll(G, base, epoch);
          } else {
            if (!(rdy >> nx & 1)) {
#pragma unroll 1
              while (__any_sync(~0u, ld_relaxed32(hp + 256 * nx) != epoch << 6) && ++it < SPIN_LIMIT);
            }
            wait_clock(clock() + (P.xd >> 4 * nx & 15) * 64);
            if (nx >= 3) mbar_wait(BAR(B_PFULL - 3 + nx));
            if (elect()) { mbar_expect_tx(BAR(B_XR + nx), 4096); bulk_load(base + tab(T_X, nx), G->xr + (128 * nx + bid) * 256, 4096, BAR(B_XR + nx)); }
            nx++;
          }
        }
      }
      REGION_IDS;
      int h, j, r;
      ffn_role(h, j, r);
      mbar_wait(BAR(B_PFULL + 3));
      {
        float4 s = {};
        uint32_t ph = 0, pre = 0;
#pragma unroll 1
        for (int c = 2; c < 4; c++) strip<1, 3>(G, &maps.x1s, base, c, epoch, ph, pre, s);
        __syncwarp();
        sts128(base + OFF_SX + 4096 + 16 * lane, __float_as_uint(s.x), __float_as_uint(s.y), __float_as_uint(s.z), __float_as_uint(s.w));
        arrive1(BAR(B_S3));
      }
      ffn_role(h, j, r);
      cluster_wait();
      mbar_wait(BAR(B_UVD));
      asm volatile("fence.acq_rel.gpu;" ::: "memory");
      if (lane < 8) red_hint(G->hint[7][lane]);
      unsigned x;
      int it = 0;
#pragma unroll 1
      do { asm volatile("ld.acquire.gpu.global.u32 %0, [%1];" : "=r"(x) : "l"(G->hint[7][bid >> 4]) : "memory"); } while (__any_sync(~0u, x != 128 * epoch) && ++it < SPIN_LIMIT);
      fence_async_all();
      const int ch = D_ * (epoch & 1);
      mbar_wait(BAR(B_EXT));
      mbar_wait(BAR(B_EMPTY + 18));
      if (elect()) {
        mbar_expect_tx(BAR(B_FULL + 32), 20480);
#pragma unroll
        for (int k = 0; k < 4; k++) tma2d(base + (k < 3 ? OFF_X1 + k * WSLOT : OFF_SX), &maps.x1b, 128 * r + 64 * h, ch + 128 * j + 32 * (k ^ (j & 1)), BAR(B_FULL + 32));
        tma2d(base + OFF_SX + 4096, &maps.x1b, 128 * r + 64 * h, ch + 512 + 32 * j, BAR(B_FULL + 32));
        mbar_expect_tx(BAR(B_FULL), 8192); mbar_expect_tx(BAR(B_FULL + 1), 8192); mbar_expect_tx(BAR(B_FULL + 2), 4096);
      }
      mbar_wait(BAR(B_EMPTY + 27));
      if (elect()) mbar_arrive_remote(mapa(BAR(B_XFREE), h ^ 1));
    } else {
      LAUNCHES;
      uint32_t epoch;
      {
        REGION_IDS;
        uint32_t dv;
        asm volatile("ld.global.nc.u16 %0, [%1];" : "=r"(dv) : "l"(P.ssmd + 128 * (lane & 7) % D_ + bid));
        if (lane < 5) sts128(base + tab(T_F, lane) + (w & 1) * (F_O - 16), 0, 0, 0, 0);
        epoch = EPOCH;
        __syncwarp();
#pragma unroll 1
        for (int c = 0; c < 5; c++) {
          const float d = i0 == 64 ? bf_lo(dv) : 0.f;
          dv = __shfl_down_sync(~0u, dv, 1);
          const uint32_t a = base + tab(T_F, c) + 16 * (i0 - 64);
          mbar_wait(BAR(B_FRAW + c));
#pragma unroll
          for (int k = 0; k < 4; k++) {
            uint4 x = lds128(a + F_E + 1024 * k);
            const uint32_t pv = lds32(a + F_E - 4 + 1024 * k);
            if (k == 0) { x.x = pack_bf16(bf_lo(x.x) + d, bf_hi(x.x)); sts32(a + F_E, x.x); }
            sts128(a + F_O + 1024 * k, __byte_perm(pv, x.x, 0x5432), __byte_perm(x.x, x.y, 0x5432), __byte_perm(x.y, x.z, 0x5432), __byte_perm(x.z, x.w, 0x5432));
          }
          __syncwarp();
          if (elect()) mbar_arrive2(BAR(B_FRDY + c));
          if (c == 0 && w == P.fin) row_stats(G, base, epoch);
        }
      }
      REGION_IDS;
      int h, j, r;
      ffn_role(h, j, r);
      cluster_wait();
      if (w == 2) {
        uint32_t rdy = 0, s = 0;
        mbar_wait(BAR(B_QTD));
        mbar_wait(BAR(B_FL + 2));
#pragma unroll 1
        for (int n = 0; n < 10; n++) {
          if (n == P.cn) {
            mbar_wait(BAR(B_PEMPTY + 3));
            if (elect()) {
              tma3d(base + OFF_UV, &maps.w1 + (r & 1), 0, 40 * (r & 14), 3 * (4 * h + j), BAR(B_UVB));
              tma3d(base + OFF_UV + 12288, &maps.w1 + (r & 1), 0, 40 * (r & 14) + 32, 3 * (4 * h + j), BAR(B_UVB));
            }
            {
              const uint2* mp = &G->modv[lane & 4 ? 0 : 2][40 * (r & 14) + (lane & 24) + 2 * (lane & 3)];
              uint4 v[3];
              int it = 0;
#pragma unroll 1
              do {
                v[0] = ld_relaxed128(mp); v[1] = ld_relaxed128(mp + 32); v[2] = ld_relaxed128(mp + 64 - (lane & 16));
              } while (__any_sync(~0u, ((v[0].x ^ epoch) | (v[0].y ^ epoch) | (v[0].z ^ epoch) | (v[0].w ^ epoch) | (v[1].x ^ epoch) | (v[1].y ^ epoch) | (v[1].z ^ epoch) | (v[1].w ^ epoch) |
                                        (v[2].x ^ epoch) | (v[2].y ^ epoch) | (v[2].z ^ epoch) | (v[2].w ^ epoch)) & 1) && ++it < SPIN_LIMIT);
#pragma unroll
              for (int i = 0; i < 3; i++)
                sts32(base + OFF_CO + 128 * i + 4 * lane, badd2(pack_bf16(__uint_as_float(v[i].x) + __uint_as_float(v[i].y), __uint_as_float(v[i].z) + __uint_as_float(v[i].w)), lane & 4 ? 0 : 0x3F803F80u));
            }
            fence_async_smem();
            __syncwarp();
            if (elect()) mbar_expect_tx(BAR(B_UVB), WSLOT);
          }
          mbar_wait(BAR(n < 2 ? B_FL + 3 + n : n == 2 ? B_PFULL + 4 : B_EMPTY + 2 * n - 5));
#pragma unroll 1
          for (int it = 0; !(rdy >> n & 1) && it < SPIN_LIMIT; it++) rdy = __ballot_sync(~0u, ld_relaxed32(G->xsh[min(lane >> 1, n ? 4 : P.aw)][(r & 6) + (lane & 1)]) == 64 * epoch) & (n ? ~0u : (4u << 2 * P.aw) - 1);
          if (elect()) {
            tma2d(base + OFF_A + s, &maps.xs, 128 * r + 64 * h, 64 * n, BAR(B_FULL + 2 * n));
            tma2d(base + OFF_A + ARING + s, &maps.xs, 128 * r + 64 - 64 * h, 64 * n, BAR(B_FULL + 2 * n));
          }
          s = s == 2 * ASLOT ? 0 : s + ASLOT;
        }
      } else {
        if (P.m3 < 5) mod_poll(G, base, P.m3, 1, epoch);
        float4 s = {};
        uint32_t ph = 0, pre = 0;
        mbar_wait(BAR(B_FL + 2));
        mbar_wait(BAR(B_PFULL + 3));
#pragma unroll 1
        for (int c = 0; c < 5; c = c == 1 ? 4 : c + 1) {
          if (c == 4) {
            ffn_role(h, j, r);
            mbar_wait(BAR(B_PEMPTY + 4));
            if (elect()) {
              mbar_expect_tx(BAR(B_UVE), 6144);
              tma3d(base + OFF_UVE, &maps.w1e + (r & 1), 0, 40 * (r & 14) + 64, 3 * (4 * h + j), BAR(B_UVE));
            }
          }
          strip<0, 1>(G, &maps.x1s, base, c, epoch, ph, pre, s);
        }
        mbar_wait(BAR(B_S3));
        const uint4 y = lds128(base + OFF_SX + 4096 + 16 * lane);
        const float s0 = s.x + __uint_as_float(y.x), q0 = s.y + __uint_as_float(y.y), s1 = s.z + __uint_as_float(y.z), q1 = s.w + __uint_as_float(y.w);
        ffn_role(h, j, r);
        asm volatile("{.reg .b128 t, x; .reg .b64 a, b; mov.b64 a, {%1,%2}; mov.b64 b, {%3,%4}; mov.b128 x, {a,b}; atom.relaxed.gpu.global.exch.b128 t, [%0], x;}"
                     ::"l"(&G->st2[2 * r + h][j][4 * lane]), "r"((__float_as_uint(s0) & ~1u) | (epoch & 1)), "f"(q0), "r"((__float_as_uint(s1) & ~1u) | (epoch & 1)), "f"(q1) : "memory");
        uint4* z = G->x1[~epoch & 1] + 1280 * bid + lane;
#pragma unroll 1
        for (int k = 0; k < 40; k++) st_relaxed128(z + 32 * k, 0, 0, 0, 0);
      }
    }
  } else if (wg == 2) {
    asm volatile("setmaxnreg.dec.sync.aligned.u32 40;");
    mbar_init<12>(BAR(B_FULL + 12 * w), 1);
    mbar_init<9>(BAR(B_EMPTY - 1 + 9 * w), 8);
    asm volatile("fence.mbarrier_init.release.cluster;" ::: "memory");
    LAUNCHES;
    const uint32_t epoch = EPOCH;
    cluster_wait();
#pragma unroll 1
    for (uint64_t prog = P.prog; prog; prog >>= 4) {
      REGION_IDS;
      const int s = (prog & 7) - 1;
      if (!(prog & 8)) {
        const uint32_t a = base + tab(T_KV, s) + 128 * (lane & 3) + ((w ^ (lane & 3)) << 4) + 4 * (lane & 16) + (lane & 12), keep = ~(lane & 1), bit = epoch & lane & 1;
        uint4* dst = G->xr + (128 * s + 64 * (bid & 1) + 8 * w + 2 * (lane & 16) + (lane >> 1 & 6)) * 256 + 255 - 4 * (bid >> 1) - (lane & 3);
        mbar_wait(BAR(B_KV));
        mbar_wait(BAR(B_KV + s));
        const uint4 wv = lds128(base + OFF_TAP + 512 * s + 64 * w + 16 * (lane & 16) + 4 * (lane & 12));
        uint32_t kk[11], r[8];
#pragma unroll
        for (int k = 0; k < 11; k++) kk[k] = k < 3 ? lds32((a ^ (64 * (k & 1))) + KV_H + 512 * k) : lds32((a ^ (64 * (~k & 1))) + 512 * (k - 3));
        if (elect()) red_hint(G->hint[s][4 * (bid & 1) + w]);
#pragma unroll
        for (int k = 0; k < 8; k++) r[k] = lds32((a ^ (64 * (k & 1))) + KV_V + 512 * k);
        const uint32_t w0 = __byte_perm(wv.x, wv.z, 0x5410), w1 = __byte_perm(wv.x, wv.z, 0x7632),
                       w2 = __byte_perm(wv.y, wv.w, 0x5410), w3 = __byte_perm(wv.y, wv.w, 0x7632);
#pragma unroll
        for (int k = 0; k < 8; k++) r[k] = bmul2(bfma2(kk[k + 3], w0, bfma2(kk[k + 2], w1, bfma2(kk[k + 1], w2, bmul2(kk[k], w3)))), r[k]);
        st_relaxed128(dst, (__byte_perm(r[7], r[6], 0x5410) & keep) | bit, __byte_perm(r[5], r[4], 0x5410), __byte_perm(r[3], r[2], 0x5410), __byte_perm(r[1], r[0], 0x5410));
        st_relaxed128(dst + 256, (__byte_perm(r[7], r[6], 0x7632) & keep) | bit, __byte_perm(r[5], r[4], 0x7632), __byte_perm(r[3], r[2], 0x7632), __byte_perm(r[1], r[0], 0x7632));
      } else if (s == 5) {
        mbar_wait(BAR(B_PFULL));
#pragma unroll
        for (int hf = 0; hf < 2; hf++) {
          const uint32_t a = base + tab(T_P, 0) + 16 * i0 + 2048 * hf;
          uint4 y = lds128(a);
          planes(a, y);
          sts128(a, y.x, y.y, y.z, y.w);
        }
      } else if (s >= 0) {
        const int tr = 4 * (lane & 1) + (lane >> 1 & 3);
        const uint32_t a = base + OFF_Q + 4096 * s + 128 * ((lane & 24) + tr) + ((w ^ tr) << 4);
        uint4* dst = G->qt + (128 * s + 64 * (bid & 1) + 8 * w + (lane >> 2)) * 256 + 4 * (bid >> 1) + (lane & 3);
        mbar_wait(BAR(B_Q + s));
#pragma unroll
        for (int k = 0; k < 2; k++) {
          uint32_t x[4];
          ldmatrix_x4_t(x, a ^ (64 * k));
          st_relaxed128(dst + 8192 * k, set_tag(x[0], ~lane & 1, epoch), x[1], x[2], x[3]);
        }
      } else if (w == 3) {
        row_stats(G, base, epoch);
      }
    }
    arrive1(BAR(B_QTD));
    {
      REGION_IDS;
      const uint32_t tag = opaque(~lane & 1);
      const uint32_t io = 16 * i0;
      uint4* gp = (uint4*)((char*)(G->xs + 256 * blockIdx.x) + io);
      constexpr int QO = -D_ * 256;
      const uint32_t sa = base + io;
      uint4 q[2];
      if (w == 0 && P.mr2 == 1) mr_poll(G, base, epoch);
      mbar_wait(BAR(B_QTOK));
      q[0] = ld_relaxed128(gp + QO);
      q[1] = ld_relaxed128(gp + QO + 128);
#pragma unroll 1
      for (int it = 0; it < SPIN_LIMIT; it++) {
        mbar_wait(BAR(B_MR), it & 1);
        const uint32_t x = lds32(sa + 16 * i0 + OFF_MR), y = lds32(sa + 16 * i0 + OFF_MR + 4096);
        sts32(sa + 16 * i0 + OFF_MR, x & 0xFFFF7FFFu);
        if (bar_all(3, !(((x >> 15 ^ epoch) | (y ^ epoch)) & 1))) break;
        if (w == 0 && elect()) { fence_async_smem(); mbar_expect_tx(BAR(B_MR), 8192); bulk_load(base + OFF_MR, G->st1, 8192, BAR(B_MR)); }
      }
#pragma unroll 1
      for (int c = 0; c < 5; c++) {
        mbar_wait(BAR(B_MODR + c));
        uint4 co = lds128(base + OFF_MODR + 16 * c);
        co.x = bmul2(co.x, co.z); co.y = bmul2(co.y, co.z);
        mbar_wait(BAR(B_PFULL + c));
        const uint32_t pb = io + (base + tab(T_P, c));
        gp = (uint4*)((char*)(G->xs + 256 * blockIdx.x + 32768 * c) + io);
#pragma unroll
        for (int hf = 0; hf < 2; hf++) {
#pragma unroll 1
          for (int it = 0; __any_sync(~0u, set_tag(q[hf].x, tag, epoch) != q[hf].x) && it < SPIN_LIMIT; it++) {
            q[hf] = ld_relaxed128(gp + QO + 128 * hf);
          }
          uint4 y = lds128(pb + 2048 * hf);
          if (c) planes(pb + 2048 * hf, y);
          const uint4 z = lds128(sa + OFF_MR + 2048 * hf), m = lds128(sa + OFF_MR + 2048 * hf + 4096);
          y.x = bfma2(bfma2(bfma2(q[hf].x, z.x, m.x), co.y, co.x), y.x, q[hf].x);
          if (hf) {
            __syncwarp();
            asm volatile("{.reg .pred p; elect.sync _|p, 0xffffffff; @p red.relaxed.gpu.global.add.u32 [%0], 1; @p mbarrier.arrive.shared::cta.b64 _, [%1];}"
                         ::"l"(G->xsh[c][2 * w + (blockIdx.x >> 6)]), "r"(BAR(B_PEMPTY + c)), "r"(y.x) : "memory");
          }
          y.y = bfma2(bfma2(bfma2(q[hf].y, z.y, m.y), co.y, co.x), y.y, q[hf].y);
          y.z = bfma2(bfma2(bfma2(q[hf].z, z.z, m.z), co.y, co.x), y.z, q[hf].z);
          y.w = bfma2(bfma2(bfma2(q[hf].w, z.w, m.w), co.y, co.x), y.w, q[hf].w);
          st_relaxed128(gp + 128 * hf, set_tag(bmul2(y.x, co.w), tag, epoch), bmul2(y.y, co.w), bmul2(y.z, co.w), bmul2(y.w, co.w));
          asm volatile("{.reg .pred p; .reg .b32 t; setp.ne.u32 p, %5, 0; max.u32 t, %1, 1; @!p st.relaxed.gpu.global.v4.u32 [%0+%6], {t,%2,%3,%4}; @p st.relaxed.gpu.global.v4.u32 [%0+%7], {t,%2,%3,%4};}"
                       ::"l"(gp + 128 * hf), "r"(y.x), "r"(y.y), "r"(y.z), "r"(y.w), "r"(epoch & 1), "n"(D_ * 4096), "n"(D_ * 8192) : "memory");
          if (c < 4) q[hf] = ld_relaxed128(gp + QO + 32768 + 128 * hf);
        }
      }
    }
    int h, j, r;
    ffn_role(h, j, r);
    {
      REGION_IDS;
      mbar_wait(BAR(B_UVB));
      float d[12] = {};
      fence_regs(d);
      wg_fence();
#pragma unroll
      for (int k = 0; k < 15; k++) {
        if (k == 12) { wg_commit(); mbar_wait(BAR(B_UVE)); wg_fence(); }
        wg_ss8_10(d + 4 * (k % 3), mkdesc(DB + (k < 12 ? OFF_UV + 12288 * (k / 6) + 4096 * (k % 3) + 2048 * (k / 3 & 1) : OFF_UVE + 2048 * (k % 3)), 16, 1024, 1),
                  mkdesc(DB + OFF_CO + 64 * (k / 3), 32, 128, 0), 1);
      }
      wg_commit();
      const int row = (r & 14) + (lane >> 2 & 1);
      uint32_t* dst = &G->uv[4 * h + j][32 * row + 4 * ((2 * w ^ row) & 6) + (lane & 3)];
      const uint32_t tag = !(lane & 3);
      wg_wait<0>();
      fence_regs(d);
      if (elect()) { red_hint(G->hint[8][4 * h + j]); mbar_arrive(BAR(B_UVD)); }
      uint32_t x[6];
#pragma unroll
      for (int k = 0; k < 6; k++) asm volatile("movmatrix.sync.aligned.m8n8.trans.b16 %0, %1;" : "=r"(x[k]) : "r"(pack_bf16(d[2 * k], d[2 * k + 1])));
      if (lane < 8) {
#pragma unroll
        for (int k = 0; k < 6; k++) st_relaxed32(dst + 512 * w_block(r & 1, k >> 1) + ((4 * k ^ lane) & 4), set_tag(x[k], tag, epoch));
      }
    }
    {
      REGION_IDS;
      if (w == 0) {
        int it = 0;
#pragma unroll 1
        while (__any_sync(~0u, ld_relaxed32(G->hint[8][4 * h + j]) != 64 * epoch) && ++it < SPIN_LIMIT);
        if (elect()) { mbar_expect_tx(BAR(B_BX), 12288); bulk_load(base + OFF_BX, G->uv[4 * h + j], 12288, BAR(B_BX)); }
      }
      const uint32_t* sp = &G->st2[2 * r + (h ^ (w >> 1))][0][2 * (i0 & 63)];
      uint2 x[4];
      int it = 0;
#pragma unroll 1
      do {
#pragma unroll
        for (int k = 0; k < 4; k++) x[k] = ld_relaxed64(sp + 128 * k);
      } while (__any_sync(~0u, ((x[0].x ^ epoch) | (x[1].x ^ epoch) | (x[2].x ^ epoch) | (x[3].x ^ epoch)) & 1) && ++it < SPIN_LIMIT);
      float m, sd;
      ln_final((__uint_as_float(x[0].x) + __uint_as_float(x[1].x)) + (__uint_as_float(x[2].x) + __uint_as_float(x[3].x)),
               (__uint_as_float(x[0].y) + __uint_as_float(x[1].y)) + (__uint_as_float(x[2].y) + __uint_as_float(x[3].y)), m, sd);
      const uint32_t e = pack_bf16(-m, sd);
      sts128(base + OFF_AX + 16 * i0, e, e, e, e);
      sts32(base + OFF_RT + 4 * i0, __float_as_uint(rcpf(sd)));
      fence_async_smem();
#pragma unroll 1
      for (it = 0; it < SPIN_LIMIT; it++) {
        mbar_wait(BAR(B_BX), it & 1);
        uint32_t y = 0;
#pragma unroll
        for (int k = 0; k < 6; k++) y |= lds32(base + OFF_BX + 16 * i0 + 2048 * k) ^ epoch;
        if (bar_all(3, !(y & 1))) break;
        if (w == 0 && elect()) { mbar_expect_tx(BAR(B_BX), 12288); bulk_load(base + OFF_BX, G->uv[4 * h + j], 12288, BAR(B_BX)); }
      }
      arrive1(BAR(B_EXT));
      {
        uint2 g0, g1;
        int it = 0;
#pragma unroll 1
        do {
          g0 = ld_relaxed64(&G->modv[1][128 * j + i0]);
          g1 = ld_relaxed64(&G->modv[1][512 + 32 * j + lane]);
        } while (__any_sync(~0u, ((g0.x ^ epoch) | (g0.y ^ epoch) | (g1.x ^ epoch) | (g1.y ^ epoch)) & 1) && ++it < SPIN_LIMIT);
        const uint32_t ga = base + OFF_GB + 80 * (lane >> 1 & 3) + 2 * (lane & 1) + (lane >> 3) * 4;
        asm volatile("st.shared.u16 [%0], %1;" ::"r"(ga + 16 * (w ^ (j & 1))), "h"((uint16_t)(mod_sum(g0) >> 16)) : "memory");
        asm volatile("st.shared.u16 [%0], %1;" ::"r"(ga + 64), "h"((uint16_t)(mod_sum(g1) >> 16)) : "memory");
        arrive1(BAR(B_GB));
      }
      const int id = 16 * r + 4 * h + fslice(j, w);
      const unsigned* fp = &G->hhf[8 * id + 64 * (lane & 1)];
#pragma unroll 1
      for (int q = w == 3 ? 3 : 0; q < 3; q++) {
        const int m = 3 * q + w;
        const uint4* src = G->hh + id * 1536 + 512 * q;
        it = 0;
#pragma unroll 1
        while (__any_sync(~0u, ld_relaxed32(fp + q) != 4 * epoch) && ++it < SPIN_LIMIT);
        mbar_wait(BAR(P.hid[2][m]));
        if (elect()) {
          bulk_load(base + OFF_A + h * ARING + P.hid[h][m], src, ASLOT, BAR(B_FULL + 23 + m));
          bulk_load(base + OFF_A + ARING - h * ARING + P.hid[h ^ 1][m], src + 8 * 1536, ASLOT, BAR(B_FULL + 23 + m));
        }
      }
    }
  } else {
    asm volatile("setmaxnreg.inc.sync.aligned.u32 224;");
    LAUNCHES;
    uint32_t par = EPOCH & 1;
    cluster_wait();
    uint32_t ck = 0;
    {
      float acc[128];
      uint32_t A[64];
#pragma unroll
      for (int i = 0; i < 64; i++) A[i] = 0;
      int c = wg;
#pragma unroll 1
      for (uint64_t prog = P.cprog[wg]; prog; prog >>= 8) {
        REGION_IDS;
        const int s = prog & 7;
        if (s < 5) {
          const uint32_t a = base + tab(T_KV, s) + 128 * (lane & 3) + ((w ^ (lane & 3)) << 4) + 4 * (lane & 16) + (lane & 12), keep = ~(lane & 1), bit = par & lane;
          uint4* dst = G->xr + (128 * s + 64 * (bid & 1) + 8 * w + 2 * (lane & 16) + (lane >> 1 & 6)) * 256 + 255 - 4 * (bid >> 1) - (lane & 3);
          mbar_wait(BAR(B_KV));
          mbar_wait(BAR(B_KV + s));
          const uint4 wv = lds128(base + OFF_TAP + 512 * s + 64 * w + 16 * (lane & 16) + 4 * (lane & 12));
          uint32_t kk[11], r[8];
#pragma unroll
          for (int k = 0; k < 11; k++) kk[k] = k < 3 ? lds32((a ^ (64 * (k & 1))) + KV_H + 512 * k) : lds32((a ^ (64 * (~k & 1))) + 512 * (k - 3));
          if (elect()) red_hint(G->hint[s][4 * (bid & 1) + w]);
#pragma unroll
          for (int k = 0; k < 8; k++) r[k] = lds32((a ^ (64 * (k & 1))) + KV_V + 512 * k);
          const uint32_t w0 = __byte_perm(wv.x, wv.z, 0x5410), w1 = __byte_perm(wv.x, wv.z, 0x7632),
                         w2 = __byte_perm(wv.y, wv.w, 0x5410), w3 = __byte_perm(wv.y, wv.w, 0x7632);
#pragma unroll
          for (int k = 0; k < 8; k++) r[k] = bmul2(bfma2(kk[k + 3], w0, bfma2(kk[k + 2], w1, bfma2(kk[k + 1], w2, bmul2(kk[k], w3)))), r[k]);
          st_relaxed128(dst, (__byte_perm(r[7], r[6], 0x5410) & keep) | bit, __byte_perm(r[5], r[4], 0x5410), __byte_perm(r[3], r[2], 0x5410), __byte_perm(r[1], r[0], 0x5410));
          st_relaxed128(dst + 256, (__byte_perm(r[7], r[6], 0x7632) & keep) | bit, __byte_perm(r[5], r[4], 0x7632), __byte_perm(r[3], r[2], 0x7632), __byte_perm(r[1], r[0], 0x7632));
        }
        if (prog & 8) {
          float s0 = 0.f, s1 = 0.f, q0 = 0.f, q1 = 0.f;
          const uint32_t a = OFF_Q + 1024 * w + 128 * (lane & 7) + (((lane >> 3) ^ (lane & 7)) << 4);
          const uint32_t ra = mapa(base + OFF_ST + 128 * (bid & 1) + 64 * (lane & 1) + 16 * w + 8 * (lane >> 2), lane >> 1 & 1), rb = mapa(BAR(B_ST1), lane >> 1 & 1);
          if (w == 3 && elect()) mbar_expect_tx(BAR(B_ST1), 256);
#pragma unroll 1
          for (int k = 0; k < 5; k++) {
            mbar_wait(BAR(B_Q + k));
            const uint32_t o = opaque(base + 4096 * k);
            const uint4 x = lds128(o + a), y = lds128(o + (a ^ 64));
            const uint32_t e[8] = {x.x, x.y, x.z, x.w, y.x, y.y, y.z, y.w};
#pragma unroll
            for (int i = 0; i < 8; i++) { const float lo = bf_lo(e[i]), hi = bf_hi(e[i]); s0 += lo; s1 += hi; q0 = fmaf(lo, lo, q0); q1 = fmaf(hi, hi, q1); }
          }
          s0 += s1; q0 += q1;
          s0 += __shfl_xor_sync(~0u, s0, 8); q0 += __shfl_xor_sync(~0u, q0, 8);
          s0 += __shfl_xor_sync(~0u, s0, 16); q0 += __shfl_xor_sync(~0u, q0, 16);
          if (lane < 8) asm volatile("st.async.shared::cluster.mbarrier::complete_tx::bytes.v2.b32 [%0], {%1,%2}, [%3];" ::"r"(ra), "r"(__float_as_uint(s0)), "r"(__float_as_uint(q0)), "r"(rb) : "memory");
        }
        if (prog & 32) {
          const int L = 16 * w + (lane >> 2) + 2 * (lane & 3) - 7;
          const uint32_t fo = base + ((L & 1) ? F_O + 2 * (L + 1) : F_E + 2 * L);
          mbar_wait(BAR(B_FRDY + c));
          cload<0, 0>(A, fo + tab(T_F, c));
          cload<15, 1>(A, fo + tab(T_F, c));
          arrive1(BAR(B_FL + c));
        }
        if (!(prog & 64)) continue;
        uint32_t xo;
        if (P.turn >> c & 1) mbar_wait(BAR(B_TURN - 3 + c));
        if (c == 0) mbar_wait(BAR(P.c0));
#pragma unroll 1
        for (int it = 0; it < SPIN_LIMIT; it++) {
          xo = tab(T_X, opaque(c));
          mbar_wait(BAR(B_XR + c), it & 1);
          const uint32_t tag = lds32(base + xo + 32 * i0);
          wg_fence();
          csteps<0, 0>(acc, A, mkdesc(DB + xo, 16, 128, 0));
          csteps<15, 6>(acc, A, mkdesc(DB + xo, 16, 128, 0));
          wg_commit();
          if (bar_all(1 + wg, !((tag ^ par) & 1))) break;
          wg_wait<0>();
          if (w == 0 && elect()) { mbar_expect_tx(BAR(B_XR + c), 4096); bulk_load(base + xo, G->xr + (128 * c + bid) * 256, 4096, BAR(B_XR + c)); }
        }
        wg_fence();
        csteps<5, 1>(acc, A, mkdesc(DB + tab(T_X, opaque(c)), 16, 128, 0));
        wg_commit();
        if (c >= 2 && c < 4 && elect()) mbar_arrive(BAR(B_TURN - 2 + c));
        if (c >= 3) mbar_wait(BAR(B_PEMPTY + c - 3));
        wg_wait<0>();
        fence_regs(acc);
        ck = base + OFF_A + wg * ARING + lane * 128 + (((2 * w) ^ (lane & 7)) << 4);
        const uint32_t pb = base + tab(T_P, c) + 4096 * w;
#pragma unroll
        for (int k = 0; k < 8; k++) {
          uint32_t p[4];
#pragma unroll
          for (int e = 0; e < 4; e++) { const int i = 4 * k + e; p[e] = i < 31 ? pack_bf16(acc[4 * i] + acc[4 * i + 6], acc[4 * i + 1] + acc[4 * i + 7]) : pack_bf16(acc[124], acc[125]); }
          if (k == 0 && (lane & 3) < w) p[0] = 0;
          stmatrix_x4_t(k == 0 ? pb + 16 * ((255 - lane + 2 * w) & 255) : pb + 16 * (255 - lane + 2 * w) - 512 * k, p[0], p[1], p[2], p[3]);
        }
        arrive1(BAR(B_PFULL + c));
        c += 2;
      }
    }
    const uint32_t abd = DB + OFF_A + wg * ARING;
    auto a_tile = [&](int as, int n, bool first) {
#pragma unroll 1
      for (int it = 0; __any_sync(~0u, ((lds32(ck + as) ^ par) | (lds32(ck + as + (first ? 4096 : 256)) ^ par)) & 1) && it < SPIN_LIMIT; it++) {
        int h, j, r;
        ffn_role(h, j, r);
        if (elect()) {
          const uint32_t dst = base + OFF_A + wg * ARING + as;
          mbar_expect_tx(BAR(B_RETRY + wid), ASLOT);
          if (first) tma2d(dst, &maps.xs, 128 * r + 64 * (h ^ wg), 64 * n, BAR(B_RETRY + wid));
          else bulk_load(dst, G->hh + ((2 * r + (h ^ wg)) * 8 + 4 * h + fslice(j, n % 3)) * 1536 + (n / 3) * 512, ASLOT, BAR(B_RETRY + wid));
        }
        mbar_wait(BAR(B_RETRY + wid), par >> 1);
        par ^= 2;
      }
    };
    float acc[192];
    int ws = 0, as = 0;
#pragma unroll 1
    for (int u = 0; u < 20 - NT; u++) {
      mbar_wait(BAR(B_FULL + u));
      if (!(u & 1)) a_tile(as, u >> 1, true);
      wg_fence();
#pragma unroll
      for (int k = 0; k < 4; k++) wg_ss192_11(acc + 96 * (k & 1), mkdesc(abd + as + k / 2 * 2048, 16, 1024, 1), mkdesc(DB + ws + 12288 * (k & 1) + k / 2 * 2048, 4096, 1024, 1), u + k / 2);
      wg_commit();
      wg_wait<1>();
      if (elect()) mbar_arrive(BAR(B_EMPTY + u - 1));
      ws = next_slot(ws);
      as = as == 5 * ASLOT / 2 ? 0 : as + ASLOT / 2;
    }
    auto tail = [&](int v, int i) {
      const int u = 20 - NT + i / 2;
      if (i < 2 * NT) wg_ss192_11(acc + 96 * v, mkdesc(opaque(abd) + u % 6 * 4096 + (i & 1) * 2048, 16, 1024, 1), mkdesc(DB + u % 5 * WSLOT + (i & 1) * 2048 + 12288 * v, 4096, 1024, 1), 1);
      if (i == 2 * NT) wg_ss192_01(acc + 96 * v, mkdesc(DB + OFF_AX + 1024 * opaque(wg), 0, 128, 0), mkdesc(DB + OFF_BX + 6144 * v, 2048, 1024, 1), 1);
    };
#pragma unroll
    for (int u = 20 - NT; u <= 20; u++) {
      mbar_wait(BAR(u < 20 ? B_FULL + u : B_EXT));
      if (u == 16 || u == 18) a_tile(u % 6 * 4096, u >> 1, true);
      wg_fence();
      tail(0, 2 * (u + NT - 20));
      tail(0, 2 * (u + NT - 20) + 1);
      wg_commit();
      if (u == 20 - NT) { wg_wait<1>(); if (elect()) mbar_arrive(BAR(B_EMPTY + u - 1)); }
    }
    float o[80];
    uint32_t fr[3][16], bo;
    {
      int h, j, r;
      ffn_role(h, j, r);
      REGION_IDS;
      const float r0 = 0.5f * __uint_as_float(lds32(base + OFF_RT + 256 * wg + 64 * w + (lane & 28))), r1 = 0.5f * __uint_as_float(lds32(base + OFF_RT + 256 * wg + 64 * w + 32 + (lane & 28)));
      const int id = (2 * r + (h ^ wg)) * 8 + 4 * h + j;
      uint4* const hdst = G->hh + id * 1536 + 128 * w + (lane ^ lane >> 3);
      const uint32_t keep = ~(~lane & 1), bit = par & ~keep;
      bo = 1024 + ((j & 1) << 23);
      auto own = [&](int i) { wg_rs160_1(o, fr[i >> 2] + 4 * (i & 3), mkdesc(DB + (5 + i / 4) % 6 * WSLOT + (i & 3) * 2048, 8192, bo, 1), i); };
      auto gate = [&](float* g, int d) {
#pragma unroll
        for (int e = 0; e < 4; e++) { g[e] *= e < 2 ? r0 : r1; g[e + d] *= g[e]; asm("tanh.approx.f32 %0, %0;" : "+f"(g[e])); }
      };
      auto mix = [&](uint32_t* x, const float* g, int d) {
        x[0] = pack_bf16(fmaf(g[d], g[0], g[d]), fmaf(g[d + 1], g[1], g[d + 1]));
        x[1] = pack_bf16(fmaf(g[d + 2], g[2], g[d + 2]), fmaf(g[d + 3], g[3], g[d + 3]));
      };
      auto hint = [&](int v) { asm volatile("{.reg .pred p; setp.eq.u32 p, %1, 0; @p red.relaxed.gpu.global.add.u32 [%0], 1;}" ::"l"(&G->hhf[id * 8 + v]), "r"(lane) : "memory"); };
      auto put = [&](int v, int k) {
        uint32_t* x = fr[v] + 2 * k;
        const uint32_t t0 = (x[k / 2] & keep) | bit, t1 = (x[5 + k / 2] & keep) | bit;
        if (!v) { x[k / 2] = t0; x[5 + k / 2] = t1; }
        st_relaxed128(hdst + 512 * v + 8 * k, k ? x[0] : t0, k ? t0 : x[2], x[4], x[6]);
        st_relaxed128(hdst + 512 * v + 8 * k + 64, x[1], x[3], k ? x[5] : t1, k ? t1 : x[7]);
      };
      auto move = [&](uint32_t* x) {
#pragma unroll
        for (int k = 0; k < 16; k++) asm volatile("mul.rn.f32 %0, %0, %1;" : "+r"(x[k]) : "f"(P.one));
      };
      wg_fence();
#pragma unroll
      for (int i = 0; i < NP; i++) tail(1, i);
      if (NP) wg_commit();
      wg_wait<NP ? 1 : 0>();
#pragma unroll
      for (int k = 0; k < 96; k++) asm volatile("" : "+f"(acc[k])::"memory");
      if (elect()) mbar_arrive(BAR(B_EMPTY + 18));
      gate(acc + 28, 32);
#pragma unroll
      for (int g = 0; g < 8 + NB; g++) {
        const int k = 7 - g, i = (g - P0) / ST + NP;
        const bool mm = g >= P0 && (g - P0) % ST == 0;
        if (mm && i <= 7) split(P.zero, g);
        if (mm && i == 0) wg_fence();
        if (mm && i < 7) tail(1, i);
        if (mm && i == 6) wg_commit();
        if (g < 8) {
          if (k) gate(acc + 4 * k - 4, 32);
          mix(fr[0] + 2 * k, acc + 4 * k, 32);
          if (k == 4) hint(0);
          if (!(k & 3)) put(0, k);
          if (!k) move(fr[0]);
        } else {
#pragma unroll
          for (int e = 0; e < 4; e++) acc[96 + 4 * k + e] = silu2(acc[96 + 4 * k + e] * (e < 2 ? r0 : r1));
        }
      }
      static_assert(P0 + ST * (6 - NP) < 8 + NB, "all products are issued");
      split(P.zero, 14);
      wg_wait<0>();
#pragma unroll
      for (int k = 96; k < 192; k++) asm volatile("" : "+f"(acc[k])::"memory");
      if (elect()) mbar_arrive(BAR(B_EMPTY + 19));
#pragma unroll
      for (int k = 7 - NB; k >= 0; k--) gate(acc + 64 + 4 * k, 96);
      mbar_wait(BAR(B_FULL + 20));
      mbar_wait(BAR(B_FULL + 21));
#pragma unroll
      for (int k = 7; k >= 0; k--) {
        const float* g = acc + 64 + 4 * k;
        if (k < 8 - NB) mix(fr[1] + 2 * k, g, 96);
        else { fr[1][2 * k] = pack_bf16(g[0] * g[96], g[1] * g[97]); fr[1][2 * k + 1] = pack_bf16(g[2] * g[98], g[3] * g[99]); }
      }
#pragma unroll
      for (int k = 0; k < 4; k++) pin4(P.zero, fr[1] + 4 * k);
      if (PA) { put(1, 4); hint(1); }
      if (PA == 2) put(1, 0);
      if (PA) split(P.zero, 31);
      wg_fence();
      own(0);
      own(1);
      split(P.zero, 15);
      if (!PA) { put(1, 4); hint(1); }
      if (!O3) own(2);
      if (PA < 2) put(1, 0);
      if (!O3) { own(3); wg_commit(); }
      gate(acc + 124, 32);
#pragma unroll
      for (int g = 0; g < 8; g++) {
        const int k = 7 - g, i = (g - O0) / OS + (O3 ? 2 : 4);
        const bool mm = g >= O0 && (g - O0) % OS == 0 && i < 8;
        if (mm || g == 0) split(P.zero, 16 + k);
        if (mm) own(i);
        if (mm && (i == 3 || i == 5 || i == 7)) wg_commit();
        if (mm && i == 5) { wg_wait<1>(); if (elect()) mbar_arrive(BAR(B_EMPTY + 20)); }
        if (k) gate(acc + 92 + 4 * k, 32);
        mix(fr[2] + 2 * k, acc + 96 + 4 * k, 32);
        if (k == 1) hint(2);
        if (!(k & 3)) put(2, k);
      }
      static_assert(O0 + OS * (O3 ? 5 : 3) < 8, "all products are issued");
      mbar_wait(BAR(B_FULL + 22));
      wg_fence();
#pragma unroll
      for (int i = 8; i < 12; i++) own(i);
      wg_commit();
      wg_wait<1>();
      if (elect()) mbar_arrive(BAR(B_EMPTY + 21));
      ck = base + OFF_A + wg * ARING + 2048 * w + 516 * (lane >> 3) + 144 * (lane >> 2 & 1) + 32 * (lane & 3);
    }
    uint32_t x1[40];
    if (!wg) {
      REGION_IDS;
      const uint32_t xa = base + (lane >> 4) * 1024 + (lane & 7) * 128 + (((2 * w + ((lane >> 3) & 1)) ^ (lane & 7)) << 4);
      mbar_wait(BAR(B_FULL + 32));
#pragma unroll
      for (int k = 0; k < 10; k++) ldmatrix_x4_t(x1 + 4 * k, xa + (k < 6 ? OFF_X1 + k / 2 * WSLOT + (k & 1) * 2048 : OFF_SX + 2048 * (k - 6)));
    }
#pragma unroll 1
    for (int u = 23; u < (wg ? 32 : LAG2); u++) {
      as = P.hid[wg][u - 23];
      const uint64_t wd = mkdesc(0, 0, bo, 1) | P.w2t[u - 20].x;
      mbar_wait(BAR(B_FULL + u));
      a_tile(as, u - 23, false);
      wg_fence();
#pragma unroll
      for (int kk = 0; kk < 4; kk++) wg_ss160_01(o, mkdesc(abd + as + kk / 2 * 512 + (kk & 1) * 32, 16, 1024, 2), wd + kk * 128, 1);
      wg_commit();
      if (u == 31 && elect()) mbar_arrive(BAR(B_LAG));
      wg_wait<1>();
      if (elect()) mbar_arrive(BAR(B_EMPTY + u - 1));
    }
    int h, j, r;
    ffn_role(h, j, r);
    REGION_IDS;
    const uint32_t xb = base + OFF_XCH + 5120 * w;
    if (wg) {
      const uint32_t rdst = mapa(xb + 16 * lane, h ^ 1), rbar = mapa(BAR(B_FULL), h ^ 1);
      mbar_wait(BAR(B_XFREE));
      wg_wait<0>();
      fence_regs(o);
#pragma unroll
      for (int k = 0; k < 10; k++)
        asm volatile("st.async.shared::cluster.mbarrier::complete_tx::bytes.v4.b32 [%0], {%1,%2,%3,%4}, [%5];" ::"r"(rdst + 512 * k), "r"(pack_bf16(o[8 * k], o[8 * k + 1])),
                     "r"(pack_bf16(o[8 * k + 2], o[8 * k + 3])), "r"(pack_bf16(o[8 * k + 4], o[8 * k + 5])), "r"(pack_bf16(o[8 * k + 6], o[8 * k + 7])), "r"(rbar + 8 * (k / 4)) : "memory");
    } else {
      uint32_t gr[40];
      const float r0 = __uint_as_float(lds32(base + OFF_RT + 64 * w + (lane & 28))), r1 = __uint_as_float(lds32(base + OFF_RT + 64 * w + 32 + (lane & 28)));
      const uint32_t p0 = pack_bf16(r0, r0), p1 = pack_bf16(r1, r1), q0 = pack_bf16(r0 - bf_lo(p0), r0 - bf_lo(p0)), q1 = pack_bf16(r1 - bf_lo(p1), r1 - bf_lo(p1));
      mbar_wait(BAR(B_GB));
#pragma unroll
      for (int k = 0; k < 5; k++) {
        const uint4 g = lds128(base + OFF_GB + 80 * (lane & 3) + 16 * k);
        gr[8 * k] = g.x; gr[8 * k + 2] = g.y; gr[8 * k + 4] = g.z; gr[8 * k + 6] = g.w;
      }
      auto scale = [&](int k) {
#pragma unroll
        for (int e = 4 * k; e < 4 * k + 4; e += 2) { gr[e + 1] = bfma2(gr[e], p1, bmul2(gr[e], q1)); gr[e] = bfma2(gr[e], p0, bmul2(gr[e], q0)); }
      };
#pragma unroll
      for (int k = max(127 - 4 * LAG2, 0); k < 10; k++) scale(k);
      wg_wait<0>();
      if (elect()) mbar_arrive(BAR(B_EMPTY + LAG2 - 1));
#pragma unroll 1
      for (int u = LAG2; u < 32; u++) {
        mbar_wait(BAR(B_FULL + u));
        a_tile(P.hid[0][u - 23], u - 23, false);
      }
      auto da = [&](int i) { return mkdesc(DB + hid_at(i / 4 + LAG2 - 23, 0) + (i & 2) * 256 + (i & 1) * 32, 16, 1024, 2); };
      auto db = [&](int i, int b) { return mkdesc(DB + w2_at(i / 4 + LAG2 - 20) + b * w2_step(i / 4 + LAG2 - 20) + (i & 3) * 2048, w2_step(i / 4 + LAG2 - 20), bo, 1); };
      const int row = 128 * r + 64 * h + 16 * w;
      auto merge = [&](int e) {
        if (e % 4 == 0) mbar_wait_cluster(BAR(B_FULL + e / 4), 1);
        const uint4 p = lds128(xb + 16 * lane + 512 * e);
        x1[4 * e] = bfma2(gr[4 * e], p.x, x1[4 * e]); x1[4 * e + 1] = bfma2(gr[4 * e + 1], p.y, x1[4 * e + 1]);
        x1[4 * e + 2] = bfma2(gr[4 * e + 2], p.z, x1[4 * e + 2]); x1[4 * e + 3] = bfma2(gr[4 * e + 3], p.w, x1[4 * e + 3]);
      };
      auto out = [&](int k) {
        const float* v = o + 8 * k;
        uint32_t y[4];
#pragma unroll
        for (int e = 0; e < 4; e++) y[e] = bfma2(gr[4 * k + e], pack_bf16(v[2 * e], v[2 * e + 1]), x1[4 * k + e]);
        stmatrix_x4(k < 8 ? xb + 2048 * (k >> 2) + (lane & 15) * 128 + (((2 * (k & 3) + (lane >> 4)) ^ (lane & 7) ^ 4 * (j & 1)) << 4)
                          : xb + 4096 + (lane & 15) * 64 + (((2 * (k & 1) + (lane >> 4)) ^ (lane >> 1 & 3)) << 4), y[0], y[1], y[2], y[3]);
        if ((k & 3) == 3 || k == 9) {
          fence_async_smem();
          __syncwarp();
          if (lane == 0) tma2d_store(k < 8 ? &maps.outa : &maps.outb, k < 8 ? 128 * j + 64 * (k >> 2) : 512 + 32 * j, row, xb + 2048 * (k >> 2));
        }
      };
      constexpr int ND = 128 - 4 * LAG2;
      mbar_wait(BAR(B_LAG));
      wg_fence();
#pragma unroll
      for (int i = 0; i < ND; i++) {
        wg_ss160_01(o, da(i), db(i, 0), 1);
        if (i >= 1 && i <= 10) { scale(i - 1); split(P.zero, 32 + i); }
      }
      wg_commit();
#pragma unroll
      for (int e = 0; e < MG; e++) merge(e);
      __syncwarp();
      wg_wait<0>();
      fence_regs(o);
#pragma unroll
      for (int k = 0; k < 10; k++) {
        if (k >= MG && k % 4 == 0) {
#pragma unroll
          for (int e = k; e < min(k + 4, 10); e++) merge(e);
          __syncwarp();
        }
        out(k);
      }
      if (lane == 0) { bulk_commit(); bulk_wait_read(); }
    }
  }
}

typedef CUresult (*EncFn)(CUtensorMap*, CUtensorMapDataType, cuuint32_t, void*, const cuuint64_t*, const cuuint64_t*, const cuuint32_t*,
                          const cuuint32_t*, CUtensorMapInterleave, CUtensorMapSwizzle, CUtensorMapL2promotion, CUtensorMapFloatOOBfill);
static int enc_err = 0;
static void enc(EncFn fn, CUtensorMap* m, const void* p, int rank, const cuuint64_t* gd, const cuuint64_t* gs, const cuuint32_t* bd, CUtensorMapSwizzle sw) {
  cuuint32_t es[5] = {1, 1, 1, 1, 1};
  enc_err = 2 * enc_err + (fn(m, CU_TENSOR_MAP_DATA_TYPE_BFLOAT16, rank, (void*)p, gd, gs, bd, es, CU_TENSOR_MAP_INTERLEAVE_NONE, sw,
                              CU_TENSOR_MAP_L2_PROMOTION_L2_128B, CU_TENSOR_MAP_FLOAT_OOB_FILL_NONE) != CUDA_SUCCESS);
}

extern "C" void kernel_launch(void* const* d_in, const int* in_sizes, int n_in, void* d_out, int out_size) {
  const bf16 *q = (const bf16*)d_in[0], *k = (const bf16*)d_in[1], *v = (const bf16*)d_in[2], *shift = (const bf16*)d_in[3],
             *ssmk = (const bf16*)d_in[4], *ssmd = (const bf16*)d_in[5], *w1 = (const bf16*)d_in[7], *w3 = (const bf16*)d_in[8],
             *w2 = (const bf16*)d_in[9], *c = (const bf16*)d_in[10], *wmod = (const bf16*)d_in[11];
  EncFn fn = nullptr;
  cudaDriverEntryPointQueryResult qr;
  cudaGetDriverEntryPoint("cuTensorMapEncodeTiled", (void**)&fn, cudaEnableDefault, &qr);
  Scratch* pg;
  cudaGetSymbolAddress((void**)&pg, g_s);
  Maps maps;
  enc_err = 0;
  const CUtensorMapSwizzle S128 = CU_TENSOR_MAP_SWIZZLE_128B;
  { cuuint64_t gd[3] = {D_, S_ / 8, 8}, gs[2] = {D_ * 16, D_ * 2}; cuuint32_t b[3] = {64, 4, 8};
    enc(fn, &maps.km, k, 3, gd, gs, b, S128);
    enc(fn, &maps.v, v, 3, gd, gs, b, S128);
    enc(fn, &maps.q, q, 3, gd, gs, b, S128);
    b[2] = 3;
    enc(fn, &maps.kh, k, 3, gd, gs, b, S128); }
  { cuuint64_t gd[3] = {256, 2, 5}, gs[2] = {512, 1024}; cuuint32_t b[3] = {256, 1, 5};
    enc(fn, &maps.tap, shift, 3, gd, gs, b, CU_TENSOR_MAP_SWIZZLE_NONE); }
  { cuuint64_t gd[3] = {6 * D_, D_, 1}, gs[2] = {6 * D_ * 2, 6 * D_ * 2 * D_}; cuuint32_t b[3] = {64, 64, 1};
    enc(fn, &maps.wm, wmod, 3, gd, gs, b, S128); }
  { cuuint64_t gd[3] = {64, D_, F_ / 64}, gs[2] = {F_ * 2, 128}; cuuint32_t b[3] = {64, 32, 3};
    enc(fn, &maps.w1, w1, 3, gd, gs, b, S128);
    enc(fn, &maps.w3, w3, 3, gd, gs, b, S128);
    b[1] = 16;
    enc(fn, &maps.w1e, w1, 3, gd, gs, b, S128);
    enc(fn, &maps.w3e, w3, 3, gd, gs, b, S128);
    b[1] = 32; b[2] = 1;
    enc(fn, &maps.w1s, w1, 3, gd, gs, b, S128);
    enc(fn, &maps.w3s, w3, 3, gd, gs, b, S128); }
  { cuuint64_t gd[2] = {S_, D_}, gs[1] = {S_ * 2}; cuuint32_t b1[2] = {64, 64}, b2[2] = {64, 32};
    enc(fn, &maps.xs, pg->xs, 2, gd, gs, b1, S128);
    gd[1] = 2 * D_;
    enc(fn, &maps.x1b, pg->x1, 2, gd, gs, b2, S128);
    enc(fn, &maps.x1s, pg->x1, 2, gd, gs, b2, CU_TENSOR_MAP_SWIZZLE_NONE); }
  { cuuint64_t gd[5] = {D_, 2, 4, 4, 48}, gs[4] = {D_ * 2, D_ * 4, D_ * 16, D_ * 64}; cuuint32_t b[5] = {64, 2, 4, 4, 2};
    enc(fn, &maps.w2a, w2, 5, gd, gs, b, S128);
    gs[1] = D_ * 16; gs[2] = D_ * 4;
    enc(fn, &maps.w2b, w2, 5, gd, gs, b, S128); }
  { cuuint64_t gd[2] = {D_, S_}, gs[1] = {D_ * 2}; cuuint32_t b1[2] = {64, 16}, b2[2] = {32, 16};
    enc(fn, &maps.outa, d_out, 2, gd, gs, b1, S128);
    enc(fn, &maps.outb, d_out, 2, gd, gs, b2, CU_TENSOR_MAP_SWIZZLE_64B); }
  if (enc_err) return;
  cudaFuncSetAttribute(k_fused, cudaFuncAttributeMaxDynamicSharedMemorySize, SMEM_BYTES);
  cudaLaunchConfig_t cfg = {132, 512, SMEM_BYTES};
  cudaLaunchAttribute at = {cudaLaunchAttributeClusterDimension};
  at.val.clusterDim.x = 2; at.val.clusterDim.y = at.val.clusterDim.z = 1;
  cfg.attrs = &at; cfg.numAttrs = 1;
  int nc = 0;
  cudaOccupancyMaxActiveClusters(&nc, k_fused, &cfg);
  Ptrs P = {ssmk, c, ssmd, pg, 0xE48DCBA9ull, {0x676760, 0x64620F01}, 0, 700, 420, 5500, 0, 0, 0x20400, 0, 6, B_KV, 0, 0, 2, 1, 0x57C00, 1.f};
  const char* sched = "k10v14f04q04q14q24q34q44k24v24f14k34v34f24k44v44f34f44";
  int t = 700, pace = 440;
  for (int e = 0; e < NE; e++) {
    const char x = sched[3 * e];
    const int r = sched[3 * e + 1] - '0', kind = x == 'k' ? 0 : x == 'v' ? 1 : x == 'q' ? 2 : x == 'f' ? 3 : 4;
    t += (sched[3 * e + 2] - '0') * pace / 4;
    P.sched[e] = make_uint2(t | kind << 16 | r << 20, (kind < 2 ? tab(T_KV, r) + kind * KV_V : kind == 2 ? OFF_Q + 4096 * r : tab(T_F, r) + F_E) | (r + (kind < 2 ? B_KV : kind == 2 ? B_Q : B_FRAW)) << 18);
  }
  const int wt[5] = {12000, 14100, 14500, 15000, 16400};
  for (int u = 0; u < 5; u++) P.wt[u] = wt[u];
  const int dep[5] = {B_FL + 1, B_FL + 2, B_PFULL + 2, B_FL + 1, B_PEMPTY + 2};
  for (int u = 0; u < 20; u++) P.wdep[u] = u % 5 * WSLOT | (~u & 1) << 12 | (u < 5 ? dep[u] : B_EMPTY + u - 5);
  for (int v = 0; v < 12; v++) P.w2t[v] = make_uint2(w2_desc(v), v ? B_EMPTY + (v > 5 ? 15 + v : v > 3 ? 14 + v : v > 1 ? 16 : 15) : B_UVD);
  for (int m = 0; m < 9; m++) { P.hid[0][m] = hid_at(m, 0) - OFF_A; P.hid[1][m] = hid_at(m, 1) - OFF_A - ARING; P.hid[2][m] = B_EMPTY + 19 + (m > 2 ? m : m / 2); }
  if (nc < 66) { P.boff = 128; k_fused<<<4, 512, SMEM_BYTES, cudaStreamPerThread>>>(P, maps); P.boff = 0; }
  k_fused<<<nc < 66 ? 128 : 132, 512, SMEM_BYTES, cudaStreamPerThread>>>(P, maps);
}
```
